```python
import torch

def _softmax(x, axis=-1):
    return torch.softmax(x, dim=axis)

def _gelu(x):
    return torch.nn.functional.gelu(x, approximate='tanh')

def _silu(x):
    return torch.nn.functional.silu(x)

def _sigmoid(x):
    return torch.sigmoid(x)

def _layernorm(x, axis=-1, eps=1e-05):
    m = x.mean(dim=axis, keepdim=True)
    v = x.var(dim=axis, keepdim=True, unbiased=False)
    return (x - m) / torch.sqrt(v + eps)

def _scatter_add(tgt, idx, src, axis=0):
    return tgt.clone().index_add_(axis, idx, src)

def _segment_sum(src, seg, n):
    out = torch.zeros((n,) + src.shape[1:], dtype=src.dtype)
    return out.index_add_(0, seg, src)

def _pad(x, pw):
    flat = tuple((v for pair in reversed(pw) for v in pair))
    return torch.nn.functional.pad(x, flat)
kernel_name = 'standalone__molecular_angular_painn__graph'

def setup_inputs():

    _w = lambda a: (lambda t: t.to(torch.bfloat16) if t.is_floating_point() else t)(torch.as_tensor(a))
    N, deg, D = (10000, 64, 64)
    n_rbf = max(16, 4)
    E = N * deg
    cutoff = 5.0
    freqs = (torch.arange(1, n_rbf + 1) * torch.pi / cutoff).to(float)
    return {'sv': _w((lambda *s: torch.randn(*s, dtype=torch.bfloat16) * 0.4)(N, 4, D) * 0.3), 'pos': _w((lambda *s: torch.randn(*s, dtype=torch.bfloat16) * 1.6)(N, 3) * 1.2), 'src': _w((lambda lo, hi, *s: torch.randint(lo, hi, s))(0, N, E).to(torch.int64)), 'dst': _w((lambda lo, hi, *s: torch.randint(lo, hi, s))(0, N, E).to(torch.int64)), 'freqs': _w(freqs), 'w_phi1': _w((lambda *s: torch.randn(*s, dtype=torch.bfloat16) * 3.2)(D, D) / D ** 0.5), 'w_phi2': _w((lambda *s: torch.randn(*s, dtype=torch.bfloat16) * 1.6)(D, 3 * D) / D ** 0.5), 'w_rbf': _w((lambda *s: torch.randn(*s, dtype=torch.bfloat16) * 1.6)(n_rbf, 3 * D) / n_rbf ** 0.5)}

def reference(sv, pos, src, dst, freqs, w_phi1, w_phi2, w_rbf):
    N, _, D = sv.shape
    E = src.shape[0]
    PI, cutoff = (3.141592653589793, 5.0)
    s, v = (sv[:, 0, :].clone(), sv[:, 1:, :].clone())
    r_vec = pos[src] - pos[dst]
    d = torch.sqrt((r_vec * r_vec).sum(-1) + 1e-08)
    r_hat = r_vec / d[:, None]
    rbf = torch.sin(d[:, None] * freqs[None, :]) / d[:, None]
    fcut = 0.5 * (torch.cos(PI * d / cutoff) + 1.0)
    fcut = torch.where(d < cutoff, fcut, 0.0 * d)
    Wf = rbf @ w_rbf * fcut[:, None]
    phi = (_silu(s @ w_phi1) @ w_phi2)[src]
    m = phi * Wf
    m_s, m_vv, m_vr = (m[:, :D].clone(), m[:, D:2 * D].clone(), m[:, 2 * D:].clone())
    ds = _segment_sum(m_s, dst, N)
    dv_e = m_vv[:, None, :] * v[src] + m_vr[:, None, :] * r_hat[:, :, None]
    dv = _segment_sum(dv_e.reshape(E, 3 * D), dst, N).reshape(N, 3, D)
    return sv + torch.concatenate([ds[:, None, :], dv], axis=1)
```

```cpp
#include <cuda_runtime.h>
#include <cuda_bf16.h>
#include <stdint.h>

namespace {

constexpr int NT        = 384;
constexpr int NWARP     = NT / 32;
constexpr int MAX_N     = 10240;
constexpr int MAX_CTA   = 144;
constexpr int MAX_NPC   = 80;
constexpr int MAX_ROUNDS = 38;
constexpr int REC_CAP   = MAX_ROUNDS * 128;
constexpr int SEND_J    = 12;
constexpr int SLOT_CAP  = 6144;

constexpr uint32_t D_MIN_BITS = 0x38D2;
constexpr uint32_t D_MAX_BITS = 0x409C;
constexpr int TAB_ROWS  = (int)(D_MAX_BITS - D_MIN_BITS) + 1;
constexpr int TAB_ZERO  = TAB_ROWS;
constexpr int TAB_BYTES = (TAB_ROWS + 1) * 32;

constexpr int SM_TABLE  = 0;
constexpr int SM_COEF   = 65536;
constexpr int SM_META   = SM_COEF + 9 * 8192;
constexpr int SM_SID    = SM_META + SLOT_CAP * 8;
constexpr int SM_W2T    = SM_SID + SLOT_CAP * 2;
constexpr int SM_WTAB   = SM_W2T + 16384;
constexpr int SM_MISC   = SM_WTAB + 12288;
constexpr int SM_BINCNT = SM_MISC;
constexpr int SM_BINOFF = SM_BINCNT + MAX_CTA * 4;
constexpr int SM_NCNT   = SM_BINOFF + MAX_CTA * 4;
constexpr int SM_NOFF   = SM_NCNT + MAX_NPC * 4;
constexpr int SM_CTRL   = SM_NOFF + MAX_NPC * 4;
constexpr int SM_BARS   = SM_CTRL + 64;
constexpr int SM_TOTAL  = SM_BARS + 32;
constexpr int P1_POS    = 0;
constexpr int P1_STAGE  = 61440;
constexpr int P1_SV     = P1_STAGE + REC_CAP * 16;
constexpr int P1_W1     = P1_SV + MAX_NPC * 528;
constexpr int P1_W2V    = P1_W1 + 8192;
constexpr int P1_END    = P1_W2V + 8192;
static_assert(P1_END <= SM_W2T, "phase 1 overlay too large");
static_assert(SM_W2T % 1024 == 0 && SM_COEF % 1024 == 0, "alignment");
static_assert(SM_TOTAL <= 232448, "smem");
static_assert(TAB_BYTES <= SM_COEF, "table");
static_assert(MAX_N * 6 <= P1_STAGE, "pos");
static_assert(MAX_NPC * 1024 <= SM_W2T - 0, "slow path accumulators");

__device__ uint4    g_F[MAX_N * 32];
__device__ uint4    g_rec[MAX_CTA * REC_CAP];
__device__ uint32_t g_offs[MAX_CTA * MAX_CTA];
__device__ uint4    g_table[(TAB_BYTES + 15) / 16];
__device__ unsigned g_bar;

struct Params {
    const __nv_bfloat16* sv;
    const __nv_bfloat16* pos;
    const int*           src;
    const int*           dst;
    const __nv_bfloat16* freqs;
    const __nv_bfloat16* w1;
    const __nv_bfloat16* w2;
    const __nv_bfloat16* wr;
    __nv_bfloat16*       out;
    int N, E, ncta, npc;
    uint32_t npc_magic;
    int quads_per_cta;
};

__device__ __forceinline__ uint32_t smem_u32(const void* p) { return (uint32_t)__cvta_generic_to_shared(p); }
__device__ __forceinline__ float bf_lo(uint32_t v) { return __uint_as_float(v << 16); }
__device__ __forceinline__ float bf_hi(uint32_t v) { return __uint_as_float(v & 0xffff0000u); }
__device__ __forceinline__ uint32_t pack_bf(float lo, float hi) {
    uint32_t r;
    asm("cvt.rn.bf16x2.f32 %0, %1, %2;" : "=r"(r) : "f"(hi), "f"(lo));
    return r;
}
__device__ __forceinline__ float rbf(float x) { return bf_lo(pack_bf(x, 0.f)); }
__device__ __forceinline__ uint32_t hmul2(uint32_t a, uint32_t b) {
    uint32_t r;
    asm("mul.rn.bf16x2 %0, %1, %2;" : "=r"(r) : "r"(a), "r"(b));
    return r;
}
__device__ __forceinline__ uint32_t hsub2(uint32_t a, uint32_t b) {
    uint32_t r;
    asm("sub.rn.bf16x2 %0, %1, %2;" : "=r"(r) : "r"(a), "r"(b));
    return r;
}
__device__ __forceinline__ uint32_t lds32(uint32_t a) { uint32_t v; asm volatile("ld.shared.u32 %0, [%1];" : "=r"(v) : "r"(a)); return v; }
__device__ __forceinline__ uint2 lds64(uint32_t a) { uint2 v; asm volatile("ld.shared.v2.u32 {%0,%1}, [%2];" : "=r"(v.x), "=r"(v.y) : "r"(a)); return v; }
__device__ __forceinline__ uint4 lds128(uint32_t a) { uint4 v; asm volatile("ld.shared.v4.u32 {%0,%1,%2,%3}, [%4];" : "=r"(v.x), "=r"(v.y), "=r"(v.z), "=r"(v.w) : "r"(a)); return v; }
__device__ __forceinline__ void sts128(uint32_t a, uint4 v) { asm volatile("st.shared.v4.u32 [%0], {%1,%2,%3,%4};" ::"r"(a), "r"(v.x), "r"(v.y), "r"(v.z), "r"(v.w) : "memory"); }
__device__ __forceinline__ void mbar_init(uint32_t bar, int cnt) { asm volatile("mbarrier.init.shared::cta.b64 [%0], %1;" ::"r"(bar), "r"(cnt) : "memory"); }
__device__ __forceinline__ void mbar_expect_tx(uint32_t bar, uint32_t bytes) { asm volatile("mbarrier.arrive.expect_tx.shared::cta.b64 _, [%0], %1;" ::"r"(bar), "r"(bytes) : "memory"); }
__device__ __forceinline__ void mbar_wait(uint32_t bar, uint32_t parity) {
    uint32_t done;
    int spins = 0;
    do {
        asm volatile("{\n.reg .pred p;\nmbarrier.try_wait.parity.shared::cta.b64 p, [%1], %2;\nselp.u32 %0, 1, 0, p;\n}"
                     : "=r"(done) : "r"(bar), "r"(parity) : "memory");
    } while (!done && ++spins < (1 << 22));
}
__device__ __forceinline__ void bulk_g2s(uint32_t dst, const void* src, uint32_t bytes, uint32_t bar) {
    asm volatile("cp.async.bulk.shared::cluster.global.mbarrier::complete_tx::bytes [%0], [%1], %2, [%3];"
                 ::"r"(dst), "l"(src), "r"(bytes), "r"(bar) : "memory");
}
__device__ __forceinline__ void cp_async16(uint32_t dst, const void* src) {
    asm volatile("cp.async.cg.shared.global [%0], [%1], 16;" ::"r"(dst), "l"(src) : "memory");
}
__device__ __forceinline__ void fence_async_smem() { asm volatile("fence.proxy.async.shared::cta;" ::: "memory"); }
__device__ __forceinline__ void wg_barrier(int id) { asm volatile("bar.sync %0, 128;" ::"r"(id) : "memory"); }
__device__ __forceinline__ void ldsm4(uint32_t (&r)[4], uint32_t a) {
    asm volatile("ldmatrix.sync.aligned.m8n8.x4.shared.b16 {%0,%1,%2,%3}, [%4];" : "=r"(r[0]), "=r"(r[1]), "=r"(r[2]), "=r"(r[3]) : "r"(a));
}
__device__ __forceinline__ void ldsm4t(uint32_t (&r)[4], uint32_t a) {
    asm volatile("ldmatrix.sync.aligned.m8n8.x4.trans.shared.b16 {%0,%1,%2,%3}, [%4];" : "=r"(r[0]), "=r"(r[1]), "=r"(r[2]), "=r"(r[3]) : "r"(a));
}
__device__ __forceinline__ void stsm4(uint32_t a, uint32_t r0, uint32_t r1, uint32_t r2, uint32_t r3) {
    asm volatile("stmatrix.sync.aligned.m8n8.x4.shared.b16 [%0], {%1,%2,%3,%4};" ::"r"(a), "r"(r0), "r"(r1), "r"(r2), "r"(r3) : "memory");
}
__device__ __forceinline__ void mma16816(float (&c)[4], const uint32_t (&a)[4], uint32_t b0, uint32_t b1) {
    asm volatile("mma.sync.aligned.m16n8k16.row.col.f32.bf16.bf16.f32 {%0,%1,%2,%3}, {%4,%5,%6,%7}, {%8,%9}, {%0,%1,%2,%3};"
                 : "+f"(c[0]), "+f"(c[1]), "+f"(c[2]), "+f"(c[3])
                 : "r"(a[0]), "r"(a[1]), "r"(a[2]), "r"(a[3]), "r"(b0), "r"(b1));
}

__device__ __forceinline__ uint64_t mkdesc(uint32_t saddr) {
    return (uint64_t)((saddr & 0x3FFFF) >> 4) | ((uint64_t)1 << 16) | ((uint64_t)(1024 >> 4) << 32) | ((uint64_t)1 << 62);
}
__device__ __forceinline__ void wg_fence() { asm volatile("wgmma.fence.sync.aligned;" ::: "memory"); }
__device__ __forceinline__ void wg_commit() { asm volatile("wgmma.commit_group.sync.aligned;" ::: "memory"); }
__device__ __forceinline__ void wg_wait0() { asm volatile("wgmma.wait_group.sync.aligned 0;" ::: "memory"); }

__device__ __forceinline__ void wgmma_rs_n64(float (&d)[32], uint32_t a0, uint32_t a1, uint32_t a2, uint32_t a3, uint64_t bdesc, int scale) {
    asm volatile("{\n.reg .pred p;\nsetp.ne.b32 p, %37, 0;\n"
                 "wgmma.mma_async.sync.aligned.m64n64k16.f32.bf16.bf16 "
                 "{%0,%1,%2,%3,%4,%5,%6,%7,%8,%9,%10,%11,%12,%13,%14,%15,%16,%17,%18,%19,%20,%21,%22,%23,%24,%25,%26,%27,%28,%29,%30,%31}, "
                 "{%32,%33,%34,%35}, %36, p, 1, 1, 1;\n}"
                 : "+f"(d[0]), "+f"(d[1]), "+f"(d[2]), "+f"(d[3]), "+f"(d[4]), "+f"(d[5]), "+f"(d[6]), "+f"(d[7]),
                   "+f"(d[8]), "+f"(d[9]), "+f"(d[10]), "+f"(d[11]), "+f"(d[12]), "+f"(d[13]), "+f"(d[14]), "+f"(d[15]),
                   "+f"(d[16]), "+f"(d[17]), "+f"(d[18]), "+f"(d[19]), "+f"(d[20]), "+f"(d[21]), "+f"(d[22]), "+f"(d[23]),
                   "+f"(d[24]), "+f"(d[25]), "+f"(d[26]), "+f"(d[27]), "+f"(d[28]), "+f"(d[29]), "+f"(d[30]), "+f"(d[31])
                 : "r"(a0), "r"(a1), "r"(a2), "r"(a3), "l"(bdesc), "r"(scale));
}
__device__ __forceinline__ void wgmma_rs_n16(float (&d)[8], uint32_t a0, uint32_t a1, uint32_t a2, uint32_t a3, uint64_t bdesc, int scale) {
    asm volatile("{\n.reg .pred p;\nsetp.ne.b32 p, %13, 0;\n"
                 "wgmma.mma_async.sync.aligned.m64n16k16.f32.bf16.bf16 {%0,%1,%2,%3,%4,%5,%6,%7}, {%8,%9,%10,%11}, %12, p, 1, 1, 1;\n}"
                 : "+f"(d[0]), "+f"(d[1]), "+f"(d[2]), "+f"(d[3]), "+f"(d[4]), "+f"(d[5]), "+f"(d[6]), "+f"(d[7])
                 : "r"(a0), "r"(a1), "r"(a2), "r"(a3), "l"(bdesc), "r"(scale));
}
__device__ __forceinline__ void wgmma_ss_n16(float (&d)[8], uint64_t adesc, uint64_t bdesc, int scale) {
    asm volatile("{\n.reg .pred p;\nsetp.ne.b32 p, %10, 0;\n"
                 "wgmma.mma_async.sync.aligned.m64n16k16.f32.bf16.bf16 {%0,%1,%2,%3,%4,%5,%6,%7}, %8, %9, p, 1, 1, 1, 1;\n}"
                 : "+f"(d[0]), "+f"(d[1]), "+f"(d[2]), "+f"(d[3]), "+f"(d[4]), "+f"(d[5]), "+f"(d[6]), "+f"(d[7])
                 : "l"(adesc), "l"(bdesc), "r"(scale));
}
__device__ __forceinline__ void wgmma_ss_n48(float (&d)[24], uint64_t adesc, uint64_t bdesc, int scale) {
    asm volatile("{\n.reg .pred p;\nsetp.ne.b32 p, %26, 0;\n"
                 "wgmma.mma_async.sync.aligned.m64n48k16.f32.bf16.bf16 "
                 "{%0,%1,%2,%3,%4,%5,%6,%7,%8,%9,%10,%11,%12,%13,%14,%15,%16,%17,%18,%19,%20,%21,%22,%23}, %24, %25, p, 1, 1, 1, 1;\n}"
                 : "+f"(d[0]), "+f"(d[1]), "+f"(d[2]), "+f"(d[3]), "+f"(d[4]), "+f"(d[5]), "+f"(d[6]), "+f"(d[7]),
                   "+f"(d[8]), "+f"(d[9]), "+f"(d[10]), "+f"(d[11]), "+f"(d[12]), "+f"(d[13]), "+f"(d[14]), "+f"(d[15]),
                   "+f"(d[16]), "+f"(d[17]), "+f"(d[18]), "+f"(d[19]), "+f"(d[20]), "+f"(d[21]), "+f"(d[22]), "+f"(d[23])
                 : "l"(adesc), "l"(bdesc), "r"(scale));
}

__device__ __forceinline__ void ld_row(uint4& v, const void* p, bool pred) {
    asm volatile("{\n.reg .pred p;\nsetp.ne.b32 p, %5, 0;\n"
                 "mov.b32 %0, 0;\nmov.b32 %1, 0;\nmov.b32 %2, 0;\nmov.b32 %3, 0;\n"
                 "@p ld.global.L1::no_allocate.v4.u32 {%0,%1,%2,%3}, [%4];\n}"
                 : "=r"(v.x), "=r"(v.y), "=r"(v.z), "=r"(v.w) : "l"(p), "r"((int)pred));
}

__device__ __forceinline__ uint32_t edge_dist(uint32_t sxy, uint32_t sz, uint32_t dxy, uint32_t dz, uint32_t& rxy, uint32_t& rz) {
    rxy = hsub2(sxy, dxy);
    rz  = hsub2(sz, dz);
    uint32_t qxy = hmul2(rxy, rxy), qz = hmul2(rz, rz);
    float ss = rbf((bf_lo(qxy) + bf_hi(qxy)) + bf_lo(qz));
    float s2 = rbf(ss + 1e-8f);
    float d;
    asm("sqrt.approx.f32 %0, %1;" : "=f"(d) : "f"(s2));
    return pack_bf(d, 0.f) & 0xffffu;
}

__device__ __forceinline__ void load_pos(uint32_t sm_pos, int i, uint32_t& xy, uint32_t& z) {
    uint32_t a  = sm_pos + ((6u * (uint32_t)i) & ~3u);
    uint32_t w0 = lds32(a), w1 = lds32(a + 4);
    uint32_t sh = (i & 1) << 4;
    xy = __funnelshift_r(w0, w1, sh);
    z  = (w1 >> sh) & 0xffffu;
}

__device__ __forceinline__ float radial_value(float d, float f) {
    float arg = rbf(d * f);
    float sn  = rbf(sinf(arg));
    float rb  = rbf(__fdiv_rn(sn, d));
    float c   = rbf(cosf(rbf(__fdiv_rn(rbf(d * 3.14159265358979323846f), 5.0f))));
    float fc  = rbf(0.5f * rbf(c + 1.0f));
    return rb * fc;
}

struct Item { int nl; int base; int G; int first; int last; int valid; };

__global__ void __launch_bounds__(NT, 1) painn_kernel(const Params p) {
    extern __shared__ __align__(1024) uint8_t smem[];
    const uint32_t sb   = smem_u32(smem);
    const int tid  = threadIdx.x, lane = tid & 31, warp = tid >> 5;
    const int cta  = blockIdx.x;
    const int g    = lane >> 2, t = lane & 3;
    int* binCnt = (int*)(smem + SM_BINCNT);
    int* binOff = (int*)(smem + SM_BINOFF);
    int* nCnt   = (int*)(smem + SM_NCNT);
    int* nOff   = (int*)(smem + SM_NOFF);
    volatile int* ctrl = (volatile int*)(smem + SM_CTRL);
    const uint32_t bar_pos = sb + SM_BARS, bar_tab = sb + SM_BARS + 8;

    const int node0  = cta * p.npc;
    const int nnodes = max(0, min(p.npc, p.N - node0));

    if (tid == 0) {
        mbar_init(bar_pos, 1);
        mbar_init(bar_tab, 1);
        asm volatile("fence.mbarrier_init.release.cluster;" ::: "memory");
        uint32_t pos_bytes = (uint32_t)(p.N * 6 + 15) & ~15u;
        mbar_expect_tx(bar_pos, pos_bytes);
        bulk_g2s(sb + P1_POS, p.pos, pos_bytes, bar_pos);
    }
    const bool mlp_warp = warp >= 7;
    int4 s4[4], d4[4];
    {
        const int q0 = cta * p.quads_per_cta;
        const int qend = min(q0 + p.quads_per_cta, p.E >> 2);
#pragma unroll
        for (int k = 0; k < 4; k++) {
            int round = mlp_warp ? (k < 2 ? 28 + (warp - 7) + 5 * k : -1) : warp + 7 * k;
            int q = q0 + round * 32 + lane;
            bool ok = round >= 0 && q < qend;
            s4[k] = ok ? __ldg((const int4*)p.src + q) : make_int4(-1, -1, -1, -1);
            d4[k] = ok ? __ldg((const int4*)p.dst + q) : make_int4(0, 0, 0, 0);
        }
    }
    for (int i = tid; i < nnodes * 32; i += NT) {
        int r = i >> 5, c = i & 31;
        cp_async16(sb + P1_SV + r * 528 + c * 16, (const uint8_t*)p.sv + (size_t)(node0 + r) * 512 + c * 16);
    }
    for (int i = tid; i < 1024; i += NT) {
        int m = i >> 9, k = (i >> 3) & 63, c = i & 7;
        const uint8_t* srcp = m == 0 ? (const uint8_t*)p.w1 + k * 128 + c * 16 : (const uint8_t*)p.w2 + k * 384 + 128 + c * 16;
        cp_async16(sb + (m == 0 ? P1_W1 : P1_W2V) + k * 128 + ((c ^ (k & 7)) << 4), srcp);
    }
    asm volatile("cp.async.commit_group;" ::: "memory");
    for (int i = tid; i < MAX_CTA; i += NT) binCnt[i] = 0;
    if (tid < MAX_NPC) nCnt[tid] = 0;
    if (tid < 16) ctrl[tid] = 0;
    for (int task = tid; task < 512; task += NT) {
        int mat = task >> 8, kap = (task >> 2) & 63, wb = task & 3;
        int j = (kap & 48) + 2 * (kap & 7) + ((kap >> 3) & 1);
        const uint4* sp = (const uint4*)(p.w2 + j * 192 + mat * 128 + wb * 16);
        uint4 u = __ldg(sp), v = __ldg(sp + 1);
        uint4 ev = make_uint4(__byte_perm(u.x, u.y, 0x5410), __byte_perm(u.z, u.w, 0x5410), __byte_perm(v.x, v.y, 0x5410), __byte_perm(v.z, v.w, 0x5410));
        uint4 od = make_uint4(__byte_perm(u.x, u.y, 0x7632), __byte_perm(u.z, u.w, 0x7632), __byte_perm(v.x, v.y, 0x7632), __byte_perm(v.z, v.w, 0x7632));
        uint32_t rb = sb + SM_W2T + mat * 8192 + kap * 128;
        sts128(rb + (((2 * wb) ^ (kap & 7)) << 4), ev);
        sts128(rb + (((2 * wb + 1) ^ (kap & 7)) << 4), od);
    }
    if (tid < 128) {
        int c0 = 16 * warp + 2 * g;
#pragma unroll
        for (int ty = 0; ty < 3; ty++) {
#pragma unroll
            for (int hf = 0; hf < 2; hf++) {
                int k = 8 * hf + 2 * t;
                uint32_t a = __ldg((const uint32_t*)(p.wr + k * 192 + ty * 64 + c0));
                uint32_t b = __ldg((const uint32_t*)(p.wr + (k + 1) * 192 + ty * 64 + c0));
                float4 f = make_float4(bf_lo(a), bf_lo(b), bf_hi(a), bf_hi(b));
                *(float4*)(smem + SM_WTAB + ((ty * 2 + hf) * 128 + tid) * 16) = f;
            }
        }
    }
    {
        int rows_per = (TAB_ROWS + 1 + p.ncta - 1) / p.ncta;
        for (int i = tid; i < rows_per * 8; i += NT) {
            int row = cta * rows_per + (i >> 3), kp = i & 7;
            if (row <= TAB_ROWS) {
                uint32_t val = 0;
                if (row < TAB_ROWS) {
                    float d = __uint_as_float((D_MIN_BITS + row) << 16);
                    uint32_t f2 = __ldg((const uint32_t*)p.freqs + kp);
                    val = pack_bf(radial_value(d, bf_lo(f2)), radial_value(d, bf_hi(f2)));
                }
                ((uint32_t*)g_table)[row * 8 + kp] = val;
            }
        }
    }
    asm volatile("cp.async.wait_group 0;" ::: "memory");
    __syncthreads();
    mbar_wait(bar_pos, 0);

    uint32_t r0[16], r1[16], r2[16], rk[16];
#pragma unroll
    for (int k = 0; k < 4; k++) {
        const int ss[4] = {s4[k].x, s4[k].y, s4[k].z, s4[k].w};
        const int dd[4] = {d4[k].x, d4[k].y, d4[k].z, d4[k].w};
#pragma unroll
        for (int j = 0; j < 4; j++) {
            const int e = k * 4 + j;
            rk[e] = 0xffffffffu;
            int s = ss[j], d = dd[j];
            if (s >= 0) {
                uint32_t sxy, sz, dxy, dz, rxy, rz;
                load_pos(sb + P1_POS, s, sxy, sz);
                load_pos(sb + P1_POS, d, dxy, dz);
                uint32_t db = edge_dist(sxy, sz, dxy, dz, rxy, rz);
                if (db <= D_MAX_BITS) {
                    float inv;
                    asm("rcp.approx.f32 %0, %1;" : "=f"(inv) : "f"(__uint_as_float(db << 16)));
                    uint32_t bin = __umulhi((uint32_t)d, p.npc_magic);
                    uint32_t dl  = (uint32_t)d - bin * (uint32_t)p.npc;
                    r0[e] = (uint32_t)s | ((db - D_MIN_BITS) << 16);
                    r1[e] = pack_bf(bf_lo(rxy) * inv, bf_hi(rxy) * inv);
                    r2[e] = (pack_bf(bf_lo(rz) * inv, 0.f) & 0xffffu) | (dl << 16);
                    rk[e] = (uint32_t)atomicAdd(&binCnt[bin], 1) | (bin << 16);
                }
            }
        }
    }

    if (mlp_warp) {
        const int mt = warp - 7;
        if (mt * 16 < nnodes) {
            float acc[8][4];
#pragma unroll
            for (int i = 0; i < 8; i++) { acc[i][0] = acc[i][1] = acc[i][2] = acc[i][3] = 0.f; }
            const int lrow = (lane & 7) + ((lane >> 3) & 1) * 8, lch = lane >> 4;
#pragma unroll
            for (int ks = 0; ks < 4; ks++) {
                uint32_t a[4];
                ldsm4(a, sb + P1_SV + (mt * 16 + lrow) * 528 + (2 * ks + lch) * 16);
                const int kk = 16 * ks + lrow;
#pragma unroll
                for (int nt = 0; nt < 8; nt += 2) {
                    uint32_t b[4];
                    ldsm4t(b, sb + P1_W1 + kk * 128 + (((nt + lch) ^ (kk & 7)) << 4));
                    mma16816(acc[nt], a, b[0], b[1]);
                    mma16816(acc[nt + 1], a, b[2], b[3]);
                }
            }
            uint32_t hp[8][2];
#pragma unroll
            for (int i = 0; i < 8; i++) {
                float h[4];
#pragma unroll
                for (int q = 0; q < 4; q++) {
                    float x = rbf(acc[i][q]);
                    h[q] = __fdividef(x, 1.0f + __expf(-x));
                    acc[i][q] = 0.f;
                }
                hp[i][0] = pack_bf(h[0], h[1]);
                hp[i][1] = pack_bf(h[2], h[3]);
            }
#pragma unroll
            for (int ks = 0; ks < 4; ks++) {
                uint32_t a[4] = {hp[2 * ks][0], hp[2 * ks][1], hp[2 * ks + 1][0], hp[2 * ks + 1][1]};
                const int kk = 16 * ks + lrow;
#pragma unroll
                for (int nt = 0; nt < 8; nt += 2) {
                    uint32_t b[4];
                    ldsm4t(b, sb + P1_W2V + kk * 128 + (((nt + lch) ^ (kk & 7)) << 4));
                    mma16816(acc[nt], a, b[0], b[1]);
                    mma16816(acc[nt + 1], a, b[2], b[3]);
                }
            }
#pragma unroll
            for (int rh = 0; rh < 2; rh++) {
                const int row = mt * 16 + g + 8 * rh;
                if (row < nnodes) {
#pragma unroll
                    for (int i = 0; i < 8; i++) {
                        uint32_t ph = pack_bf(acc[i][2 * rh], acc[i][2 * rh + 1]);
                        uint32_t va = sb + P1_SV + row * 528 + 128 + (8 * i + 2 * t) * 2;
                        uint4 o = make_uint4(hp[i][rh], hmul2(ph, lds32(va)), hmul2(ph, lds32(va + 128)), hmul2(ph, lds32(va + 256)));
                        g_F[(size_t)(node0 + row) * 32 + 4 * i + t] = o;
                    }
                }
            }
        }
    }
    __syncthreads();
    if (warp == 0) {
        int c[5], s = 0;
#pragma unroll
        for (int i = 0; i < 5; i++) { int b = lane * 5 + i; c[i] = b < p.ncta ? binCnt[b] : 0; s += c[i]; }
        int x = s;
#pragma unroll
        for (int o = 1; o < 32; o <<= 1) { int y = __shfl_up_sync(0xffffffffu, x, o); if (lane >= o) x += y; }
        int off = x - s;
#pragma unroll
        for (int i = 0; i < 5; i++) {
            int b = lane * 5 + i;
            if (b < p.ncta) { binOff[b] = off; g_offs[cta * MAX_CTA + b] = (uint32_t)off | ((uint32_t)c[i] << 16); }
            off += c[i];
        }
        if (lane == 31) ctrl[8] = x;
    }
    __syncthreads();
#pragma unroll
    for (int e = 0; e < 16; e++) {
        if (rk[e] != 0xffffffffu) {
            int pos = binOff[rk[e] >> 16] + (int)(rk[e] & 0xffffu);
            sts128(sb + P1_STAGE + pos * 16, make_uint4(r0[e], r1[e], r2[e], 0u));
        }
    }
    __syncthreads();
    {
        const int total = ctrl[8];
        for (int i = tid; i < total; i += NT) g_rec[(size_t)cta * REC_CAP + i] = lds128(sb + P1_STAGE + i * 16);
    }

    __syncthreads();
    if (tid == 0) {
        __threadfence();
        unsigned old = atomicAdd(&g_bar, 1u);
        unsigned target = (old / (unsigned)p.ncta + 1u) * (unsigned)p.ncta;
        unsigned cur;
        int spins = 0;
        do {
            asm volatile("ld.acquire.gpu.global.u32 %0, [%1];" : "=r"(cur) : "l"(&g_bar) : "memory");
        } while ((int)(cur - target) < 0 && ++spins < (1 << 24));
        __threadfence();
        asm volatile("fence.proxy.async;" ::: "memory");
        mbar_expect_tx(bar_tab, TAB_BYTES);
        bulk_g2s(sb + SM_TABLE, g_table, TAB_BYTES, bar_tab);
    }
    __syncthreads();

    if (tid < p.ncta) binOff[tid] = (int)__ldcg(&g_offs[tid * MAX_CTA + cta]);
    __syncthreads();
    {
        uint4 ra[SEND_J], rb2[SEND_J];
        int rka[SEND_J], rkb[SEND_J];
#pragma unroll
        for (int j = 0; j < SEND_J; j++) {
            int s = warp + NWARP * j;
            uint32_t v = s < p.ncta ? (uint32_t)binOff[s] : 0u;
            int off = v & 0xffff, c = v >> 16;
            const uint4* bp = g_rec + (size_t)s * REC_CAP + off + lane;
            rka[j] = lane < c;
            rkb[j] = lane + 32 < c;
            if (rka[j]) ra[j] = __ldcg(bp);
            if (rkb[j]) rb2[j] = __ldcg(bp + 32);
            if (c > 64) ctrl[1] = 1;
        }
#pragma unroll
        for (int j = 0; j < SEND_J; j++) {
            rka[j] = rka[j] ? atomicAdd(&nCnt[ra[j].z >> 16], 1) : -1;
            rkb[j] = rkb[j] ? atomicAdd(&nCnt[rb2[j].z >> 16], 1) : -1;
        }
        __syncthreads();
        if (warp == 0) {
            int c[3], s = 0;
#pragma unroll
            for (int i = 0; i < 3; i++) {
                int b = lane * 3 + i;
                c[i] = b < nnodes ? max(16, (nCnt[b] + 15) & ~15) : 0;
                s += c[i];
            }
            int x = s;
#pragma unroll
            for (int o = 1; o < 32; o <<= 1) { int y = __shfl_up_sync(0xffffffffu, x, o); if (lane >= o) x += y; }
            int off = x - s;
#pragma unroll
            for (int i = 0; i < 3; i++) { int b = lane * 3 + i; if (b < nnodes) nOff[b] = off; off += c[i]; }
            if (lane == 31 && x > SLOT_CAP) ctrl[1] = 1;
        }
        __syncthreads();
        if (ctrl[1] == 0) {
            uint16_t* sid = (uint16_t*)(smem + SM_SID);
            uint2* meta = (uint2*)(smem + SM_META);
#pragma unroll
            for (int j = 0; j < SEND_J; j++) {
                if (rka[j] >= 0) {
                    int pos = nOff[ra[j].z >> 16] + rka[j];
                    sid[pos]  = (uint16_t)(ra[j].x & 0xffffu);
                    meta[pos] = make_uint2(((ra[j].x >> 16) << 5) | (ra[j].z << 16), ra[j].y);
                }
                if (rkb[j] >= 0) {
                    int pos = nOff[rb2[j].z >> 16] + rkb[j];
                    sid[pos]  = (uint16_t)(rb2[j].x & 0xffffu);
                    meta[pos] = make_uint2(((rb2[j].x >> 16) << 5) | (rb2[j].z << 16), rb2[j].y);
                }
            }
            for (int i = tid; i < nnodes * 16; i += NT) {
                int nl = i >> 4, c = nCnt[nl];
                int j = (c & ~15) + (i & 15);
                if (j >= c && (j < 16 || (c & 15))) {
                    int pos = nOff[nl] + j;
                    sid[pos]  = 0xffffu;
                    meta[pos] = make_uint2((uint32_t)TAB_ZERO << 5, 0u);
                }
            }
        }
    }
    __syncthreads();
    mbar_wait(bar_tab, 0);

    if (ctrl[1] != 0) {
        float* acc = (float*)smem;
        __syncthreads();
        for (int i = tid; i < nnodes * 256; i += NT) acc[i] = 0.f;
        __syncthreads();
        const uint16_t* posu = (const uint16_t*)p.pos;
        const uint32_t* tabg = (const uint32_t*)g_table;
        for (int e0 = warp * 32; e0 < p.E; e0 += NT) {
            int e = e0 + lane;
            int s = 0, d = 0;
            uint32_t db = 0xffff, rxy = 0, rz = 0;
            bool act = false;
            if (e < p.E) {
                s = p.src[e]; d = p.dst[e];
                if (d >= node0 && d < node0 + nnodes) {
                    uint32_t sxy = posu[s * 3] | ((uint32_t)posu[s * 3 + 1] << 16), sz = posu[s * 3 + 2];
                    uint32_t dxy = posu[d * 3] | ((uint32_t)posu[d * 3 + 1] << 16), dz = posu[d * 3 + 2];
                    db  = edge_dist(sxy, sz, dxy, dz, rxy, rz);
                    act = db <= D_MAX_BITS;
                }
            }
            unsigned m = __ballot_sync(0xffffffffu, act);
            while (m) {
                int l = __ffs(m) - 1;
                m &= m - 1;
                int es = __shfl_sync(0xffffffffu, s, l), ed = __shfl_sync(0xffffffffu, d, l);
                uint32_t edb = __shfl_sync(0xffffffffu, db, l), exy = __shfl_sync(0xffffffffu, rxy, l), ez = __shfl_sync(0xffffffffu, rz, l);
                float inv = 1.0f / __uint_as_float(edb << 16);
                float rh[3] = {rbf(bf_lo(exy) * inv), rbf(bf_hi(exy) * inv), rbf(bf_lo(ez) * inv)};
                uint4 f = __ldcg(&g_F[(size_t)es * 32 + lane]);
                float ps0 = 0.f, ps1 = 0.f, pr0 = 0.f, pr1 = 0.f;
                for (int j2 = 0; j2 < 32; j2++) {
                    uint32_t hj = __shfl_sync(0xffffffffu, f.x, j2);
                    uint32_t a0 = *(const uint32_t*)(p.w2 + (2 * j2) * 192 + 2 * lane), a1 = *(const uint32_t*)(p.w2 + (2 * j2 + 1) * 192 + 2 * lane);
                    uint32_t b0 = *(const uint32_t*)(p.w2 + (2 * j2) * 192 + 128 + 2 * lane), b1 = *(const uint32_t*)(p.w2 + (2 * j2 + 1) * 192 + 128 + 2 * lane);
                    ps0 += bf_lo(hj) * bf_lo(a0) + bf_hi(hj) * bf_lo(a1);
                    ps1 += bf_lo(hj) * bf_hi(a0) + bf_hi(hj) * bf_hi(a1);
                    pr0 += bf_lo(hj) * bf_lo(b0) + bf_hi(hj) * bf_lo(b1);
                    pr1 += bf_lo(hj) * bf_hi(b0) + bf_hi(hj) * bf_hi(b1);
                }
                float ws0 = 0.f, ws1 = 0.f, wv0 = 0.f, wv1 = 0.f, wr0 = 0.f, wr1 = 0.f;
                for (int k2 = 0; k2 < 8; k2++) {
                    uint32_t rk2 = __ldcg(tabg + (edb - D_MIN_BITS) * 8 + k2);
#pragma unroll
                    for (int h = 0; h < 2; h++) {
                        float rv = h ? bf_hi(rk2) : bf_lo(rk2);
                        const __nv_bfloat16* wrow = p.wr + (2 * k2 + h) * 192 + 2 * lane;
                        uint32_t a = *(const uint32_t*)wrow, b = *(const uint32_t*)(wrow + 64), c = *(const uint32_t*)(wrow + 128);
                        ws0 += rv * bf_lo(a); ws1 += rv * bf_hi(a);
                        wv0 += rv * bf_lo(b); wv1 += rv * bf_hi(b);
                        wr0 += rv * bf_lo(c); wr1 += rv * bf_hi(c);
                    }
                }
                float* a = acc + (ed - node0) * 256 + 2 * lane;
                atomicAdd(a, ps0 * ws0); atomicAdd(a + 1, ps1 * ws1);
                const uint32_t q[3] = {f.y, f.z, f.w};
#pragma unroll
                for (int c = 0; c < 3; c++) {
                    atomicAdd(a + 64 * (c + 1), wv0 * bf_lo(q[c]) + pr0 * wr0 * rh[c]);
                    atomicAdd(a + 64 * (c + 1) + 1, wv1 * bf_hi(q[c]) + pr1 * wr1 * rh[c]);
                }
            }
        }
        __syncthreads();
        for (int i = tid; i < nnodes * 128; i += NT) {
            uint32_t r = *(const uint32_t*)(p.sv + (size_t)node0 * 256 + 2 * i);
            *(uint32_t*)(p.out + (size_t)node0 * 256 + 2 * i) = pack_bf(bf_lo(r) + acc[2 * i], bf_hi(r) + acc[2 * i + 1]);
        }
        return;
    }

    const int wg = warp >> 2, w = warp & 3, t128 = tid & 127;
    const uint32_t coef0 = sb + SM_COEF + wg * 3 * 8192;
    const uint8_t* Fb = (const uint8_t*)g_F + w * 128 + g * 16;
    volatile int* wq = ctrl + 2 + wg * 2;

    auto make_item = [&](int nl, int chunk) {
        Item it;
        it.nl = nl;
        it.valid = nl < nnodes;
        int padded = it.valid ? max(16, (nCnt[nl] + 15) & ~15) : 0;
        it.base  = it.valid ? nOff[nl] + 64 * chunk : 0;
        it.G     = min(4, (padded - 64 * chunk) >> 4);
        it.first = chunk;
        it.last  = 64 * (chunk + 1) >= padded;
        return it;
    };
    auto produce = [&](const Item& it, uint32_t cbuf) {
        const int r = t128 >> 1, half = t128 & 1;
        if (r < 16 * it.G) {
            uint2 m = lds64(sb + SM_META + (it.base + r) * 8);
            uint32_t ta = sb + SM_TABLE + (m.x & 0xffffu);
            uint4 t0 = lds128(ta), t1 = lds128(ta + 16);
            uint32_t mA = half ? __byte_perm(m.y, 0, 0x3232) : 0x3f803f80u;
            uint32_t mB = half ? __byte_perm(m.x, 0, 0x3232) : __byte_perm(m.y, 0, 0x1010);
            uint32_t rb = cbuf + r * 128;
            int x = r & 7, c = 4 * half;
            sts128(rb + (((c + 0) ^ x) << 4), make_uint4(hmul2(t0.x, mA), hmul2(t0.y, mA), hmul2(t0.z, mA), hmul2(t0.w, mA)));
            sts128(rb + (((c + 1) ^ x) << 4), make_uint4(hmul2(t1.x, mA), hmul2(t1.y, mA), hmul2(t1.z, mA), hmul2(t1.w, mA)));
            sts128(rb + (((c + 2) ^ x) << 4), make_uint4(hmul2(t0.x, mB), hmul2(t0.y, mB), hmul2(t0.z, mB), hmul2(t0.w, mB)));
            sts128(rb + (((c + 3) ^ x) << 4), make_uint4(hmul2(t1.x, mB), hmul2(t1.y, mB), hmul2(t1.z, mB), hmul2(t1.w, mB)));
        }
    };
    uint4 buf[4][4];
    auto issue_rows = [&](const Item& it) {
#pragma unroll
        for (int s = 0; s < 4; s++) {
            uint32_t p0 = 0xffffffffu, p1 = 0xffffffffu;
            if (s < it.G) {
                uint32_t a = sb + SM_SID + (it.base + 16 * s + 2 * t) * 2;
                p0 = lds32(a);
                p1 = lds32(a + 16);
            }
            uint32_t i0 = p0 & 0xffffu, i1 = p0 >> 16, i2 = p1 & 0xffffu, i3 = p1 >> 16;
            ld_row(buf[s][0], Fb + (size_t)i0 * 512, i0 != 0xffffu);
            ld_row(buf[s][1], Fb + (size_t)i1 * 512, i1 != 0xffffu);
            ld_row(buf[s][2], Fb + (size_t)i2 * 512, i2 != 0xffffu);
            ld_row(buf[s][3], Fb + (size_t)i3 * 512, i3 != 0xffffu);
        }
    };
    auto load_resid = [&](const Item& it) -> uint32_t {
        uint32_t r = 0;
        if (it.valid && it.last) r = __ldg((const uint32_t*)(p.sv + (size_t)(node0 + it.nl) * 256 + t * 64 + 16 * w + 2 * g));
        return r;
    };

    float dH[32], dQ[3][8];
#pragma unroll
    for (int i = 0; i < 32; i++) dH[i] = 0.f;
#pragma unroll
    for (int i = 0; i < 8; i++) { dQ[0][i] = 0.f; dQ[1][i] = 0.f; dQ[2][i] = 0.f; }

    if (tid == 0) ctrl[0] = 3;
    __syncthreads();
    Item cur = make_item(wg, 0);
    Item nxt;
    {
        if (cur.valid) produce(cur, coef0);
        fence_async_smem();
        if (cur.last && t128 == 0) wq[0] = atomicAdd((int*)&ctrl[0], 1);
        wg_barrier(1 + wg);
        nxt = cur.last ? make_item(wq[0], 0) : make_item(cur.nl, cur.first + 1);
        issue_rows(cur);
    }
    uint32_t resid = load_resid(cur);
    int it_idx = 0;
    int par = 1;

    while (cur.valid) {
        uint32_t A[4][4][4];
#pragma unroll
        for (int s = 0; s < 4; s++) {
            const uint32_t* b0 = &buf[s][0].x; const uint32_t* b1 = &buf[s][1].x;
            const uint32_t* b2 = &buf[s][2].x; const uint32_t* b3 = &buf[s][3].x;
#pragma unroll
            for (int c = 0; c < 4; c++) {
                A[s][c][0] = __byte_perm(b0[c], b1[c], 0x5410);
                A[s][c][1] = __byte_perm(b0[c], b1[c], 0x7632);
                A[s][c][2] = __byte_perm(b2[c], b3[c], 0x5410);
                A[s][c][3] = __byte_perm(b2[c], b3[c], 0x7632);
            }
        }
        const float res0 = bf_lo(resid), res1 = bf_hi(resid);
        const uint32_t cbuf = coef0 + it_idx * 8192;
        const int nidx = it_idx == 2 ? 0 : it_idx + 1;
        wg_fence();
#pragma unroll
        for (int s = 0; s < 4; s++) {
            if (s < cur.G) {
                const uint64_t bd = mkdesc(cbuf + s * 2048);
                const int sc = (s > 0) || (cur.first > 0);
                wgmma_rs_n64(dH, A[s][0][0], A[s][0][1], A[s][0][2], A[s][0][3], bd, sc);
                wgmma_rs_n16(dQ[0], A[s][1][0], A[s][1][1], A[s][1][2], A[s][1][3], bd, sc);
                wgmma_rs_n16(dQ[1], A[s][2][0], A[s][2][1], A[s][2][2], A[s][2][3], bd, sc);
                wgmma_rs_n16(dQ[2], A[s][3][0], A[s][3][1], A[s][3][2], A[s][3][3], bd, sc);
            }
        }
        wg_commit();
        if (nxt.valid) produce(nxt, coef0 + nidx * 8192);
        if (nxt.valid && nxt.last && t128 == 0) wq[par] = atomicAdd((int*)&ctrl[0], 1);
        fence_async_smem();
        wg_wait0();
        wg_barrier(1 + wg);
        Item nn;
        if (!nxt.valid) nn = nxt;
        else nn = nxt.last ? make_item(wq[par], 0) : make_item(nxt.nl, nxt.first + 1);
        par ^= 1;
        issue_rows(nxt);
        const uint32_t resid_n = load_resid(nxt);

        if (cur.last) {
            {
                const int row = 16 * w + (lane & 7) + ((lane >> 3) & 1) * 8;
                const uint32_t rb = cbuf + row * 128;
                const int x = row & 7, ch = lane >> 4;
#pragma unroll
                for (int i = 0; i < 8; i += 2) {
                    stsm4(rb + (((i + ch) ^ x) << 4),
                          pack_bf(dH[4 * i], dH[4 * i + 1]), pack_bf(dH[4 * i + 2], dH[4 * i + 3]),
                          pack_bf(dH[4 * i + 4], dH[4 * i + 5]), pack_bf(dH[4 * i + 6], dH[4 * i + 7]));
                }
            }
            fence_async_smem();
            wg_barrier(1 + wg);
            float ys[8], yv[24];
#pragma unroll
            for (int i = 0; i < 8; i++) ys[i] = 0.f;
#pragma unroll
            for (int i = 0; i < 24; i++) yv[i] = 0.f;
            wg_fence();
#pragma unroll
            for (int ks = 0; ks < 4; ks++) {
                wgmma_ss_n16(ys, mkdesc(sb + SM_W2T + ks * 2048), mkdesc(cbuf + ks * 2048), ks);
                wgmma_ss_n48(yv, mkdesc(sb + SM_W2T + 8192 + ks * 2048), mkdesc(cbuf + ks * 2048 + 32), ks);
            }
            wg_commit();
            wg_wait0();
            float pr[4][2];
            {
                const uint32_t wa = sb + SM_WTAB + t128 * 16;
                uint4 u0 = lds128(wa), u1 = lds128(wa + 2048);
                pr[0][0] = __uint_as_float(u0.x) * ys[0] + __uint_as_float(u0.y) * ys[1] + __uint_as_float(u1.x) * ys[4] + __uint_as_float(u1.y) * ys[5];
                pr[0][1] = __uint_as_float(u0.z) * ys[2] + __uint_as_float(u0.w) * ys[3] + __uint_as_float(u1.z) * ys[6] + __uint_as_float(u1.w) * ys[7];
                uint4 v0 = lds128(wa + 2 * 2048), v1 = lds128(wa + 3 * 2048), x0 = lds128(wa + 4 * 2048), x1 = lds128(wa + 5 * 2048);
#pragma unroll
                for (int a = 0; a < 3; a++) {
                    const float* q = dQ[a];
                    const float* y = yv + 8 * a;
                    pr[a + 1][0] = __uint_as_float(v0.x) * q[0] + __uint_as_float(v0.y) * q[1] + __uint_as_float(v1.x) * q[4] + __uint_as_float(v1.y) * q[5]
                                 + __uint_as_float(x0.x) * y[0] + __uint_as_float(x0.y) * y[1] + __uint_as_float(x1.x) * y[4] + __uint_as_float(x1.y) * y[5];
                    pr[a + 1][1] = __uint_as_float(v0.z) * q[2] + __uint_as_float(v0.w) * q[3] + __uint_as_float(v1.z) * q[6] + __uint_as_float(v1.w) * q[7]
                                 + __uint_as_float(x0.z) * y[2] + __uint_as_float(x0.w) * y[3] + __uint_as_float(x1.z) * y[6] + __uint_as_float(x1.w) * y[7];
                }
            }
            const bool hi2 = t & 2, hi1 = t & 1;
            float ka0 = hi2 ? pr[2][0] : pr[0][0], ka1 = hi2 ? pr[2][1] : pr[0][1];
            float kb0 = hi2 ? pr[3][0] : pr[1][0], kb1 = hi2 ? pr[3][1] : pr[1][1];
            float sa0 = hi2 ? pr[0][0] : pr[2][0], sa1 = hi2 ? pr[0][1] : pr[2][1];
            float sb0 = hi2 ? pr[1][0] : pr[3][0], sb1 = hi2 ? pr[1][1] : pr[3][1];
            ka0 += __shfl_xor_sync(0xffffffffu, sa0, 2); ka1 += __shfl_xor_sync(0xffffffffu, sa1, 2);
            kb0 += __shfl_xor_sync(0xffffffffu, sb0, 2); kb1 += __shfl_xor_sync(0xffffffffu, sb1, 2);
            float k0 = hi1 ? kb0 : ka0, k1 = hi1 ? kb1 : ka1;
            float s0 = hi1 ? ka0 : kb0, s1 = hi1 ? ka1 : kb1;
            k0 += __shfl_xor_sync(0xffffffffu, s0, 1);
            k1 += __shfl_xor_sync(0xffffffffu, s1, 1);
            *(uint32_t*)(p.out + (size_t)(node0 + cur.nl) * 256 + t * 64 + 16 * w + 2 * g) = pack_bf(res0 + k0, res1 + k1);
        }
        cur = nxt; nxt = nn; resid = resid_n; it_idx = nidx;
    }
}

}

extern "C" void kernel_launch(void* const* d_in, const int* in_sizes, int n_in, void* d_out, int out_size) {
    (void)n_in; (void)out_size;
    static int n_sm = 0;
    if (n_sm == 0) {
        int dev = 0;
        cudaGetDevice(&dev);
        cudaDeviceGetAttribute(&n_sm, cudaDevAttrMultiProcessorCount, dev);
        cudaFuncSetAttribute(painn_kernel, cudaFuncAttributeMaxDynamicSharedMemorySize, SM_TOTAL);
    }
    Params p;
    p.sv    = (const __nv_bfloat16*)d_in[0];
    p.pos   = (const __nv_bfloat16*)d_in[1];
    p.src   = (const int*)d_in[2];
    p.dst   = (const int*)d_in[3];
    p.freqs = (const __nv_bfloat16*)d_in[4];
    p.w1    = (const __nv_bfloat16*)d_in[5];
    p.w2    = (const __nv_bfloat16*)d_in[6];
    p.wr    = (const __nv_bfloat16*)d_in[7];
    p.out   = (__nv_bfloat16*)d_out;
    p.N = in_sizes[1] / 3;
    p.E = in_sizes[2];
    p.ncta = n_sm < MAX_CTA ? n_sm : MAX_CTA;
    p.npc = (p.N + p.ncta - 1) / p.ncta;
    p.npc_magic = (uint32_t)(0x100000000ull / (uint32_t)p.npc) + 1u;
    p.quads_per_cta = ((p.E >> 2) + p.ncta - 1) / p.ncta;
    if (p.N > MAX_N || p.npc > MAX_NPC || (p.E & 3) || p.quads_per_cta > MAX_ROUNDS * 32) return;

    cudaLaunchConfig_t cfg = {};
    cfg.gridDim = dim3(p.ncta);
    cfg.blockDim = dim3(NT);
    cfg.dynamicSmemBytes = SM_TOTAL;
    cfg.stream = cudaStreamPerThread;
    cudaLaunchAttribute attr[1];
    attr[0].id = cudaLaunchAttributeCooperative;
    attr[0].val.cooperative = 1;
    cfg.attrs = attr;
    cfg.numAttrs = 1;
    cudaLaunchKernelEx(&cfg, painn_kernel, p);
}
```

```cpp
#include <cuda_runtime.h>
#include <cuda_bf16.h>
#include <stdint.h>

namespace {

constexpr int NT        = 384;
constexpr int NWARP     = NT / 32;
constexpr int MAX_N     = 10240;
constexpr int MAX_CTA   = 144;
constexpr int MAX_NPC   = 80;
constexpr int MAX_ROUNDS = 38;
constexpr int REC_CAP   = MAX_ROUNDS * 128;
constexpr int SLOT_CAP  = 6144;

constexpr uint32_t D_MIN_BITS = 0x38D2;
constexpr uint32_t D_MAX_BITS = 0x409C;
constexpr int TAB_ROWS  = (int)(D_MAX_BITS - D_MIN_BITS) + 1;
constexpr int TAB_ZERO  = TAB_ROWS;
constexpr int TAB_BYTES = (TAB_ROWS + 1) * 32;

constexpr int SM_TABLE  = 0;
constexpr int SM_COEF   = 65536;
constexpr int SM_META   = SM_COEF + 9 * 8192;
constexpr int SM_SID    = SM_META + SLOT_CAP * 8;
constexpr int SM_W2T    = SM_SID + SLOT_CAP * 2;
constexpr int SM_WTAB   = SM_W2T + 16384;
constexpr int SM_MISC   = SM_WTAB + 12288;
constexpr int SM_BINCNT = SM_MISC;
constexpr int SM_BINOFF = SM_BINCNT + MAX_CTA * 4;
constexpr int SM_NCNT   = SM_BINOFF + MAX_CTA * 4;
constexpr int SM_NINFO  = SM_NCNT + MAX_NPC * 4;
constexpr int SM_CTRL   = SM_NINFO + MAX_NPC * 4;
constexpr int SM_BARS   = SM_CTRL + 64;
constexpr int SM_TOTAL  = SM_BARS + 64;
constexpr int P1_POS    = 0;
constexpr int P1_STAGE  = 61440;
constexpr int P1_SV     = P1_STAGE + REC_CAP * 16;
constexpr int P1_W1     = P1_SV + MAX_NPC * 528;
constexpr int P1_W2V    = P1_W1 + 64 * 144;
constexpr int P1_END    = P1_W2V + 64 * 144;
constexpr int STAGE_SMALL = (SM_META - SM_COEF) / 16;
constexpr int STAGE_BIG   = SM_META / 16;
static_assert(P1_END <= SM_W2T, "phase 1 overlay too large");
static_assert(SM_W2T % 1024 == 0 && SM_COEF % 1024 == 0, "alignment");
static_assert(SM_TOTAL <= 232448, "smem");
static_assert(SM_BARS % 8 == 0, "mbarrier alignment");
static_assert(TAB_BYTES <= SM_COEF, "table");
static_assert(MAX_N * 6 <= P1_STAGE, "pos");
static_assert(MAX_NPC * 1024 <= SM_W2T - 0, "slow path accumulators");

__device__ uint4    g_F[MAX_N * 32];
__device__ uint4    g_rec[MAX_CTA * REC_CAP];
__device__ uint32_t g_offs[MAX_CTA * MAX_CTA];
__device__ uint4    g_table[(TAB_BYTES + 15) / 16];
__device__ unsigned g_bar;
#define STAMP(k)

struct Params {
    const __nv_bfloat16* sv;
    const __nv_bfloat16* pos;
    const int*           src;
    const int*           dst;
    const __nv_bfloat16* freqs;
    const __nv_bfloat16* w1;
    const __nv_bfloat16* w2;
    const __nv_bfloat16* wr;
    __nv_bfloat16*       out;
    int N, E, ncta, npc;
    uint32_t npc_magic;
    int quads_per_cta;
    uint32_t row_bytes;
};

__device__ __forceinline__ uint32_t smem_u32(const void* p) { return (uint32_t)__cvta_generic_to_shared(p); }
__device__ __forceinline__ float bf_lo(uint32_t v) { return __uint_as_float(v << 16); }
__device__ __forceinline__ float bf_hi(uint32_t v) { return __uint_as_float(v & 0xffff0000u); }
__device__ __forceinline__ uint32_t pack_bf(float lo, float hi) {
    uint32_t r;
    asm("cvt.rn.bf16x2.f32 %0, %1, %2;" : "=r"(r) : "f"(hi), "f"(lo));
    return r;
}
__device__ __forceinline__ float rbf(float x) { return bf_lo(pack_bf(x, 0.f)); }
__device__ __forceinline__ uint32_t hmul2(uint32_t a, uint32_t b) {
    uint32_t r;
    asm("mul.rn.bf16x2 %0, %1, %2;" : "=r"(r) : "r"(a), "r"(b));
    return r;
}
__device__ __forceinline__ uint32_t hsub2(uint32_t a, uint32_t b) {
    uint32_t r;
    asm("sub.rn.bf16x2 %0, %1, %2;" : "=r"(r) : "r"(a), "r"(b));
    return r;
}
__device__ __forceinline__ uint32_t lds32(uint32_t a) { uint32_t v; asm volatile("ld.shared.u32 %0, [%1];" : "=r"(v) : "r"(a)); return v; }
__device__ __forceinline__ uint2 lds64(uint32_t a) { uint2 v; asm volatile("ld.shared.v2.u32 {%0,%1}, [%2];" : "=r"(v.x), "=r"(v.y) : "r"(a)); return v; }
__device__ __forceinline__ uint4 lds128(uint32_t a) { uint4 v; asm volatile("ld.shared.v4.u32 {%0,%1,%2,%3}, [%4];" : "=r"(v.x), "=r"(v.y), "=r"(v.z), "=r"(v.w) : "r"(a)); return v; }
__device__ __forceinline__ void sts128(uint32_t a, uint4 v) { asm volatile("st.shared.v4.u32 [%0], {%1,%2,%3,%4};" ::"r"(a), "r"(v.x), "r"(v.y), "r"(v.z), "r"(v.w) : "memory"); }
__device__ __forceinline__ void mbar_init(uint32_t bar, int cnt) { asm volatile("mbarrier.init.shared::cta.b64 [%0], %1;" ::"r"(bar), "r"(cnt) : "memory"); }
__device__ __forceinline__ void mbar_expect_tx(uint32_t bar, uint32_t bytes) { asm volatile("mbarrier.arrive.expect_tx.shared::cta.b64 _, [%0], %1;" ::"r"(bar), "r"(bytes) : "memory"); }
__device__ __forceinline__ void mbar_wait(uint32_t bar, uint32_t parity) {
    uint32_t done;
    int spins = 0;
    do {
        asm volatile("{\n.reg .pred p;\nmbarrier.try_wait.parity.shared::cta.b64 p, [%1], %2;\nselp.u32 %0, 1, 0, p;\n}"
                     : "=r"(done) : "r"(bar), "r"(parity) : "memory");
    } while (!done && ++spins < (1 << 22));
}
__device__ __forceinline__ void bulk_g2s(uint32_t dst, const void* src, uint32_t bytes, uint32_t bar) {
    asm volatile("cp.async.bulk.shared::cluster.global.mbarrier::complete_tx::bytes [%0], [%1], %2, [%3];"
                 ::"r"(dst), "l"(src), "r"(bytes), "r"(bar) : "memory");
}
__device__ __forceinline__ void cp_async16(uint32_t dst, const void* src) {
    asm volatile("cp.async.cg.shared.global [%0], [%1], 16;" ::"r"(dst), "l"(src) : "memory");
}
__device__ __forceinline__ void fence_async_smem() { asm volatile("fence.proxy.async.shared::cta;" ::: "memory"); }
__device__ __forceinline__ void wg_barrier() {
    uint32_t t;
    asm volatile("mov.u32 %0, %%tid.x;" : "=r"(t));
    asm volatile("bar.sync %0, 128;" ::"r"((t >> 7) + 1) : "memory");
}
__device__ __forceinline__ void ldsm4(uint32_t (&r)[4], uint32_t a) {
    asm volatile("ldmatrix.sync.aligned.m8n8.x4.shared.b16 {%0,%1,%2,%3}, [%4];" : "=r"(r[0]), "=r"(r[1]), "=r"(r[2]), "=r"(r[3]) : "r"(a));
}
__device__ __forceinline__ void ldsm4t(uint32_t (&r)[4], uint32_t a) {
    asm volatile("ldmatrix.sync.aligned.m8n8.x4.trans.shared.b16 {%0,%1,%2,%3}, [%4];" : "=r"(r[0]), "=r"(r[1]), "=r"(r[2]), "=r"(r[3]) : "r"(a));
}
__device__ __forceinline__ void stsm4(uint32_t a, uint32_t r0, uint32_t r1, uint32_t r2, uint32_t r3) {
    asm volatile("stmatrix.sync.aligned.m8n8.x4.shared.b16 [%0], {%1,%2,%3,%4};" ::"r"(a), "r"(r0), "r"(r1), "r"(r2), "r"(r3) : "memory");
}
__device__ __forceinline__ void mma16816(float (&c)[4], const uint32_t (&a)[4], uint32_t b0, uint32_t b1) {
    asm volatile("mma.sync.aligned.m16n8k16.row.col.f32.bf16.bf16.f32 {%0,%1,%2,%3}, {%4,%5,%6,%7}, {%8,%9}, {%0,%1,%2,%3};"
                 : "+f"(c[0]), "+f"(c[1]), "+f"(c[2]), "+f"(c[3])
                 : "r"(a[0]), "r"(a[1]), "r"(a[2]), "r"(a[3]), "r"(b0), "r"(b1));
}

__device__ __forceinline__ uint32_t desc_lo(uint32_t saddr) { return ((saddr & 0x3FFFF) >> 4) | (1u << 16); }
#define DESC_HI "0x40000040"
__device__ __forceinline__ void wg_fence() { asm volatile("wgmma.fence.sync.aligned;" ::: "memory"); }
__device__ __forceinline__ void wg_commit() { asm volatile("wgmma.commit_group.sync.aligned;" ::: "memory"); }
__device__ __forceinline__ void wg_wait0() { asm volatile("wgmma.wait_group.sync.aligned 0;" ::: "memory"); }

__device__ __forceinline__ void wgmma_rs_n64(float (&d)[8], float (&e)[24], const uint32_t (&a)[4], uint32_t bdesc, int scale) {
    asm volatile("{\n.reg .pred p;\n.reg .b64 b;\nsetp.ne.b32 p, %37, 0;\nmov.b64 b, {%36, " DESC_HI "};\n"
                 "wgmma.mma_async.sync.aligned.m64n64k16.f32.bf16.bf16 {%0,%1,%2,%3,%4,%5,%6,%7,%8,%9,%10,%11,%12,%13,%14,%15,%16,%17,%18,%19,%20,%21,%22,%23,%24,%25,%26,%27,%28,%29,%30,%31}, {%32,%33,%34,%35}, b, p, 1, 1, 1;\n}"
                 : "+f"(d[0]), "+f"(d[1]), "+f"(d[2]), "+f"(d[3]), "+f"(d[4]), "+f"(d[5]), "+f"(d[6]), "+f"(d[7]),
                   "+f"(e[0]), "+f"(e[1]), "+f"(e[2]), "+f"(e[3]), "+f"(e[4]), "+f"(e[5]), "+f"(e[6]), "+f"(e[7]), "+f"(e[8]), "+f"(e[9]), "+f"(e[10]), "+f"(e[11]), "+f"(e[12]), "+f"(e[13]), "+f"(e[14]), "+f"(e[15]), "+f"(e[16]), "+f"(e[17]), "+f"(e[18]), "+f"(e[19]), "+f"(e[20]), "+f"(e[21]), "+f"(e[22]), "+f"(e[23])
                 : "r"(a[0]), "r"(a[1]), "r"(a[2]), "r"(a[3]), "r"(bdesc), "r"(scale));
}
__device__ __forceinline__ void wgmma_rs_n16(float (&d)[8], const uint32_t (&a)[4], uint32_t bdesc, int scale) {
    asm volatile("{\n.reg .pred p;\n.reg .b64 b;\nsetp.ne.b32 p, %13, 0;\nmov.b64 b, {%12, " DESC_HI "};\n"
                 "wgmma.mma_async.sync.aligned.m64n16k16.f32.bf16.bf16 {%0,%1,%2,%3,%4,%5,%6,%7}, {%8,%9,%10,%11}, b, p, 1, 1, 1;\n}"
                 : "+f"(d[0]), "+f"(d[1]), "+f"(d[2]), "+f"(d[3]), "+f"(d[4]), "+f"(d[5]), "+f"(d[6]), "+f"(d[7])
                 : "r"(a[0]), "r"(a[1]), "r"(a[2]), "r"(a[3]), "r"(bdesc), "r"(scale));
}
__device__ __forceinline__ void wgmma_ss_n16(float (&d)[8], uint32_t adesc, uint32_t bdesc, int scale) {
    asm volatile("{\n.reg .pred p;\n.reg .b64 a, b;\nsetp.ne.b32 p, %10, 0;\nmov.b64 a, {%8, " DESC_HI "};\nmov.b64 b, {%9, " DESC_HI "};\n"
                 "wgmma.mma_async.sync.aligned.m64n16k16.f32.bf16.bf16 {%0,%1,%2,%3,%4,%5,%6,%7}, a, b, p, 1, 1, 1, 1;\n}"
                 : "+f"(d[0]), "+f"(d[1]), "+f"(d[2]), "+f"(d[3]), "+f"(d[4]), "+f"(d[5]), "+f"(d[6]), "+f"(d[7])
                 : "r"(adesc), "r"(bdesc), "r"(scale));
}
__device__ __forceinline__ void wgmma_ss_n48(float (&d)[24], uint32_t adesc, uint32_t bdesc, int scale) {
    asm volatile("{\n.reg .pred p;\n.reg .b64 a, b;\nsetp.ne.b32 p, %26, 0;\nmov.b64 a, {%24, " DESC_HI "};\nmov.b64 b, {%25, " DESC_HI "};\n"
                 "wgmma.mma_async.sync.aligned.m64n48k16.f32.bf16.bf16 {%0,%1,%2,%3,%4,%5,%6,%7,%8,%9,%10,%11,%12,%13,%14,%15,%16,%17,%18,%19,%20,%21,%22,%23}, a, b, p, 1, 1, 1, 1;\n}"
                 : "+f"(d[0]), "+f"(d[1]), "+f"(d[2]), "+f"(d[3]), "+f"(d[4]), "+f"(d[5]), "+f"(d[6]), "+f"(d[7]), "+f"(d[8]), "+f"(d[9]), "+f"(d[10]), "+f"(d[11]), "+f"(d[12]), "+f"(d[13]), "+f"(d[14]), "+f"(d[15]), "+f"(d[16]), "+f"(d[17]), "+f"(d[18]), "+f"(d[19]), "+f"(d[20]), "+f"(d[21]), "+f"(d[22]), "+f"(d[23])
                 : "r"(adesc), "r"(bdesc), "r"(scale));
}

__device__ __forceinline__ void ld_row(uint4& v, uint64_t base, uint32_t id, uint32_t rb) {
    asm volatile("{\n.reg .u64 a;\nmad.wide.u32 a, %5, %6, %4;\n"
                 "ld.global.L1::no_allocate.v4.u32 {%0,%1,%2,%3}, [a];\n}"
                 : "=r"(v.x), "=r"(v.y), "=r"(v.z), "=r"(v.w) : "l"(base), "r"(id), "r"(rb));
}
__device__ __forceinline__ void ld_row_pad(uint4& v, uint64_t base, uint32_t id, uint32_t rb) {
    asm volatile("{\n.reg .pred p;\n.reg .u64 a;\nsetp.ne.u32 p, %5, 0xffff;\nmad.wide.u32 a, %5, %6, %4;\n"
                 "mov.b32 %0, 0;\nmov.b32 %1, 0;\nmov.b32 %2, 0;\nmov.b32 %3, 0;\n"
                 "@p ld.global.L1::no_allocate.v4.u32 {%0,%1,%2,%3}, [a];\n}"
                 : "=r"(v.x), "=r"(v.y), "=r"(v.z), "=r"(v.w) : "l"(base), "r"(id), "r"(rb));
}
__device__ __forceinline__ void kill_row(uint4& v) {
    asm volatile("" : "=r"(v.x), "=r"(v.y), "=r"(v.z), "=r"(v.w));
}
__device__ __forceinline__ void sts32(uint32_t a, uint32_t v) { asm volatile("st.shared.u32 [%0], %1;" ::"r"(a), "r"(v) : "memory"); }

__device__ __forceinline__ uint32_t edge_dist(uint32_t sxy, uint32_t sz, uint32_t dxy, uint32_t dz, uint32_t& rxy, uint32_t& rz) {
    rxy = hsub2(sxy, dxy);
    rz  = hsub2(sz, dz);
    uint32_t qxy = hmul2(rxy, rxy), qz = hmul2(rz, rz);
    float ss = rbf((bf_lo(qxy) + bf_hi(qxy)) + bf_lo(qz));
    float s2 = rbf(ss + 1e-8f);
    float d;
    asm("sqrt.approx.ftz.f32 %0, %1;" : "=f"(d) : "f"(s2));
    return pack_bf(d, 0.f) & 0xffffu;
}

__device__ __forceinline__ void load_pos(uint32_t sm_pos, int i, uint32_t& xy, uint32_t& z) {
    uint32_t a  = (sm_pos + 6u * (uint32_t)i) & ~3u;
    uint32_t w0 = lds32(a), w1 = lds32(a + 4);
    uint32_t sh = (uint32_t)i << 4;
    xy = __funnelshift_r(w0, w1, sh);
    z  = __funnelshift_r(w1, w1, sh);
}

__device__ __noinline__ float radial_value(float d, float f) {
    float arg = rbf(d * f);
    float sn  = rbf(sinf(arg));
    float rb  = rbf(__fdiv_rn(sn, d));
    float c   = rbf(cosf(rbf(__fdiv_rn(rbf(d * 3.14159265358979323846f), 5.0f))));
    float fc  = rbf(0.5f * rbf(c + 1.0f));
    return rb * fc;
}

__global__ void __launch_bounds__(NT, 1) painn_kernel(const Params p) {
    extern __shared__ __align__(1024) uint8_t smem[];
    const uint32_t sb   = smem_u32(smem);
    const int tid  = threadIdx.x, lane = tid & 31, warp = __shfl_sync(0xffffffffu, tid >> 5, 0);
    const int cta  = blockIdx.x;
    const int g    = lane >> 2, t = lane & 3;
    int* binCnt = (int*)(smem + SM_BINCNT);
    int* binOff = (int*)(smem + SM_BINOFF);
    int* nCnt   = (int*)(smem + SM_NCNT);
    uint32_t* nInfo = (uint32_t*)(smem + SM_NINFO);
    volatile int* ctrl = (volatile int*)(smem + SM_CTRL);
    const uint32_t bar_pos = sb + SM_BARS, bar_tab = bar_pos + 8, bar_mlp = bar_pos + 16, bar_rec = bar_pos + 24;

    const int node0  = cta * p.npc;
    const int nnodes = max(0, min(p.npc, p.N - node0));

    STAMP(0);
    if (tid == 0) {
        mbar_init(bar_pos, 1);
        mbar_init(bar_tab, 1);
        mbar_init(bar_mlp, 1);
        mbar_init(bar_rec, 1);
        asm volatile("fence.mbarrier_init.release.cluster;" ::: "memory");
        uint32_t pos_bytes = (uint32_t)(p.N * 6 + 15) & ~15u;
        mbar_expect_tx(bar_pos, pos_bytes);
        bulk_g2s(sb + P1_POS, p.pos, pos_bytes, bar_pos);
        mbar_expect_tx(bar_mlp, (uint32_t)nnodes * 512u + 2u * 8192u);
    }
    const bool mlp_warp = warp >= 7;
    int4 s4[4], d4[4];
    {
        const int q0 = cta * p.quads_per_cta;
        const int qend = min(q0 + p.quads_per_cta, p.E >> 2);
#pragma unroll
        for (int k = 0; k < 4; k++) {
            int round = mlp_warp ? (k < 2 ? 28 + (warp - 7) + 5 * k : -1) : warp + 7 * k;
            int q = q0 + round * 32 + lane;
            bool ok = round >= 0 && q < qend;
            s4[k] = ok ? __ldg((const int4*)p.src + q) : make_int4(-1, -1, -1, -1);
            d4[k] = ok ? __ldg((const int4*)p.dst + q) : make_int4(0, 0, 0, 0);
        }
    }
    for (int i = tid; i < MAX_CTA; i += NT) binCnt[i] = 0;
    if (tid < MAX_NPC) nCnt[tid] = 0;
    if (tid < 16) ctrl[tid] = 0;
    if (tid < 240) {
        const uint8_t* a = tid < 192 ? (const uint8_t*)p.w2 + tid * 128 : (const uint8_t*)p.wr + (tid - 192) * 128;
        asm volatile("prefetch.global.L2 [%0];" ::"l"(a));
    }
    __syncthreads();
    if (tid < 128) {
        const int k = tid & 63;
        const uint8_t* srcp = tid < 64 ? (const uint8_t*)p.w1 + k * 128 : (const uint8_t*)p.w2 + k * 384 + 128;
        bulk_g2s(sb + (tid < 64 ? P1_W1 : P1_W2V) + k * 144, srcp, 128, bar_mlp);
    } else if (tid - 128 < nnodes) {
        const int r = tid - 128;
        bulk_g2s(sb + P1_SV + r * 528, (const uint8_t*)p.sv + (size_t)(node0 + r) * 512, 512, bar_mlp);
    }

    if (mlp_warp) {
        const int rows_per = (TAB_ROWS + 1 + p.ncta - 1) / p.ncta;
        for (int i = tid - 7 * 32; i < rows_per * 8; i += 5 * 32) {
            int row = cta * rows_per + (i >> 3), kp = i & 7;
            if (row <= TAB_ROWS) {
                uint32_t val = 0;
                if (row < TAB_ROWS) {
                    float d = __uint_as_float((D_MIN_BITS + row) << 16);
                    uint32_t f2 = __ldg((const uint32_t*)p.freqs + kp);
                    val = pack_bf(radial_value(d, bf_lo(f2)), radial_value(d, bf_hi(f2)));
                }
                ((uint32_t*)g_table)[row * 8 + kp] = val;
            }
        }
        const int mt = warp - 7;
        if (mt * 16 < nnodes) {
            mbar_wait(bar_mlp, 0);
            float acc[8][4];
#pragma unroll
            for (int i = 0; i < 8; i++) { acc[i][0] = acc[i][1] = acc[i][2] = acc[i][3] = 0.f; }
            const int lrow = (lane & 7) + ((lane >> 3) & 1) * 8, lch = lane >> 4;
#pragma unroll
            for (int ks = 0; ks < 4; ks++) {
                uint32_t a[4];
                ldsm4(a, sb + P1_SV + (mt * 16 + lrow) * 528 + (2 * ks + lch) * 16);
                const uint32_t wb = sb + P1_W1 + (16 * ks + lrow) * 144 + lch * 16;
#pragma unroll
                for (int nt = 0; nt < 8; nt += 2) {
                    uint32_t b[4];
                    ldsm4t(b, wb + nt * 16);
                    mma16816(acc[nt], a, b[0], b[1]);
                    mma16816(acc[nt + 1], a, b[2], b[3]);
                }
            }
            uint32_t hp[8][2];
#pragma unroll
            for (int i = 0; i < 8; i++) {
                float h[4];
#pragma unroll
                for (int q = 0; q < 4; q++) {
                    float x = rbf(acc[i][q]);
                    h[q] = __fdividef(x, 1.0f + __expf(-x));
                    acc[i][q] = 0.f;
                }
                hp[i][0] = pack_bf(h[0], h[1]);
                hp[i][1] = pack_bf(h[2], h[3]);
            }
#pragma unroll
            for (int ks = 0; ks < 4; ks++) {
                uint32_t a[4] = {hp[2 * ks][0], hp[2 * ks][1], hp[2 * ks + 1][0], hp[2 * ks + 1][1]};
                const uint32_t wb = sb + P1_W2V + (16 * ks + lrow) * 144 + lch * 16;
#pragma unroll
                for (int nt = 0; nt < 8; nt += 2) {
                    uint32_t b[4];
                    ldsm4t(b, wb + nt * 16);
                    mma16816(acc[nt], a, b[0], b[1]);
                    mma16816(acc[nt + 1], a, b[2], b[3]);
                }
            }
#pragma unroll
            for (int rh = 0; rh < 2; rh++) {
                const int row = mt * 16 + g + 8 * rh;
                if (row < nnodes) {
                    const uint32_t va = sb + P1_SV + row * 528 + 128 + 4 * t;
                    uint4* fo = g_F + (size_t)(node0 + row) * 32 + t;
#pragma unroll
                    for (int i = 0; i < 8; i++) {
                        uint32_t ph = pack_bf(acc[i][2 * rh], acc[i][2 * rh + 1]);
                        fo[4 * i] = make_uint4(hp[i][rh], hmul2(ph, lds32(va + 16 * i)), hmul2(ph, lds32(va + 16 * i + 128)), hmul2(ph, lds32(va + 16 * i + 256)));
                    }
                }
            }
        }
    }
    mbar_wait(bar_pos, 0);
    STAMP(1);

    uint32_t r0[16], r1[16], r2[16], rk[16];
#pragma unroll
    for (int k = 0; k < 4; k++) {
        const int ss[4] = {s4[k].x, s4[k].y, s4[k].z, s4[k].w};
        const int dd[4] = {d4[k].x, d4[k].y, d4[k].z, d4[k].w};
#pragma unroll
        for (int j = 0; j < 4; j++) rk[k * 4 + j] = 0xffffffffu;
        if (ss[0] >= 0) {
#pragma unroll
            for (int j = 0; j < 4; j++) {
                const int e = k * 4 + j;
                const int s = ss[j], d = dd[j];
                uint32_t sxy, sz, dxy, dz, rxy, rz;
                load_pos(sb + P1_POS, s, sxy, sz);
                load_pos(sb + P1_POS, d, dxy, dz);
                uint32_t db = edge_dist(sxy, sz, dxy, dz, rxy, rz);
                float inv;
                asm("rcp.approx.ftz.f32 %0, %1;" : "=f"(inv) : "f"(__uint_as_float(db << 16)));
                uint32_t bin = __umulhi((uint32_t)d, p.npc_magic);
                uint32_t dl  = (uint32_t)d - bin * (uint32_t)p.npc;
                r0[e] = (uint32_t)s | ((db - D_MIN_BITS) << 16);
                r1[e] = pack_bf(bf_lo(rxy) * inv, bf_hi(rxy) * inv);
                r2[e] = __byte_perm(pack_bf(bf_lo(rz) * inv, 0.f), dl, 0x5410);
                if (db <= D_MAX_BITS) rk[e] = (uint32_t)atomicAdd(&binCnt[bin], 1) | (bin << 16);
            }
        }
    }
    STAMP(2);
    __syncthreads();
    STAMP(3);
    if (warp == 0) {
        int c[5], s = 0;
#pragma unroll
        for (int i = 0; i < 5; i++) { int b = lane * 5 + i; c[i] = b < p.ncta ? binCnt[b] : 0; s += c[i]; }
        int x = s;
#pragma unroll
        for (int o = 1; o < 32; o <<= 1) { int y = __shfl_up_sync(0xffffffffu, x, o); if (lane >= o) x += y; }
        int off = x - s;
#pragma unroll
        for (int i = 0; i < 5; i++) {
            int b = lane * 5 + i;
            if (b < p.ncta) { binOff[b] = off; g_offs[cta * MAX_CTA + b] = (uint32_t)off | ((uint32_t)c[i] << 16); }
            off += c[i];
        }
        if (lane == 31) ctrl[8] = x;
    }
    __syncthreads();
#pragma unroll
    for (int e = 0; e < 16; e++) {
        if (rk[e] != 0xffffffffu) {
            int pos = binOff[rk[e] >> 16] + (int)(rk[e] & 0xffffu);
            sts128(sb + P1_STAGE + pos * 16, make_uint4(r0[e], r1[e], r2[e], 0u));
        }
    }
    __syncthreads();
    {
        const int total = ctrl[8];
        for (int i = tid; i < total; i += NT) g_rec[(size_t)cta * REC_CAP + i] = lds128(sb + P1_STAGE + i * 16);
    }

    __syncthreads();
    STAMP(4);
    unsigned bar_target = 0;
    if (tid == 0) {
        unsigned old;
        asm volatile("atom.add.release.gpu.global.u32 %0, [%1], 1;" : "=r"(old) : "l"(&g_bar) : "memory");
        bar_target = (old / (unsigned)p.ncta + 1u) * (unsigned)p.ncta;
    }
    for (int task = tid; task < 512; task += NT) {
        int mat = task >> 8, kap = (task >> 2) & 63, wb = task & 3;
        int j = (kap & 48) + 2 * (kap & 7) + ((kap >> 3) & 1);
        const uint4* sp = (const uint4*)(p.w2 + j * 192 + mat * 128 + wb * 16);
        uint4 u = __ldg(sp), v = __ldg(sp + 1);
        uint4 ev = make_uint4(__byte_perm(u.x, u.y, 0x5410), __byte_perm(u.z, u.w, 0x5410), __byte_perm(v.x, v.y, 0x5410), __byte_perm(v.z, v.w, 0x5410));
        uint4 od = make_uint4(__byte_perm(u.x, u.y, 0x7632), __byte_perm(u.z, u.w, 0x7632), __byte_perm(v.x, v.y, 0x7632), __byte_perm(v.z, v.w, 0x7632));
        uint32_t rb = sb + SM_W2T + mat * 8192 + kap * 128;
        sts128(rb + (((2 * wb) ^ (kap & 7)) << 4), ev);
        sts128(rb + (((2 * wb + 1) ^ (kap & 7)) << 4), od);
    }
    if (tid >= 256) {
        const int u = tid - 256;
        const int c0 = 16 * (u >> 5) + 2 * g;
#pragma unroll
        for (int q = 0; q < 6; q++) {
            const int ty = q >> 1, k = 8 * (q & 1) + 2 * t;
            uint32_t a = __ldg((const uint32_t*)(p.wr + k * 192 + ty * 64 + c0));
            uint32_t b = __ldg((const uint32_t*)(p.wr + (k + 1) * 192 + ty * 64 + c0));
            *(float4*)(smem + SM_WTAB + (q * 128 + u) * 16) = make_float4(bf_lo(a), bf_lo(b), bf_hi(a), bf_hi(b));
        }
    }
    if (warp == 0) {
        if (lane == 0) {
            unsigned cur;
            int spins = 0;
            do {
                asm volatile("ld.acquire.gpu.global.u32 %0, [%1];" : "=r"(cur) : "l"(&g_bar) : "memory");
            } while ((int)(cur - bar_target) < 0 && ++spins < (1 << 24));
            asm volatile("fence.proxy.async;" ::: "memory");
        }
        __syncwarp();
        STAMP(5);
        uint32_t v[5];
        int s = 0;
#pragma unroll
        for (int i = 0; i < 5; i++) {
            int b = lane * 5 + i;
            v[i] = b < p.ncta ? __ldcg(&g_offs[b * MAX_CTA + cta]) : 0u;
        }
#pragma unroll
        for (int i = 0; i < 5; i++) s += (int)(v[i] >> 16);
        int x = s;
#pragma unroll
        for (int o = 1; o < 32; o <<= 1) { int y = __shfl_up_sync(0xffffffffu, x, o); if (lane >= o) x += y; }
        const int total = __shfl_sync(0xffffffffu, x, 31);
        const bool big = total > STAGE_SMALL;
        if (total <= STAGE_BIG) {
            if (lane == 0) {
                mbar_expect_tx(bar_rec, (uint32_t)total * 16u);
                if (!big) { mbar_expect_tx(bar_tab, TAB_BYTES); bulk_g2s(sb + SM_TABLE, g_table, TAB_BYTES, bar_tab); }
            }
            uint32_t dsta = sb + (big ? 0 : SM_COEF) + (uint32_t)(x - s) * 16u;
#pragma unroll
            for (int i = 0; i < 5; i++) {
                const uint32_t c = v[i] >> 16;
                if (c) bulk_g2s(dsta, g_rec + (size_t)(lane * 5 + i) * REC_CAP + (v[i] & 0xffffu), c * 16u, bar_rec);
                dsta += c * 16u;
            }
        } else if (lane == 0) {
            ctrl[1] = 1;
            mbar_expect_tx(bar_rec, 0);
        }
        if (lane == 0) { ctrl[8] = total; ctrl[9] = big; }
    }
    __syncthreads();
    const int total = ctrl[8];
    const uint32_t stage = sb + (ctrl[9] ? 0 : SM_COEF);
    mbar_wait(bar_rec, 0);
    if (ctrl[1] == 0) {
        for (int i = tid; i < total; i += NT) {
            uint32_t dl = lds32(stage + i * 16 + 8) >> 16;
            sts32(stage + i * 16 + 12, (uint32_t)atomicAdd(&nCnt[dl], 1));
        }
    }
    __syncthreads();
    if (warp == 0) {
        int c[3], s = 0;
#pragma unroll
        for (int i = 0; i < 3; i++) {
            int b = lane * 3 + i;
            c[i] = b < nnodes ? max(16, (nCnt[b] + 15) & ~15) : 0;
            s += c[i];
        }
        int x = s;
#pragma unroll
        for (int o = 1; o < 32; o <<= 1) { int y = __shfl_up_sync(0xffffffffu, x, o); if (lane >= o) x += y; }
        int off = x - s;
#pragma unroll
        for (int i = 0; i < 3; i++) { int b = lane * 3 + i; if (b < nnodes) nInfo[b] = (uint32_t)off | ((uint32_t)c[i] << 16); off += c[i]; }
        if (lane == 31 && x > SLOT_CAP) ctrl[1] = 1;
        if (lane == 0) ctrl[0] = 3;
    }
    __syncthreads();
    if (ctrl[1] == 0) {
        uint16_t* sid = (uint16_t*)(smem + SM_SID);
        uint2* meta = (uint2*)(smem + SM_META);
        for (int i = tid; i < total; i += NT) {
            uint4 r = lds128(stage + i * 16);
            int pos = (int)(nInfo[r.z >> 16] & 0xffffu) + (int)r.w;
            sid[pos]  = (uint16_t)(r.x & 0xffffu);
            meta[pos] = make_uint2(((r.x >> 16) << 5) | (r.z << 16), r.y);
        }
        for (int i = tid; i < nnodes * 16; i += NT) {
            int nl = i >> 4, c = nCnt[nl];
            int j = (c & ~15) + (i & 15);
            if (j >= c && (j < 16 || (c & 15))) {
                int pos = (int)(nInfo[nl] & 0xffffu) + j;
                sid[pos]  = 0xffffu;
                meta[pos] = make_uint2((uint32_t)TAB_ZERO << 5, 0u);
            }
        }
    }
    fence_async_smem();
    __syncthreads();
    if (tid == 0 && ctrl[9] && ctrl[1] == 0) { mbar_expect_tx(bar_tab, TAB_BYTES); bulk_g2s(sb + SM_TABLE, g_table, TAB_BYTES, bar_tab); }
    STAMP(6);

    if (__shfl_sync(0xffffffffu, ctrl[1], 0) != 0) {
        float* acc = (float*)smem;
        if (ctrl[8] <= STAGE_SMALL) mbar_wait(bar_tab, 0);
        __syncthreads();
        for (int i = tid; i < nnodes * 256; i += NT) acc[i] = 0.f;
        __syncthreads();
        const uint16_t* posu = (const uint16_t*)p.pos;
        const uint32_t* tabg = (const uint32_t*)g_table;
        for (int e0 = warp * 32; e0 < p.E; e0 += NT) {
            int e = e0 + lane;
            int s = 0, d = 0;
            uint32_t db = 0xffff, rxy = 0, rz = 0;
            bool act = false;
            if (e < p.E) {
                s = p.src[e]; d = p.dst[e];
                if (d >= node0 && d < node0 + nnodes) {
                    uint32_t sxy = posu[s * 3] | ((uint32_t)posu[s * 3 + 1] << 16), sz = posu[s * 3 + 2];
                    uint32_t dxy = posu[d * 3] | ((uint32_t)posu[d * 3 + 1] << 16), dz = posu[d * 3 + 2];
                    db  = edge_dist(sxy, sz, dxy, dz, rxy, rz);
                    act = db <= D_MAX_BITS;
                }
            }
            unsigned m = __ballot_sync(0xffffffffu, act);
            while (m) {
                int l = __ffs(m) - 1;
                m &= m - 1;
                int es = __shfl_sync(0xffffffffu, s, l), ed = __shfl_sync(0xffffffffu, d, l);
                uint32_t edb = __shfl_sync(0xffffffffu, db, l), exy = __shfl_sync(0xffffffffu, rxy, l), ez = __shfl_sync(0xffffffffu, rz, l);
                float inv = 1.0f / __uint_as_float(edb << 16);
                float rh[3] = {rbf(bf_lo(exy) * inv), rbf(bf_hi(exy) * inv), rbf(bf_lo(ez) * inv)};
                uint4 f = __ldcg(&g_F[(size_t)es * 32 + lane]);
                float ps0 = 0.f, ps1 = 0.f, pr0 = 0.f, pr1 = 0.f;
                for (int j2 = 0; j2 < 32; j2++) {
                    uint32_t hj = __shfl_sync(0xffffffffu, f.x, j2);
                    uint32_t a0 = *(const uint32_t*)(p.w2 + (2 * j2) * 192 + 2 * lane), a1 = *(const uint32_t*)(p.w2 + (2 * j2 + 1) * 192 + 2 * lane);
                    uint32_t b0 = *(const uint32_t*)(p.w2 + (2 * j2) * 192 + 128 + 2 * lane), b1 = *(const uint32_t*)(p.w2 + (2 * j2 + 1) * 192 + 128 + 2 * lane);
                    ps0 += bf_lo(hj) * bf_lo(a0) + bf_hi(hj) * bf_lo(a1);
                    ps1 += bf_lo(hj) * bf_hi(a0) + bf_hi(hj) * bf_hi(a1);
                    pr0 += bf_lo(hj) * bf_lo(b0) + bf_hi(hj) * bf_lo(b1);
                    pr1 += bf_lo(hj) * bf_hi(b0) + bf_hi(hj) * bf_hi(b1);
                }
                float ws0 = 0.f, ws1 = 0.f, wv0 = 0.f, wv1 = 0.f, wr0 = 0.f, wr1 = 0.f;
                for (int k2 = 0; k2 < 8; k2++) {
                    uint32_t rk2 = __ldcg(tabg + (edb - D_MIN_BITS) * 8 + k2);
#pragma unroll
                    for (int h = 0; h < 2; h++) {
                        float rv = h ? bf_hi(rk2) : bf_lo(rk2);
                        const __nv_bfloat16* wrow = p.wr + (2 * k2 + h) * 192 + 2 * lane;
                        uint32_t a = *(const uint32_t*)wrow, b = *(const uint32_t*)(wrow + 64), c = *(const uint32_t*)(wrow + 128);
                        ws0 += rv * bf_lo(a); ws1 += rv * bf_hi(a);
                        wv0 += rv * bf_lo(b); wv1 += rv * bf_hi(b);
                        wr0 += rv * bf_lo(c); wr1 += rv * bf_hi(c);
                    }
                }
                float* a = acc + (ed - node0) * 256 + 2 * lane;
                atomicAdd(a, ps0 * ws0); atomicAdd(a + 1, ps1 * ws1);
                const uint32_t q[3] = {f.y, f.z, f.w};
#pragma unroll
                for (int c = 0; c < 3; c++) {
                    atomicAdd(a + 64 * (c + 1), wv0 * bf_lo(q[c]) + pr0 * wr0 * rh[c]);
                    atomicAdd(a + 64 * (c + 1) + 1, wv1 * bf_hi(q[c]) + pr1 * wr1 * rh[c]);
                }
            }
        }
        __syncthreads();
        for (int i = tid; i < nnodes * 128; i += NT) {
            uint32_t r = *(const uint32_t*)(p.sv + (size_t)node0 * 256 + 2 * i);
            *(uint32_t*)(p.out + (size_t)node0 * 256 + 2 * i) = pack_bf(bf_lo(r) + acc[2 * i], bf_hi(r) + acc[2 * i + 1]);
        }
        return;
    }

    const int wg = warp >> 2, w = warp & 3, t128 = tid & 127;
    const uint32_t coef0 = sb + SM_COEF + wg * 3 * 8192;
    const uint64_t Fb = (uint64_t)((const uint8_t*)g_F + w * 128 + g * 16);
    volatile int* wq = ctrl + 2 + wg * 2;
    const uint32_t sid_lane = sb + SM_SID + t * 4;
    auto fresh_tid = [&]() -> uint32_t { uint32_t x = tid; asm volatile("" : "+r"(x)); return x; };
    const uint32_t out_lane = (uint32_t)node0 * 512u + t * 128 + w * 32 + g * 4;

    auto make_item = [&](int nl, int chunk) -> int {
        const bool valid = nl < nnodes;
        const uint32_t info = valid ? nInfo[nl] : 0u;
        const int padded = info >> 16, cnt = valid ? nCnt[nl] : 0;
        const int G = min(4, (padded - 64 * chunk) >> 4);
        const int full = min(4, max(0, (cnt - 64 * chunk) >> 4));
        const int last = 64 * (chunk + 1) >= padded;
        const int z = valid ? (nl | ((((int)(info & 0xffffu) >> 4) + 4 * chunk) << 7) | (G << 16) | (full << 19) | (last << 22) | (1 << 23) | (chunk << 24)) : 0;
        return (int)__reduce_max_sync(0xffffffffu, (unsigned)z);
    };
#define IT_NODE(it)  ((it) & 0x7f)
#define IT_SLOT(it)  ((((it) >> 7) & 0x1ff) << 4)
#define IT_G(it)     (((it) >> 16) & 7)
#define IT_FULL(it)  (((it) >> 19) & 7)
#define IT_LAST(it)  (((it) >> 22) & 1)
#define IT_VALID(it) (((it) >> 23) & 1)
#define IT_CHUNK(it) ((int)((unsigned)(it) >> 24))
    auto produce = [&](const int it, uint32_t cbuf) {
        const uint32_t ft = fresh_tid();
        const uint32_t r = (ft & 127u) >> 1;
        const uint32_t prod_off = r * 128 + (((4 * (ft & 1)) ^ (r & 7)) << 4);
        if (r < 16u * IT_G(it)) {
            uint2 m = lds64(sb + SM_META + (IT_SLOT(it) + r) * 8);
            uint32_t ta = sb + SM_TABLE + (m.x & 0xffffu);
            uint4 t0 = lds128(ta), t1 = lds128(ta + 16);
            const bool half = ft & 1;
            uint32_t mA = half ? __byte_perm(m.y, 0, 0x3232) : 0x3f803f80u;
            uint32_t mB = __byte_perm(m.x, m.y, half ? 0x3232 : 0x5454);
            uint32_t a = cbuf + prod_off;
            sts128(a,        make_uint4(hmul2(t0.x, mA), hmul2(t0.y, mA), hmul2(t0.z, mA), hmul2(t0.w, mA)));
            sts128(a ^ 0x10, make_uint4(hmul2(t1.x, mA), hmul2(t1.y, mA), hmul2(t1.z, mA), hmul2(t1.w, mA)));
            sts128(a ^ 0x20, make_uint4(hmul2(t0.x, mB), hmul2(t0.y, mB), hmul2(t0.z, mB), hmul2(t0.w, mB)));
            sts128(a ^ 0x30, make_uint4(hmul2(t1.x, mB), hmul2(t1.y, mB), hmul2(t1.z, mB), hmul2(t1.w, mB)));
        }
    };
    uint4 buf[4][4];
    auto issue_group = [&](const int it, int s, uint4 (&b)[4]) {
        if (s < IT_G(it)) {
            const uint32_t a = sid_lane + IT_SLOT(it) * 2 + s * 32;
            const uint32_t p0 = lds32(a), p1 = lds32(a + 16);
            if (s < IT_FULL(it)) {
                ld_row(b[0], Fb, p0 & 0xffffu, p.row_bytes); ld_row(b[1], Fb, p0 >> 16, p.row_bytes);
                ld_row(b[2], Fb, p1 & 0xffffu, p.row_bytes); ld_row(b[3], Fb, p1 >> 16, p.row_bytes);
            } else {
                ld_row_pad(b[0], Fb, p0 & 0xffffu, p.row_bytes); ld_row_pad(b[1], Fb, p0 >> 16, p.row_bytes);
                ld_row_pad(b[2], Fb, p1 & 0xffffu, p.row_bytes); ld_row_pad(b[3], Fb, p1 >> 16, p.row_bytes);
            }
        } else {
            kill_row(b[0]); kill_row(b[1]); kill_row(b[2]); kill_row(b[3]);
        }
    };
    auto load_resid = [&](const int it) -> uint32_t {
        uint32_t r = 0;
        if (IT_LAST(it)) r = __ldg((const uint32_t*)((const uint8_t*)p.sv + (out_lane + (uint32_t)IT_NODE(it) * 512u)));
        return r;
    };

    float ys[8], yv[24], dQ[3][8];
#pragma unroll
    for (int i = 0; i < 24; i++) yv[i] = 0.f;
#pragma unroll
    for (int i = 0; i < 8; i++) { ys[i] = 0.f; dQ[0][i] = 0.f; dQ[1][i] = 0.f; dQ[2][i] = 0.f; }

    int cur = make_item(wg, 0);
    int nxt;
    {
#pragma unroll
        for (int s = 0; s < 4; s++) issue_group(cur, s, buf[s]);
        if (IT_LAST(cur) && t128 == 0) wq[0] = atomicAdd((int*)&ctrl[0], 1);
        mbar_wait(bar_tab, 0);
        STAMP(7);
        produce(cur, coef0);
        fence_async_smem();
        wg_barrier();
        if (!IT_VALID(cur)) nxt = cur;
        else nxt = IT_LAST(cur) ? make_item(wq[0], 0) : make_item(IT_NODE(cur), IT_CHUNK(cur) + 1);
    }
    uint32_t resid = load_resid(cur);
    int it_idx = 0;
    int par = 1;
    const uint32_t dcoef0 = desc_lo(coef0), dw2 = desc_lo(sb + SM_W2T);

    while (IT_VALID(cur)) {
        const uint32_t cbuf = coef0 + it_idx * 8192;
        const uint32_t dcur = dcoef0 + it_idx * 512;
        const int nidx = it_idx == 2 ? 0 : it_idx + 1;
        {
            uint32_t x = buf[0][0].x ^ buf[1][0].x ^ buf[2][0].x ^ buf[3][0].x ^ resid;
            if (x == 0x9e3779b1u) sts32(sb + SM_CTRL + 60, x);
        }
#pragma unroll
        for (int s = 0; s < 4; s++) {
            if (s < IT_G(cur)) {
                if (s > 0) wg_wait0();
                uint32_t A[4][4];
                const uint32_t* b0 = &buf[s][0].x; const uint32_t* b1 = &buf[s][1].x;
                const uint32_t* b2 = &buf[s][2].x; const uint32_t* b3 = &buf[s][3].x;
#pragma unroll
                for (int c = 0; c < 4; c++) {
                    A[c][0] = __byte_perm(b0[c], b1[c], 0x5410);
                    A[c][1] = __byte_perm(b0[c], b1[c], 0x7632);
                    A[c][2] = __byte_perm(b2[c], b3[c], 0x5410);
                    A[c][3] = __byte_perm(b2[c], b3[c], 0x7632);
                }
                const int sc = (s > 0) || (IT_CHUNK(cur) > 0);
                wg_fence();
                wgmma_rs_n64(ys, yv, A[0], dcur + s * 128, sc);
                wgmma_rs_n16(dQ[0], A[1], dcur + s * 128, sc);
                wgmma_rs_n16(dQ[1], A[2], dcur + s * 128, sc);
                wgmma_rs_n16(dQ[2], A[3], dcur + s * 128, sc);
                wg_commit();
            }
            issue_group(nxt, s, buf[s]);
        }
        if (IT_LAST(nxt) && t128 == 0) wq[par] = atomicAdd((int*)&ctrl[0], 1);
        wg_wait0();
        produce(nxt, coef0 + nidx * 8192);
        fence_async_smem();
        wg_barrier();

        if (IT_LAST(cur)) {
            {
                const uint32_t ft = fresh_tid();
                const uint32_t a = cbuf + ((ft >> 5) & 3u) * 2048u + (ft & 15u) * 128u + ((((ft >> 4) & 1u) ^ (ft & 7u)) << 4);
                stsm4(a, pack_bf(ys[0], ys[1]), pack_bf(ys[2], ys[3]), pack_bf(ys[4], ys[5]), pack_bf(ys[6], ys[7]));
#pragma unroll
                for (int i = 0; i < 6; i += 2) {
                    stsm4(a ^ ((i + 2) << 4),
                          pack_bf(yv[4 * i], yv[4 * i + 1]), pack_bf(yv[4 * i + 2], yv[4 * i + 3]),
                          pack_bf(yv[4 * i + 4], yv[4 * i + 5]), pack_bf(yv[4 * i + 6], yv[4 * i + 7]));
                }
            }
            fence_async_smem();
            wg_barrier();
            wg_fence();
#pragma unroll
            for (int ks = 0; ks < 4; ks++) {
                wgmma_ss_n16(ys, dw2 + ks * 128, dcur + ks * 128, ks);
                wgmma_ss_n48(yv, dw2 + 512 + ks * 128, dcur + ks * 128 + 2, ks);
            }
            wg_commit();
            const uint32_t wa = sb + SM_WTAB + t128 * 16;
            float pr[4][2];
            {
                uint4 v0 = lds128(wa + 2 * 2048), v1 = lds128(wa + 3 * 2048);
#pragma unroll
                for (int a = 0; a < 3; a++) {
                    const float* q = dQ[a];
                    pr[a + 1][0] = __uint_as_float(v0.x) * q[0] + __uint_as_float(v0.y) * q[1] + __uint_as_float(v1.x) * q[4] + __uint_as_float(v1.y) * q[5];
                    pr[a + 1][1] = __uint_as_float(v0.z) * q[2] + __uint_as_float(v0.w) * q[3] + __uint_as_float(v1.z) * q[6] + __uint_as_float(v1.w) * q[7];
                }
            }
            uint4 u0 = lds128(wa), u1 = lds128(wa + 2048), x0 = lds128(wa + 4 * 2048), x1 = lds128(wa + 5 * 2048);
            wg_wait0();
            pr[0][0] = __uint_as_float(u0.x) * ys[0] + __uint_as_float(u0.y) * ys[1] + __uint_as_float(u1.x) * ys[4] + __uint_as_float(u1.y) * ys[5];
            pr[0][1] = __uint_as_float(u0.z) * ys[2] + __uint_as_float(u0.w) * ys[3] + __uint_as_float(u1.z) * ys[6] + __uint_as_float(u1.w) * ys[7];
#pragma unroll
            for (int a = 0; a < 3; a++) {
                const float* y = yv + 8 * a;
                pr[a + 1][0] += __uint_as_float(x0.x) * y[0] + __uint_as_float(x0.y) * y[1] + __uint_as_float(x1.x) * y[4] + __uint_as_float(x1.y) * y[5];
                pr[a + 1][1] += __uint_as_float(x0.z) * y[2] + __uint_as_float(x0.w) * y[3] + __uint_as_float(x1.z) * y[6] + __uint_as_float(x1.w) * y[7];
            }
            const bool hi2 = t & 2, hi1 = t & 1;
            float ka0 = hi2 ? pr[2][0] : pr[0][0], ka1 = hi2 ? pr[2][1] : pr[0][1];
            float kb0 = hi2 ? pr[3][0] : pr[1][0], kb1 = hi2 ? pr[3][1] : pr[1][1];
            float sa0 = hi2 ? pr[0][0] : pr[2][0], sa1 = hi2 ? pr[0][1] : pr[2][1];
            float sb0 = hi2 ? pr[1][0] : pr[3][0], sb1 = hi2 ? pr[1][1] : pr[3][1];
            ka0 += __shfl_xor_sync(0xffffffffu, sa0, 2); ka1 += __shfl_xor_sync(0xffffffffu, sa1, 2);
            kb0 += __shfl_xor_sync(0xffffffffu, sb0, 2); kb1 += __shfl_xor_sync(0xffffffffu, sb1, 2);
            float k0 = hi1 ? kb0 : ka0, k1 = hi1 ? kb1 : ka1;
            float s0 = hi1 ? ka0 : kb0, s1 = hi1 ? ka1 : kb1;
            k0 += __shfl_xor_sync(0xffffffffu, s0, 1);
            k1 += __shfl_xor_sync(0xffffffffu, s1, 1);
            *(uint32_t*)((uint8_t*)p.out + (out_lane + (uint32_t)IT_NODE(cur) * 512u)) = pack_bf(bf_lo(resid) + k0, bf_hi(resid) + k1);
        }
        resid = load_resid(nxt);
        cur = nxt;
        if (IT_VALID(nxt)) nxt = IT_LAST(nxt) ? make_item(wq[par], 0) : make_item(IT_NODE(nxt), IT_CHUNK(nxt) + 1);
        par ^= 1;
        it_idx = nidx;
    }
    STAMP(8);
}

}

extern "C" void kernel_launch(void* const* d_in, const int* in_sizes, int n_in, void* d_out, int out_size) {
    (void)n_in; (void)out_size;
    static int n_sm = 0;
    if (n_sm == 0) {
        int dev = 0;
        cudaGetDevice(&dev);
        cudaDeviceGetAttribute(&n_sm, cudaDevAttrMultiProcessorCount, dev);
        cudaFuncSetAttribute(painn_kernel, cudaFuncAttributeMaxDynamicSharedMemorySize, SM_TOTAL);
    }
    Params p;
    p.sv    = (const __nv_bfloat16*)d_in[0];
    p.pos   = (const __nv_bfloat16*)d_in[1];
    p.src   = (const int*)d_in[2];
    p.dst   = (const int*)d_in[3];
    p.freqs = (const __nv_bfloat16*)d_in[4];
    p.w1    = (const __nv_bfloat16*)d_in[5];
    p.w2    = (const __nv_bfloat16*)d_in[6];
    p.wr    = (const __nv_bfloat16*)d_in[7];
    p.out   = (__nv_bfloat16*)d_out;
    p.N = in_sizes[1] / 3;
    p.E = in_sizes[2];
    p.ncta = n_sm < MAX_CTA ? n_sm : MAX_CTA;
    p.npc = (p.N + p.ncta - 1) / p.ncta;
    p.npc_magic = (uint32_t)(0x100000000ull / (uint32_t)p.npc) + 1u;
    p.quads_per_cta = ((p.E >> 2) + p.ncta - 1) / p.ncta;
    p.row_bytes = 512;
    if (p.N > MAX_N || p.npc > MAX_NPC || (p.E & 3) || p.quads_per_cta > MAX_ROUNDS * 32) return;

    cudaLaunchConfig_t cfg = {};
    cfg.gridDim = dim3(p.ncta);
    cfg.blockDim = dim3(NT);
    cfg.dynamicSmemBytes = SM_TOTAL;
    cfg.stream = cudaStreamPerThread;
    cudaLaunchAttribute attr[1];
    attr[0].id = cudaLaunchAttributeCooperative;
    attr[0].val.cooperative = 1;
    cfg.attrs = attr;
    cfg.numAttrs = 1;
    cudaLaunchKernelEx(&cfg, painn_kernel, p);
}
```

```cpp
#include <cuda_runtime.h>
#include <cuda.h>
#include <cuda_bf16.h>
#include <stdint.h>

namespace {

constexpr int NT        = 512;
constexpr int MAX_N     = 10240;
constexpr int MAX_CTA   = 144;
constexpr int MAX_NPC   = 80;
constexpr int MAX_ROUNDS = 38;
constexpr int REC_CAP   = MAX_ROUNDS * 128;
constexpr int SLOT_CAP  = 6144;
constexpr int NSTAGE    = 5;
constexpr int STAGE_B   = 12288;

constexpr uint32_t D_MIN_BITS = 0x38D2;
constexpr uint32_t D_MAX_BITS = 0x409C;
constexpr int TAB_ROWS  = (int)(D_MAX_BITS - D_MIN_BITS) + 1;
constexpr int TAB_ZERO  = TAB_ROWS;
constexpr int TAB_BYTES = (TAB_ROWS + 1) * 32;

constexpr int SM_RING   = 0;
constexpr int SM_HT     = SM_RING + 2 * NSTAGE * STAGE_B;
constexpr int SM_META   = SM_HT + 16384;
constexpr int SM_SID    = SM_META + SLOT_CAP * 8;
constexpr int SM_P2END  = SM_SID + SLOT_CAP * 2;
constexpr int P1_POS    = 0;
constexpr int P1_STAGE  = 61440;
constexpr int P1_SV     = P1_STAGE + REC_CAP * 16;
constexpr int P1_W1     = P1_SV + MAX_NPC * 512;
constexpr int P1_END    = P1_W1 + 8192;
constexpr int SM_W2     = SM_P2END;
constexpr int SM_MISC   = SM_W2 + 24576;
static_assert(P1_END <= SM_W2, "phase 1 overlay");
constexpr int SM_BINCNT = SM_MISC;
constexpr int SM_BINOFF = SM_BINCNT + MAX_CTA * 4;
constexpr int SM_NCNT   = SM_BINOFF + MAX_CTA * 4;
constexpr int SM_NINFO  = SM_NCNT + MAX_NPC * 4;
constexpr int SM_CTRL   = SM_NINFO + MAX_NPC * 4;
constexpr int SM_BARS   = SM_CTRL + 64;
constexpr int SM_TOTAL  = SM_BARS + (4 + 4 * NSTAGE) * 8;
constexpr int STAGE_CAP = SM_META / 16;
static_assert(P1_SV % 1024 == 0 && P1_W1 % 1024 == 0 && SM_W2 % 1024 == 0 && SM_HT % 1024 == 0, "alignment");
static_assert(SM_TOTAL <= 232448, "smem");
static_assert(SM_BARS % 8 == 0, "mbarrier alignment");
static_assert(MAX_N * 6 <= P1_STAGE, "pos");
static_assert(MAX_NPC * 1024 <= SM_MISC, "slow path accumulators");

__device__ __align__(1024) uint4 g_F[MAX_N * 32];
__device__ uint4    g_rec[MAX_CTA * REC_CAP];
__device__ uint32_t g_offs[MAX_CTA * MAX_CTA];
__device__ uint4    g_table[(TAB_BYTES + 15) / 16];
__device__ unsigned g_bar;
#define STAMP(k)

struct Params {
    const __nv_bfloat16* sv;
    const __nv_bfloat16* pos;
    const int*           src;
    const int*           dst;
    const __nv_bfloat16* freqs;
    const __nv_bfloat16* w1;
    const __nv_bfloat16* w2;
    const __nv_bfloat16* wr;
    __nv_bfloat16*       out;
    int N, E, ncta, npc;
    uint32_t npc_magic;
    int quads_per_cta;
};

__device__ __forceinline__ uint32_t smem_u32(const void* p) { return (uint32_t)__cvta_generic_to_shared(p); }
__device__ __forceinline__ float bf_lo(uint32_t v) { return __uint_as_float(v << 16); }
__device__ __forceinline__ float bf_hi(uint32_t v) { return __uint_as_float(v & 0xffff0000u); }
__device__ __forceinline__ float bf_u16(uint16_t v) { return __uint_as_float((uint32_t)v << 16); }
__device__ __forceinline__ uint32_t pack_bf(float lo, float hi) {
    uint32_t r;
    asm("cvt.rn.bf16x2.f32 %0, %1, %2;" : "=r"(r) : "f"(hi), "f"(lo));
    return r;
}
__device__ __forceinline__ float rbf(float x) { return bf_lo(pack_bf(x, 0.f)); }
__device__ __forceinline__ uint32_t hmul2(uint32_t a, uint32_t b) {
    uint32_t r;
    asm("mul.rn.bf16x2 %0, %1, %2;" : "=r"(r) : "r"(a), "r"(b));
    return r;
}
__device__ __forceinline__ uint32_t hsub2(uint32_t a, uint32_t b) {
    uint32_t r;
    asm("sub.rn.bf16x2 %0, %1, %2;" : "=r"(r) : "r"(a), "r"(b));
    return r;
}
__device__ __forceinline__ uint32_t lds32(uint32_t a) { uint32_t v; asm volatile("ld.shared.u32 %0, [%1];" : "=r"(v) : "r"(a)); return v; }
__device__ __forceinline__ uint32_t lds16(uint32_t a) { uint16_t v; asm volatile("ld.shared.u16 %0, [%1];" : "=h"(v) : "r"(a)); return v; }
__device__ __forceinline__ uint2 lds64(uint32_t a) { uint2 v; asm volatile("ld.shared.v2.u32 {%0,%1}, [%2];" : "=r"(v.x), "=r"(v.y) : "r"(a)); return v; }
__device__ __forceinline__ uint4 lds128(uint32_t a) { uint4 v; asm volatile("ld.shared.v4.u32 {%0,%1,%2,%3}, [%4];" : "=r"(v.x), "=r"(v.y), "=r"(v.z), "=r"(v.w) : "r"(a)); return v; }
__device__ __forceinline__ void sts32(uint32_t a, uint32_t v) { asm volatile("st.shared.u32 [%0], %1;" ::"r"(a), "r"(v) : "memory"); }
__device__ __forceinline__ void sts128(uint32_t a, uint4 v) { asm volatile("st.shared.v4.u32 [%0], {%1,%2,%3,%4};" ::"r"(a), "r"(v.x), "r"(v.y), "r"(v.z), "r"(v.w) : "memory"); }
__device__ __forceinline__ void mbar_init(uint32_t bar, int cnt) { asm volatile("mbarrier.init.shared::cta.b64 [%0], %1;" ::"r"(bar), "r"(cnt) : "memory"); }
__device__ __forceinline__ void mbar_expect_tx(uint32_t bar, uint32_t bytes) { asm volatile("mbarrier.arrive.expect_tx.shared::cta.b64 _, [%0], %1;" ::"r"(bar), "r"(bytes) : "memory"); }
__device__ __forceinline__ void mbar_arrive(uint32_t bar) { asm volatile("mbarrier.arrive.shared::cta.b64 _, [%0];" ::"r"(bar) : "memory"); }
__device__ __forceinline__ void mbar_wait(uint32_t bar, uint32_t parity) {
    uint32_t done;
    int spins = 0;
    do {
        asm volatile("{\n.reg .pred p;\nmbarrier.try_wait.parity.shared::cta.b64 p, [%1], %2;\nselp.u32 %0, 1, 0, p;\n}"
                     : "=r"(done) : "r"(bar), "r"(parity) : "memory");
    } while (!done && ++spins < (1 << 22));
}
__device__ __forceinline__ void bulk_g2s(uint32_t dst, const void* src, uint32_t bytes, uint32_t bar) {
    asm volatile("cp.async.bulk.shared::cluster.global.mbarrier::complete_tx::bytes [%0], [%1], %2, [%3];"
                 ::"r"(dst), "l"(src), "r"(bytes), "r"(bar) : "memory");
}
__device__ __forceinline__ void tma_load(uint32_t dst, const CUtensorMap* tm, int line, uint32_t bar) {
    asm volatile("cp.async.bulk.tensor.2d.shared::cluster.global.mbarrier::complete_tx::bytes [%0], [%1, {%3, %4}], [%2];"
                 ::"r"(dst), "l"(tm), "r"(bar), "r"(0), "r"(line) : "memory");
}
__device__ __forceinline__ void tma_store(const CUtensorMap* tm, int line, uint32_t src) {
    asm volatile("cp.async.bulk.tensor.2d.global.shared::cta.bulk_group [%0, {%2, %3}], [%1];"
                 ::"l"(tm), "r"(src), "r"(0), "r"(line) : "memory");
}
__device__ __forceinline__ void fence_async_smem() { asm volatile("fence.proxy.async.shared::cta;" ::: "memory"); }
__device__ __forceinline__ void named_barrier(int id) { asm volatile("bar.sync %0, 128;" ::"r"(id) : "memory"); }
__device__ __forceinline__ void ldsm4(uint32_t (&r)[4], uint32_t a) {
    asm volatile("ldmatrix.sync.aligned.m8n8.x4.shared.b16 {%0,%1,%2,%3}, [%4];" : "=r"(r[0]), "=r"(r[1]), "=r"(r[2]), "=r"(r[3]) : "r"(a) : "memory");
}
__device__ __forceinline__ void ldsm4t(uint32_t (&r)[4], uint32_t a) {
    asm volatile("ldmatrix.sync.aligned.m8n8.x4.trans.shared.b16 {%0,%1,%2,%3}, [%4];" : "=r"(r[0]), "=r"(r[1]), "=r"(r[2]), "=r"(r[3]) : "r"(a) : "memory");
}
__device__ __forceinline__ void stsm4(uint32_t a, uint32_t r0, uint32_t r1, uint32_t r2, uint32_t r3) {
    asm volatile("stmatrix.sync.aligned.m8n8.x4.shared.b16 [%0], {%1,%2,%3,%4};" ::"r"(a), "r"(r0), "r"(r1), "r"(r2), "r"(r3) : "memory");
}
__device__ __forceinline__ void mma16816(float (&c)[4], const uint32_t (&a)[4], uint32_t b0, uint32_t b1) {
    asm volatile("mma.sync.aligned.m16n8k16.row.col.f32.bf16.bf16.f32 {%0,%1,%2,%3}, {%4,%5,%6,%7}, {%8,%9}, {%0,%1,%2,%3};"
                 : "+f"(c[0]), "+f"(c[1]), "+f"(c[2]), "+f"(c[3])
                 : "r"(a[0]), "r"(a[1]), "r"(a[2]), "r"(a[3]), "r"(b0), "r"(b1));
}

__device__ __forceinline__ uint32_t desc_lo(uint32_t saddr) { return ((saddr & 0x3FFFF) >> 4) | (1u << 16); }
#define DESC_HI "0x40000040"
__device__ __forceinline__ void wg_fence() { asm volatile("wgmma.fence.sync.aligned;" ::: "memory"); }
__device__ __forceinline__ void wg_commit() { asm volatile("wgmma.commit_group.sync.aligned;" ::: "memory"); }
__device__ __forceinline__ void wg_wait0() { asm volatile("wgmma.wait_group.sync.aligned 0;" ::: "memory"); }

__device__ __forceinline__ void wgmma_n64(float (&d)[8], float (&e)[24], const uint32_t (&a)[4], uint32_t bdesc, int scale) {
    asm volatile("{\n.reg .pred p;\n.reg .b64 b;\nsetp.ne.b32 p, %37, 0;\nmov.b64 b, {%36, " DESC_HI "};\n"
                 "wgmma.mma_async.sync.aligned.m64n64k16.f32.bf16.bf16 "
                 "{%0,%1,%2,%3,%4,%5,%6,%7,%8,%9,%10,%11,%12,%13,%14,%15,%16,%17,%18,%19,%20,%21,%22,%23,%24,%25,%26,%27,%28,%29,%30,%31}, "
                 "{%32,%33,%34,%35}, b, p, 1, 1, 1;\n}"
                 : "+f"(d[0]), "+f"(d[1]), "+f"(d[2]), "+f"(d[3]), "+f"(d[4]), "+f"(d[5]), "+f"(d[6]), "+f"(d[7]),
                   "+f"(e[0]), "+f"(e[1]), "+f"(e[2]), "+f"(e[3]), "+f"(e[4]), "+f"(e[5]), "+f"(e[6]), "+f"(e[7]),
                   "+f"(e[8]), "+f"(e[9]), "+f"(e[10]), "+f"(e[11]), "+f"(e[12]), "+f"(e[13]), "+f"(e[14]), "+f"(e[15]),
                   "+f"(e[16]), "+f"(e[17]), "+f"(e[18]), "+f"(e[19]), "+f"(e[20]), "+f"(e[21]), "+f"(e[22]), "+f"(e[23])
                 : "r"(a[0]), "r"(a[1]), "r"(a[2]), "r"(a[3]), "r"(bdesc), "r"(scale));
}
__device__ __forceinline__ void wgmma_n48(float (&e)[24], const uint32_t (&a)[4], uint32_t bdesc, int scale) {
    asm volatile("{\n.reg .pred p;\n.reg .b64 b;\nsetp.ne.b32 p, %29, 0;\nmov.b64 b, {%28, " DESC_HI "};\n"
                 "wgmma.mma_async.sync.aligned.m64n48k16.f32.bf16.bf16 "
                 "{%0,%1,%2,%3,%4,%5,%6,%7,%8,%9,%10,%11,%12,%13,%14,%15,%16,%17,%18,%19,%20,%21,%22,%23}, "
                 "{%24,%25,%26,%27}, b, p, 1, 1, 1;\n}"
                 : "+f"(e[0]), "+f"(e[1]), "+f"(e[2]), "+f"(e[3]), "+f"(e[4]), "+f"(e[5]), "+f"(e[6]), "+f"(e[7]),
                   "+f"(e[8]), "+f"(e[9]), "+f"(e[10]), "+f"(e[11]), "+f"(e[12]), "+f"(e[13]), "+f"(e[14]), "+f"(e[15]),
                   "+f"(e[16]), "+f"(e[17]), "+f"(e[18]), "+f"(e[19]), "+f"(e[20]), "+f"(e[21]), "+f"(e[22]), "+f"(e[23])
                 : "r"(a[0]), "r"(a[1]), "r"(a[2]), "r"(a[3]), "r"(bdesc), "r"(scale));
}
__device__ __forceinline__ void wgmma_n16(float (&d)[8], const uint32_t (&a)[4], uint32_t bdesc, int scale) {
    asm volatile("{\n.reg .pred p;\n.reg .b64 b;\nsetp.ne.b32 p, %13, 0;\nmov.b64 b, {%12, " DESC_HI "};\n"
                 "wgmma.mma_async.sync.aligned.m64n16k16.f32.bf16.bf16 {%0,%1,%2,%3,%4,%5,%6,%7}, {%8,%9,%10,%11}, b, p, 1, 1, 1;\n}"
                 : "+f"(d[0]), "+f"(d[1]), "+f"(d[2]), "+f"(d[3]), "+f"(d[4]), "+f"(d[5]), "+f"(d[6]), "+f"(d[7])
                 : "r"(a[0]), "r"(a[1]), "r"(a[2]), "r"(a[3]), "r"(bdesc), "r"(scale));
}

__device__ __forceinline__ uint32_t edge_dist(uint32_t sxy, uint32_t sz, uint32_t dxy, uint32_t dz, uint32_t& rxy, uint32_t& rz) {
    rxy = hsub2(sxy, dxy);
    rz  = hsub2(sz, dz);
    uint32_t qxy = hmul2(rxy, rxy), qz = hmul2(rz, rz);
    float ss = rbf((bf_lo(qxy) + bf_hi(qxy)) + bf_lo(qz));
    float s2 = rbf(ss + 1e-8f);
    float d;
    asm("sqrt.approx.ftz.f32 %0, %1;" : "=f"(d) : "f"(s2));
    return pack_bf(d, 0.f) & 0xffffu;
}

__device__ __forceinline__ void load_pos(uint32_t sm_pos, int i, uint32_t& xy, uint32_t& z) {
    uint32_t a  = (sm_pos + 6u * (uint32_t)i) & ~3u;
    uint32_t w0 = lds32(a), w1 = lds32(a + 4);
    uint32_t sh = (uint32_t)i << 4;
    xy = __funnelshift_r(w0, w1, sh);
    z  = __funnelshift_r(w1, w1, sh);
}

__device__ __noinline__ float radial_value(float d, float f) {
    float arg = rbf(d * f);
    float sn  = rbf(sinf(arg));
    float rb  = rbf(__fdiv_rn(sn, d));
    float c   = rbf(cosf(rbf(__fdiv_rn(rbf(d * 3.14159265358979323846f), 5.0f))));
    float fc  = rbf(0.5f * rbf(c + 1.0f));
    return rb * fc;
}

__global__ void __launch_bounds__(NT, 1)
painn_kernel(const Params p, const __grid_constant__ CUtensorMap tmF, const __grid_constant__ CUtensorMap tmSV,
             const __grid_constant__ CUtensorMap tmW1, const __grid_constant__ CUtensorMap tmW2) {
    extern __shared__ __align__(1024) uint8_t smem[];
    const uint32_t sb   = smem_u32(smem);
    const int tid  = threadIdx.x, lane = tid & 31, warp = __shfl_sync(0xffffffffu, tid >> 5, 0);
    const int cta  = blockIdx.x;
    const int g    = lane >> 2, t = lane & 3;
    int* binCnt = (int*)(smem + SM_BINCNT);
    int* binOff = (int*)(smem + SM_BINOFF);
    int* nCnt   = (int*)(smem + SM_NCNT);
    uint32_t* nInfo = (uint32_t*)(smem + SM_NINFO);
    volatile int* ctrl = (volatile int*)(smem + SM_CTRL);
    const uint32_t bar_pos = sb + SM_BARS, bar_mlp = bar_pos + 8, bar_rec = bar_pos + 16;
    const uint32_t bar_full = bar_pos + 32, bar_empty = bar_full + 2 * NSTAGE * 8;

    const int node0  = cta * p.npc;
    const int nnodes = max(0, min(p.npc, p.N - node0));

    STAMP(0);
    if (tid == 0) {
        mbar_init(bar_pos, 1);
        mbar_init(bar_mlp, 1);
        mbar_init(bar_rec, 1);
        for (int i = 0; i < 2 * NSTAGE; i++) { mbar_init(bar_full + 8 * i, 1); mbar_init(bar_empty + 8 * i, 4); }
        asm volatile("fence.mbarrier_init.release.cluster;" ::: "memory");
        uint32_t pos_bytes = (uint32_t)(p.N * 6 + 15) & ~15u;
        mbar_expect_tx(bar_pos, pos_bytes);
        bulk_g2s(sb + P1_POS, p.pos, pos_bytes, bar_pos);
        mbar_expect_tx(bar_mlp, 2u * 160u * 128u + 8192u + 24576u);
        tma_load(sb + P1_SV, &tmSV, node0 * 4, bar_mlp);
        tma_load(sb + P1_SV + 160 * 128, &tmSV, node0 * 4 + 160, bar_mlp);
        tma_load(sb + P1_W1, &tmW1, 0, bar_mlp);
        tma_load(sb + SM_W2, &tmW2, 0, bar_mlp);
    }
    const bool mlp_warp = warp >= 11;
    int4 s4[3], d4[3];
    const int q0 = cta * p.quads_per_cta;
    const int qend = min(q0 + p.quads_per_cta, p.E >> 2);
    if (!mlp_warp) {
#pragma unroll
        for (int k = 0; k < 3; k++) {
            int q = q0 + (warp + 11 * k) * 32 + lane;
            bool ok = q < qend;
            s4[k] = ok ? __ldg((const int4*)p.src + q) : make_int4(-1, -1, -1, -1);
            d4[k] = ok ? __ldg((const int4*)p.dst + q) : make_int4(0, 0, 0, 0);
        }
    } else {
        int q = q0 + (33 + warp - 11) * 32 + lane;
        if (q < qend && (lane & 7) == 0) {
            asm volatile("prefetch.global.L2 [%0];" ::"l"((const int4*)p.src + q));
            asm volatile("prefetch.global.L2 [%0];" ::"l"((const int4*)p.dst + q));
        }
    }
    if (tid < MAX_CTA) binCnt[tid] = 0;
    if (tid < MAX_NPC) nCnt[tid] = 0;
    if (tid < 16) ctrl[tid] = 0;
    if (tid >= 448 && tid < 448 + 48) {
        asm volatile("prefetch.global.L2 [%0];" ::"l"((const uint8_t*)p.wr + (tid - 448) * 128));
    }
    __syncthreads();

    if (mlp_warp) {
        const int rows_per = (TAB_ROWS + 1 + p.ncta - 1) / p.ncta;
        for (int i = tid - 11 * 32; i < rows_per * 8; i += 5 * 32) {
            int row = cta * rows_per + (i >> 3), kp = i & 7;
            if (row <= TAB_ROWS) {
                uint32_t val = 0;
                if (row < TAB_ROWS) {
                    float d = __uint_as_float((D_MIN_BITS + row) << 16);
                    uint32_t f2 = __ldg((const uint32_t*)p.freqs + kp);
                    val = pack_bf(radial_value(d, bf_lo(f2)), radial_value(d, bf_hi(f2)));
                }
                ((uint32_t*)g_table)[row * 8 + kp] = val;
            }
        }
        const int mt = warp - 11;
        if (mt * 16 < nnodes) {
            mbar_wait(bar_mlp, 0);
            float acc[8][4];
#pragma unroll
            for (int i = 0; i < 8; i++) { acc[i][0] = acc[i][1] = acc[i][2] = acc[i][3] = 0.f; }
            const int lrow = (lane & 7) + ((lane >> 3) & 1) * 8, lch = lane >> 4;
#pragma unroll
            for (int ks = 0; ks < 4; ks++) {
                uint32_t a[4];
                const int line = 4 * (mt * 16 + lrow);
                ldsm4(a, sb + P1_SV + line * 128 + (((2 * ks + lch) ^ (line & 7)) << 4));
                const int kk = 16 * ks + lrow;
#pragma unroll
                for (int nt = 0; nt < 8; nt += 2) {
                    uint32_t b[4];
                    ldsm4t(b, sb + P1_W1 + kk * 128 + (((nt + lch) ^ (kk & 7)) << 4));
                    mma16816(acc[nt], a, b[0], b[1]);
                    mma16816(acc[nt + 1], a, b[2], b[3]);
                }
            }
            uint32_t hp[8][2];
#pragma unroll
            for (int i = 0; i < 8; i++) {
                float h[4];
#pragma unroll
                for (int q = 0; q < 4; q++) {
                    float x = rbf(acc[i][q]);
                    h[q] = __fdividef(x, 1.0f + __expf(-x));
                    acc[i][q] = 0.f;
                }
                hp[i][0] = pack_bf(h[0], h[1]);
                hp[i][1] = pack_bf(h[2], h[3]);
            }
#pragma unroll
            for (int ks = 0; ks < 4; ks++) {
                uint32_t a[4] = {hp[2 * ks][0], hp[2 * ks][1], hp[2 * ks + 1][0], hp[2 * ks + 1][1]};
                const int line = 3 * (16 * ks + lrow) + 1;
#pragma unroll
                for (int nt = 0; nt < 8; nt += 2) {
                    uint32_t b[4];
                    ldsm4t(b, sb + SM_W2 + line * 128 + (((nt + lch) ^ (line & 7)) << 4));
                    mma16816(acc[nt], a, b[0], b[1]);
                    mma16816(acc[nt + 1], a, b[2], b[3]);
                }
            }
            uint32_t q[3][8][2];
#pragma unroll
            for (int rh = 0; rh < 2; rh++) {
                const int row = mt * 16 + g + 8 * rh;
#pragma unroll
                for (int i = 0; i < 8; i++) {
                    const uint32_t ph = pack_bf(acc[i][2 * rh], acc[i][2 * rh + 1]);
#pragma unroll
                    for (int a = 0; a < 3; a++) {
                        const int line = 4 * row + 1 + a;
                        q[a][i][rh] = hmul2(ph, lds32(sb + P1_SV + line * 128 + ((i ^ (line & 7)) << 4) + 4 * t));
                    }
                }
            }
            __syncwarp();
            {
                const int row = mt * 16 + (lane & 7) + ((lane >> 3) & 1) * 8;
#pragma unroll
                for (int c = 0; c < 4; c++) {
                    const int line = 4 * row + c;
                    const uint32_t lb = sb + P1_SV + line * 128;
#pragma unroll
                    for (int i = 0; i < 8; i += 2) {
                        const uint32_t a = lb + (((i + lch) ^ (line & 7)) << 4);
                        if (c == 0) stsm4(a, hp[i][0], hp[i][1], hp[i + 1][0], hp[i + 1][1]);
                        else        stsm4(a, q[c - 1][i][0], q[c - 1][i][1], q[c - 1][i + 1][0], q[c - 1][i + 1][1]);
                    }
                }
            }
            fence_async_smem();
            __syncwarp();
            if (lane < 16 && mt * 16 + lane < nnodes) tma_store(&tmF, (node0 + mt * 16 + lane) * 4, sb + P1_SV + (mt * 16 + lane) * 512);
            asm volatile("cp.async.bulk.commit_group;" ::: "memory");
        }
        const int q = q0 + (33 + warp - 11) * 32 + lane;
        const bool ok = q < qend;
        s4[0] = ok ? __ldg((const int4*)p.src + q) : make_int4(-1, -1, -1, -1);
        d4[0] = ok ? __ldg((const int4*)p.dst + q) : make_int4(0, 0, 0, 0);
        s4[1] = s4[2] = make_int4(-1, -1, -1, -1);
        d4[1] = d4[2] = make_int4(0, 0, 0, 0);
    }
    mbar_wait(bar_pos, 0);
    STAMP(1);

    uint32_t r0[12], r1[12], r2[12], rk[12];
#pragma unroll
    for (int k = 0; k < 3; k++) {
        const int ss[4] = {s4[k].x, s4[k].y, s4[k].z, s4[k].w};
        const int dd[4] = {d4[k].x, d4[k].y, d4[k].z, d4[k].w};
#pragma unroll
        for (int j = 0; j < 4; j++) rk[k * 4 + j] = 0xffffffffu;
        if (ss[0] >= 0) {
#pragma unroll
            for (int j = 0; j < 4; j++) {
                const int e = k * 4 + j;
                const int s = ss[j], d = dd[j];
                uint32_t sxy, sz, dxy, dz, rxy, rz;
                load_pos(sb + P1_POS, s, sxy, sz);
                load_pos(sb + P1_POS, d, dxy, dz);
                uint32_t db = edge_dist(sxy, sz, dxy, dz, rxy, rz);
                float inv;
                asm("rcp.approx.ftz.f32 %0, %1;" : "=f"(inv) : "f"(__uint_as_float(db << 16)));
                uint32_t bin = __umulhi((uint32_t)d, p.npc_magic);
                uint32_t dl  = (uint32_t)d - bin * (uint32_t)p.npc;
                r0[e] = (uint32_t)s | ((db - D_MIN_BITS) << 16);
                r1[e] = pack_bf(bf_lo(rxy) * inv, bf_hi(rxy) * inv);
                r2[e] = __byte_perm(pack_bf(bf_lo(rz) * inv, 0.f), dl, 0x5410);
                if (db <= D_MAX_BITS) rk[e] = (uint32_t)atomicAdd(&binCnt[bin], 1) | (bin << 16);
            }
        }
    }
    STAMP(2);
    __syncthreads();
    STAMP(3);
    if (warp == 0) {
        int c[5], s = 0;
#pragma unroll
        for (int i = 0; i < 5; i++) { int b = lane * 5 + i; c[i] = b < p.ncta ? binCnt[b] : 0; s += c[i]; }
        int x = s;
#pragma unroll
        for (int o = 1; o < 32; o <<= 1) { int y = __shfl_up_sync(0xffffffffu, x, o); if (lane >= o) x += y; }
        int off = x - s;
#pragma unroll
        for (int i = 0; i < 5; i++) {
            int b = lane * 5 + i;
            if (b < p.ncta) { binOff[b] = off; g_offs[cta * MAX_CTA + b] = (uint32_t)off | ((uint32_t)c[i] << 16); }
            off += c[i];
        }
        if (lane == 31) ctrl[8] = x;
    }
    __syncthreads();
#pragma unroll
    for (int e = 0; e < 12; e++) {
        if (rk[e] != 0xffffffffu) {
            int pos = binOff[rk[e] >> 16] + (int)(rk[e] & 0xffffu);
            sts128(sb + P1_STAGE + pos * 16, make_uint4(r0[e], r1[e], r2[e], 0u));
        }
    }
    fence_async_smem();
    __syncthreads();
    if (tid == 0) {
        const uint32_t bytes = (uint32_t)ctrl[8] * 16u;
        if (bytes) asm volatile("cp.async.bulk.global.shared::cta.bulk_group [%0], [%1], %2;"
                                ::"l"(g_rec + (size_t)cta * REC_CAP), "r"(sb + P1_STAGE), "r"(bytes) : "memory");
        asm volatile("cp.async.bulk.commit_group;" ::: "memory");
    }
    asm volatile("cp.async.bulk.wait_group 0;" ::: "memory");
    asm volatile("fence.proxy.async;" ::: "memory");

    __syncthreads();
    STAMP(4);
    unsigned bar_target = 0;
    if (tid == 0) {
        unsigned old;
        __threadfence();
        asm volatile("atom.add.release.gpu.global.u32 %0, [%1], 1;" : "=r"(old) : "l"(&g_bar) : "memory");
        bar_target = (old / (unsigned)p.ncta + 1u) * (unsigned)p.ncta;
    }
    if (tid == 0) {
        unsigned cur;
        int spins = 0;
        do {
            asm volatile("ld.acquire.gpu.global.u32 %0, [%1];" : "=r"(cur) : "l"(&g_bar) : "memory");
        } while ((int)(cur - bar_target) < 0 && ++spins < (1 << 24));
        asm volatile("fence.proxy.async;" ::: "memory");
    }
    __syncthreads();
    STAMP(5);

    if (warp == 0) {
        uint32_t v[5];
        int s = 0;
#pragma unroll
        for (int i = 0; i < 5; i++) {
            int b = lane * 5 + i;
            v[i] = b < p.ncta ? __ldcg(&g_offs[b * MAX_CTA + cta]) : 0u;
        }
#pragma unroll
        for (int i = 0; i < 5; i++) s += (int)(v[i] >> 16);
        int x = s;
#pragma unroll
        for (int o = 1; o < 32; o <<= 1) { int y = __shfl_up_sync(0xffffffffu, x, o); if (lane >= o) x += y; }
        const int total = __shfl_sync(0xffffffffu, x, 31);
        int off = x - s;
#pragma unroll
        for (int i = 0; i < 5; i++) {
            int b = lane * 5 + i;
            if (b < p.ncta) { binCnt[b] = (int)v[i]; binOff[b] = off; }
            off += (int)(v[i] >> 16);
        }
        if (lane == 0) {
            ctrl[8] = total;
            if (total > STAGE_CAP) ctrl[1] = 1;
            mbar_expect_tx(bar_rec, total > STAGE_CAP ? 0u : (uint32_t)total * 16u);
        }
    }
    __syncthreads();
    const int total = ctrl[8];
    if (ctrl[1] == 0) {
        const int b = (lane << 4) | warp;
        if (lane < 9 && b < p.ncta) {
            const uint32_t v = (uint32_t)binCnt[b], c = v >> 16;
            if (c) {
                asm volatile("fence.proxy.async;" ::: "memory");
                bulk_g2s(sb + (uint32_t)binOff[b] * 16u, g_rec + (size_t)b * REC_CAP + (v & 0xffffu), c * 16u, bar_rec);
            }
        }
    }
    mbar_wait(bar_rec, 0);
    if (ctrl[1] == 0) {
        for (int i = tid; i < total; i += NT) {
            uint32_t dl = lds32(sb + i * 16 + 8) >> 16;
            sts32(sb + i * 16 + 12, (uint32_t)atomicAdd(&nCnt[dl], 1));
        }
    }
    __syncthreads();
    if (warp == 0) {
        int c[3], s = 0;
#pragma unroll
        for (int i = 0; i < 3; i++) {
            int b = lane * 3 + i;
            c[i] = b < nnodes ? max(16, (nCnt[b] + 15) & ~15) : 0;
            s += c[i];
        }
        int x = s;
#pragma unroll
        for (int o = 1; o < 32; o <<= 1) { int y = __shfl_up_sync(0xffffffffu, x, o); if (lane >= o) x += y; }
        const int slots = __shfl_sync(0xffffffffu, x, 31);
        int off = x - s, below = 0;
#pragma unroll
        for (int i = 0; i < 3; i++) {
            int b = lane * 3 + i;
            if (b < nnodes) {
                nInfo[b] = (uint32_t)off | ((uint32_t)c[i] << 16);
                below += (2 * off + c[i] < slots);
            }
            off += c[i];
        }
        below = __reduce_add_sync(0xffffffffu, below);
        if (lane == 0) {
            ctrl[2] = below;
            ctrl[3] = slots;
            if (slots > SLOT_CAP) ctrl[1] = 1;
        }
    }
    __syncthreads();
    if (ctrl[1] == 0) {
        uint16_t* sid = (uint16_t*)(smem + SM_SID);
        uint2* meta = (uint2*)(smem + SM_META);
        for (int i = tid; i < total; i += NT) {
            uint4 r = lds128(sb + i * 16);
            int pos = (int)(nInfo[r.z >> 16] & 0xffffu) + (int)r.w;
            sid[pos]  = (uint16_t)(r.x & 0xffffu);
            meta[pos] = make_uint2(((r.x >> 16) << 5) | (r.z << 16), r.y);
        }
        for (int i = tid; i < nnodes * 16; i += NT) {
            int nl = i >> 4, c = nCnt[nl];
            int j = (c & ~15) + (i & 15);
            if (j >= c && (j < 16 || (c & 15))) {
                int pos = (int)(nInfo[nl] & 0xffffu) + j;
                sid[pos]  = 0xffffu;
                meta[pos] = make_uint2((uint32_t)TAB_ZERO << 5, 0u);
            }
        }
    }
    fence_async_smem();
    __syncthreads();
    STAMP(6);

    if (__shfl_sync(0xffffffffu, ctrl[1], 0) != 0) {
        float* acc = (float*)smem;
        for (int i = tid; i < nnodes * 256; i += NT) acc[i] = 0.f;
        __syncthreads();
        const uint16_t* posu = (const uint16_t*)p.pos;
        const uint32_t* tabg = (const uint32_t*)g_table;
        const uint32_t* Fw = (const uint32_t*)g_F;
        for (int e0 = warp * 32; e0 < p.E; e0 += NT) {
            int e = e0 + lane;
            int s = 0, d = 0;
            uint32_t db = 0xffff, rxy = 0, rz = 0;
            bool act = false;
            if (e < p.E) {
                s = p.src[e]; d = p.dst[e];
                if (d >= node0 && d < node0 + nnodes) {
                    uint32_t sxy = posu[s * 3] | ((uint32_t)posu[s * 3 + 1] << 16), sz = posu[s * 3 + 2];
                    uint32_t dxy = posu[d * 3] | ((uint32_t)posu[d * 3 + 1] << 16), dz = posu[d * 3 + 2];
                    db  = edge_dist(sxy, sz, dxy, dz, rxy, rz);
                    act = db <= D_MAX_BITS;
                }
            }
            unsigned m = __ballot_sync(0xffffffffu, act);
            while (m) {
                int l = __ffs(m) - 1;
                m &= m - 1;
                int es = __shfl_sync(0xffffffffu, s, l), ed = __shfl_sync(0xffffffffu, d, l);
                uint32_t edb = __shfl_sync(0xffffffffu, db, l), exy = __shfl_sync(0xffffffffu, rxy, l), ez = __shfl_sync(0xffffffffu, rz, l);
                float inv = 1.0f / __uint_as_float(edb << 16);
                float rh[3] = {rbf(bf_lo(exy) * inv), rbf(bf_hi(exy) * inv), rbf(bf_lo(ez) * inv)};
                const uint32_t* fr = Fw + (size_t)es * 128 + lane;
                const uint32_t fh = __ldcg(fr);
                const uint32_t q[3] = {__ldcg(fr + 32), __ldcg(fr + 64), __ldcg(fr + 96)};
                float ps0 = 0.f, ps1 = 0.f, pr0 = 0.f, pr1 = 0.f;
                for (int j2 = 0; j2 < 32; j2++) {
                    uint32_t hj = __shfl_sync(0xffffffffu, fh, j2);
                    uint32_t a0 = *(const uint32_t*)(p.w2 + (2 * j2) * 192 + 2 * lane), a1 = *(const uint32_t*)(p.w2 + (2 * j2 + 1) * 192 + 2 * lane);
                    uint32_t b0 = *(const uint32_t*)(p.w2 + (2 * j2) * 192 + 128 + 2 * lane), b1 = *(const uint32_t*)(p.w2 + (2 * j2 + 1) * 192 + 128 + 2 * lane);
                    ps0 += bf_lo(hj) * bf_lo(a0) + bf_hi(hj) * bf_lo(a1);
                    ps1 += bf_lo(hj) * bf_hi(a0) + bf_hi(hj) * bf_hi(a1);
                    pr0 += bf_lo(hj) * bf_lo(b0) + bf_hi(hj) * bf_lo(b1);
                    pr1 += bf_lo(hj) * bf_hi(b0) + bf_hi(hj) * bf_hi(b1);
                }
                float ws0 = 0.f, ws1 = 0.f, wv0 = 0.f, wv1 = 0.f, wr0 = 0.f, wr1 = 0.f;
                for (int k2 = 0; k2 < 8; k2++) {
                    uint32_t rk2 = __ldcg(tabg + (edb - D_MIN_BITS) * 8 + k2);
#pragma unroll
                    for (int h = 0; h < 2; h++) {
                        float rv = h ? bf_hi(rk2) : bf_lo(rk2);
                        const __nv_bfloat16* wrow = p.wr + (2 * k2 + h) * 192 + 2 * lane;
                        uint32_t a = *(const uint32_t*)wrow, b = *(const uint32_t*)(wrow + 64), c = *(const uint32_t*)(wrow + 128);
                        ws0 += rv * bf_lo(a); ws1 += rv * bf_hi(a);
                        wv0 += rv * bf_lo(b); wv1 += rv * bf_hi(b);
                        wr0 += rv * bf_lo(c); wr1 += rv * bf_hi(c);
                    }
                }
                float* a = acc + (ed - node0) * 256 + 2 * lane;
                atomicAdd(a, ps0 * ws0); atomicAdd(a + 1, ps1 * ws1);
#pragma unroll
                for (int c = 0; c < 3; c++) {
                    atomicAdd(a + 64 * (c + 1), wv0 * bf_lo(q[c]) + pr0 * wr0 * rh[c]);
                    atomicAdd(a + 64 * (c + 1) + 1, wv1 * bf_hi(q[c]) + pr1 * wr1 * rh[c]);
                }
            }
        }
        __syncthreads();
        for (int i = tid; i < nnodes * 128; i += NT) {
            uint32_t r = *(const uint32_t*)(p.sv + (size_t)node0 * 256 + 2 * i);
            *(uint32_t*)(p.out + (size_t)node0 * 256 + 2 * i) = pack_bf(bf_lo(r) + acc[2 * i], bf_hi(r) + acc[2 * i + 1]);
        }
        return;
    }

    const int split = ctrl[2], slots = ctrl[3];
    if (warp >= 8) {
        asm volatile("setmaxnreg.dec.sync.aligned.u32 56;");
        const int wg = (warp - 8) >> 2, r = warp & 3;
        const int mid = split < nnodes ? (int)(nInfo[split] & 0xffffu) : slots;
        const int g0 = (wg == 0 ? 0 : mid) >> 4, g1 = (wg == 0 ? mid : slots) >> 4;
        const int e = lane >> 1, half = lane & 1;
        const uint32_t coef_off = e * 128 + ((half ^ (e & 7)) << 4);
        int stage = r, phase = 1;
        for (int gi = g0 + r; gi < g1; gi += 4) {
            const uint32_t st = sb + SM_RING + (wg * NSTAGE + stage) * STAGE_B;
            const uint32_t fb = bar_full + (wg * NSTAGE + stage) * 8;
            const uint2 m = lds64(sb + SM_META + (gi * 16 + e) * 8);
            const uint32_t id = lds16(sb + SM_SID + (gi * 16 + (lane & 15)) * 2);
            const uint4 tv = __ldg((const uint4*)((const uint8_t*)g_table + (m.x & 0xffffu) + half * 16));
            mbar_wait(bar_empty + (wg * NSTAGE + stage) * 8, phase);
            if (lane < 16) tma_load(st + 2048 + lane * 640, &tmF, (int)id * 4, fb);
            const uint32_t mx = __byte_perm(m.y, 0, 0x1010), my = __byte_perm(m.y, 0, 0x3232), mz = __byte_perm(m.x, 0, 0x3232);
            const uint32_t a = st + coef_off;
            sts128(a, tv);
            sts128(a ^ 0x20, make_uint4(hmul2(tv.x, mx), hmul2(tv.y, mx), hmul2(tv.z, mx), hmul2(tv.w, mx)));
            sts128(a ^ 0x40, make_uint4(hmul2(tv.x, my), hmul2(tv.y, my), hmul2(tv.z, my), hmul2(tv.w, my)));
            sts128(a ^ 0x60, make_uint4(hmul2(tv.x, mz), hmul2(tv.y, mz), hmul2(tv.z, mz), hmul2(tv.w, mz)));
            fence_async_smem();
            __syncwarp();
            if (lane == 0) mbar_expect_tx(fb, 16 * 512);
            stage += 4;
            if (stage >= NSTAGE) { stage -= NSTAGE; phase ^= 1; }
        }
    } else {
        asm volatile("setmaxnreg.inc.sync.aligned.u32 200;");
        const int wg = warp >> 2, w = warp & 3;
        const int n_begin = wg == 0 ? 0 : split, n_end = wg == 0 ? split : nnodes;
        mbar_wait(bar_mlp, 0);
        uint32_t wA[2][4][4];
        float wt[3][8];
#pragma unroll
        for (int m = 0; m < 2; m++) {
#pragma unroll
            for (int ks = 0; ks < 4; ks++) {
                const int line = 3 * (16 * ks + (lane & 7) + 8 * (lane >> 4)) + 2 * m;
                ldsm4t(wA[m][ks], sb + SM_W2 + line * 128 + (((2 * w + ((lane >> 3) & 1)) ^ (line & 7)) << 4));
            }
        }
        {
            const uint16_t* wr = (const uint16_t*)p.wr + 16 * w + g;
#pragma unroll
            for (int ty = 0; ty < 3; ty++) {
#pragma unroll
                for (int i = 0; i < 8; i++) {
                    const int k = 8 * (i >> 2) + 2 * t + (i & 1);
                    wt[ty][i] = bf_u16(__ldg(wr + k * 192 + ty * 64 + 8 * ((i >> 1) & 1)));
                }
            }
        }
        uint32_t aoff[4];
        {
            const int e = (lane & 7) + 8 * (lane >> 4), ch = 2 * w + ((lane >> 3) & 1);
#pragma unroll
            for (int b = 0; b < 4; b++) aoff[b] = 2048 + e * 640 + b * 128 + ((ch ^ ((5 * e + b) & 7)) << 4);
        }
        const uint32_t ht = sb + SM_HT + wg * 8192;
        const uint32_t stsm_a = ht + (16 * w + (lane & 15)) * 128 + (((lane >> 4) ^ (lane & 7)) << 4);
        const uint32_t dht = desc_lo(ht);
        const uint32_t out_lane = (uint32_t)node0 * 512u + t * 128 + (16 * w + (g & 1) * 8 + (g & 6)) * 2;
        float ys[8], yv[24], dQ[3][8];
#pragma unroll
        for (int i = 0; i < 24; i++) yv[i] = 0.f;
#pragma unroll
        for (int i = 0; i < 8; i++) { ys[i] = 0.f; dQ[0][i] = 0.f; dQ[1][i] = 0.f; dQ[2][i] = 0.f; }
        int stage = 0, phase = 0;
        for (int nl = n_begin; nl < n_end; nl++) {
            const int G = __shfl_sync(0xffffffffu, (int)(nInfo[nl] >> 20), 0);
            const uint32_t resid = __ldg((const uint32_t*)((const uint8_t*)p.sv + (out_lane + (uint32_t)nl * 512u)));
            for (int gi = 0; gi < G; gi++) {
                const uint32_t st = sb + SM_RING + (wg * NSTAGE + stage) * STAGE_B;
                mbar_wait(bar_full + (wg * NSTAGE + stage) * 8, phase);
                uint32_t A[4][4];
#pragma unroll
                for (int b = 0; b < 4; b++) ldsm4t(A[b], st + aoff[b]);
                const uint32_t bd = desc_lo(st);
                wg_fence();
                wgmma_n64(ys, yv, A[0], bd, gi);
                wgmma_n16(dQ[0], A[1], bd, gi);
                wgmma_n16(dQ[1], A[2], bd, gi);
                wgmma_n16(dQ[2], A[3], bd, gi);
                wg_commit();
                wg_wait0();
                if (lane == 0) mbar_arrive(bar_empty + (wg * NSTAGE + stage) * 8);
                if (++stage == NSTAGE) { stage = 0; phase ^= 1; }
            }
            named_barrier(1 + wg);
            stsm4(stsm_a, pack_bf(ys[0], ys[1]), pack_bf(ys[2], ys[3]), pack_bf(ys[4], ys[5]), pack_bf(ys[6], ys[7]));
#pragma unroll
            for (int i = 0; i < 6; i += 2) {
                stsm4(stsm_a ^ ((i + 2) << 4),
                      pack_bf(yv[4 * i], yv[4 * i + 1]), pack_bf(yv[4 * i + 2], yv[4 * i + 3]),
                      pack_bf(yv[4 * i + 4], yv[4 * i + 5]), pack_bf(yv[4 * i + 6], yv[4 * i + 7]));
            }
            fence_async_smem();
            named_barrier(1 + wg);
            wg_fence();
#pragma unroll
            for (int ks = 0; ks < 4; ks++) {
                wgmma_n16(ys, wA[0][ks], dht + ks * 128, ks);
                wgmma_n48(yv, wA[1][ks], dht + ks * 128 + 2, ks);
            }
            wg_commit();
            float pr[4][2];
#pragma unroll
            for (int a = 0; a < 3; a++) {
                const float* q = dQ[a];
                pr[a + 1][0] = wt[1][0] * q[0] + wt[1][1] * q[1] + wt[1][4] * q[4] + wt[1][5] * q[5];
                pr[a + 1][1] = wt[1][2] * q[2] + wt[1][3] * q[3] + wt[1][6] * q[6] + wt[1][7] * q[7];
            }
            wg_wait0();
            pr[0][0] = wt[0][0] * ys[0] + wt[0][1] * ys[1] + wt[0][4] * ys[4] + wt[0][5] * ys[5];
            pr[0][1] = wt[0][2] * ys[2] + wt[0][3] * ys[3] + wt[0][6] * ys[6] + wt[0][7] * ys[7];
#pragma unroll
            for (int a = 0; a < 3; a++) {
                const float* y = yv + 8 * a;
                pr[a + 1][0] += wt[2][0] * y[0] + wt[2][1] * y[1] + wt[2][4] * y[4] + wt[2][5] * y[5];
                pr[a + 1][1] += wt[2][2] * y[2] + wt[2][3] * y[3] + wt[2][6] * y[6] + wt[2][7] * y[7];
            }
            const bool hi2 = t & 2, hi1 = t & 1, odd = g & 1;
            float ka0 = hi2 ? pr[2][0] : pr[0][0], ka1 = hi2 ? pr[2][1] : pr[0][1];
            float kb0 = hi2 ? pr[3][0] : pr[1][0], kb1 = hi2 ? pr[3][1] : pr[1][1];
            float sa0 = hi2 ? pr[0][0] : pr[2][0], sa1 = hi2 ? pr[0][1] : pr[2][1];
            float sb0 = hi2 ? pr[1][0] : pr[3][0], sb1 = hi2 ? pr[1][1] : pr[3][1];
            ka0 += __shfl_xor_sync(0xffffffffu, sa0, 2); ka1 += __shfl_xor_sync(0xffffffffu, sa1, 2);
            kb0 += __shfl_xor_sync(0xffffffffu, sb0, 2); kb1 += __shfl_xor_sync(0xffffffffu, sb1, 2);
            float k0 = hi1 ? kb0 : ka0, k1 = hi1 ? kb1 : ka1;
            float s0 = hi1 ? ka0 : kb0, s1 = hi1 ? ka1 : kb1;
            k0 += __shfl_xor_sync(0xffffffffu, s0, 1);
            k1 += __shfl_xor_sync(0xffffffffu, s1, 1);
            const float other = __shfl_xor_sync(0xffffffffu, odd ? k0 : k1, 4);
            const float lo = odd ? other : k0, hi = odd ? k1 : other;
            *(uint32_t*)((uint8_t*)p.out + (out_lane + (uint32_t)nl * 512u)) = pack_bf(bf_lo(resid) + lo, bf_hi(resid) + hi);
        }
    }
    STAMP(8);
}

typedef CUresult (*EncodeFn)(CUtensorMap*, CUtensorMapDataType, cuuint32_t, void*, const cuuint64_t*, const cuuint64_t*,
                             const cuuint32_t*, const cuuint32_t*, CUtensorMapInterleave, CUtensorMapSwizzle,
                             CUtensorMapL2promotion, CUtensorMapFloatOOBfill);

void make_map(EncodeFn enc, CUtensorMap* tm, const void* base, uint64_t lines, uint32_t box) {
    cuuint64_t gd[2] = {64, lines};
    cuuint64_t gs[1] = {128};
    cuuint32_t bd[2] = {64, box};
    cuuint32_t es[2] = {1, 1};
    enc(tm, CU_TENSOR_MAP_DATA_TYPE_BFLOAT16, 2, const_cast<void*>(base), gd, gs, bd, es, CU_TENSOR_MAP_INTERLEAVE_NONE,
        CU_TENSOR_MAP_SWIZZLE_128B, CU_TENSOR_MAP_L2_PROMOTION_L2_128B, CU_TENSOR_MAP_FLOAT_OOB_FILL_NONE);
}

}

extern "C" void kernel_launch(void* const* d_in, const int* in_sizes, int n_in, void* d_out, int out_size) {
    (void)n_in; (void)out_size;
    static int n_sm = 0;
    static EncodeFn enc = nullptr;
    static void* f_ptr = nullptr;
    if (n_sm == 0) {
        int dev = 0;
        cudaGetDevice(&dev);
        cudaDeviceGetAttribute(&n_sm, cudaDevAttrMultiProcessorCount, dev);
        cudaFuncSetAttribute(painn_kernel, cudaFuncAttributeMaxDynamicSharedMemorySize, SM_TOTAL);
        void* fn = nullptr;
        cudaDriverEntryPointQueryResult qr;
        cudaGetDriverEntryPoint("cuTensorMapEncodeTiled", &fn, cudaEnableDefault, &qr);
        enc = (EncodeFn)fn;
        cudaGetSymbolAddress(&f_ptr, g_F);
    }
    Params p;
    p.sv    = (const __nv_bfloat16*)d_in[0];
    p.pos   = (const __nv_bfloat16*)d_in[1];
    p.src   = (const int*)d_in[2];
    p.dst   = (const int*)d_in[3];
    p.freqs = (const __nv_bfloat16*)d_in[4];
    p.w1    = (const __nv_bfloat16*)d_in[5];
    p.w2    = (const __nv_bfloat16*)d_in[6];
    p.wr    = (const __nv_bfloat16*)d_in[7];
    p.out   = (__nv_bfloat16*)d_out;
    p.N = in_sizes[1] / 3;
    p.E = in_sizes[2];
    p.ncta = n_sm < MAX_CTA ? n_sm : MAX_CTA;
    p.npc = (p.N + p.ncta - 1) / p.ncta;
    p.npc_magic = (uint32_t)(0x100000000ull / (uint32_t)p.npc) + 1u;
    p.quads_per_cta = ((p.E >> 2) + p.ncta - 1) / p.ncta;
    if (!enc || p.N > MAX_N || p.npc > MAX_NPC || (p.E & 3) || p.quads_per_cta > MAX_ROUNDS * 32) return;

    CUtensorMap tmF, tmSV, tmW1, tmW2;
    make_map(enc, &tmF, f_ptr, (uint64_t)p.N * 4, 4);
    make_map(enc, &tmSV, p.sv, (uint64_t)p.N * 4, 160);
    make_map(enc, &tmW1, p.w1, 64, 64);
    make_map(enc, &tmW2, p.w2, 192, 192);

    cudaLaunchConfig_t cfg = {};
    cfg.gridDim = dim3(p.ncta);
    cfg.blockDim = dim3(NT);
    cfg.dynamicSmemBytes = SM_TOTAL;
    cfg.stream = cudaStreamPerThread;
    cudaLaunchAttribute attr[1];
    attr[0].id = cudaLaunchAttributeCooperative;
    attr[0].val.cooperative = 1;
    cfg.attrs = attr;
    cfg.numAttrs = 1;
    cudaLaunchKernelEx(&cfg, painn_kernel, p, tmF, tmSV, tmW1, tmW2);
}
```

```cpp
#include <cuda_runtime.h>
#include <cuda.h>
#include <cuda_bf16.h>
#include <stdint.h>

namespace {

constexpr int NT        = 512;
constexpr int NCWG      = 3;
constexpr int MAX_N     = 10240;
constexpr int MAX_CTA   = 144;
constexpr int MAX_NPC   = 80;
constexpr int MAX_ROUNDS = 38;
constexpr int REC_CAP   = MAX_ROUNDS * 128;
constexpr int SLOT_CAP  = 6144;
constexpr int MAX_STAGE = 4;
constexpr int STAGE_B   = 12288;

constexpr uint32_t D_MIN_BITS = 0x38D2;
constexpr uint32_t D_MAX_BITS = 0x409C;
constexpr int TAB_ROWS  = (int)(D_MAX_BITS - D_MIN_BITS) + 1;
constexpr int TAB_ZERO  = TAB_ROWS;
constexpr int TAB_BYTES = (TAB_ROWS + 1) * 32;

constexpr int SM_BINCNT = 0;
constexpr int SM_BINOFF = SM_BINCNT + MAX_CTA * 4;
constexpr int SM_NCNT   = SM_BINOFF + MAX_CTA * 4;
constexpr int SM_NINFO  = SM_NCNT + MAX_NPC * 4;
constexpr int SM_CTRL   = SM_NINFO + MAX_NPC * 4;
constexpr int SM_BARS   = SM_CTRL + 64;
constexpr int SM_SID    = 2048 + 128;
constexpr int SM_META   = SM_SID + SLOT_CAP * 2;
constexpr int SM_TOTAL  = 232448;
constexpr int SM_HT     = (SM_TOTAL - NCWG * 8192) / 1024 * 1024;
constexpr int SM_RING4  = SM_HT - NCWG * 4 * STAGE_B;
constexpr int SM_RING3  = SM_HT - NCWG * 3 * STAGE_B;
constexpr int SLOT_CAP4 = (SM_RING4 - SM_META) / 8;
constexpr int SM_STAGE2 = SM_RING3 - 0;
constexpr int STAGE_CAP = (SM_TOTAL - SM_RING3) / 16;
constexpr int P1_POS    = 3072;
constexpr int P1_STAGE  = P1_POS + 61440;
constexpr int P1_SV     = (P1_STAGE + REC_CAP * 16 + 1023) / 1024 * 1024;
constexpr int P1_W1     = P1_SV + MAX_NPC * 512;
constexpr int P1_W2     = P1_W1 + 8192;
constexpr int P1_END    = P1_W2 + 24576;
static_assert(SM_BARS + (4 + 2 * NCWG * MAX_STAGE) * 8 <= SM_SID, "misc block");
static_assert(SM_SID + SLOT_CAP * 2 <= P1_POS + 61440 && SM_BARS + 256 <= P1_POS, "misc block");
static_assert(P1_END <= SM_TOTAL, "phase 1 overlay");
static_assert(SM_META + SLOT_CAP * 8 <= SM_RING3, "CSR");
static_assert(SM_RING4 % 1024 == 0 && SM_RING3 % 1024 == 0 && SM_HT % 1024 == 0, "alignment");
static_assert(SM_BARS % 8 == 0 && SM_META % 8 == 0, "alignment");
static_assert(MAX_N * 6 <= 61440, "pos");
static_assert(SM_SID + MAX_NPC * 1024 <= SM_TOTAL, "slow path accumulators");

__device__ __align__(1024) uint4 g_F[MAX_N * 32];
__device__ uint4    g_rec[MAX_CTA * REC_CAP];
__device__ uint32_t g_offs[MAX_CTA * MAX_CTA];
__device__ uint4    g_table[(TAB_BYTES + 15) / 16];
__device__ unsigned g_bar;
#define STAMP(k)

struct Params {
    const __nv_bfloat16* sv;
    const __nv_bfloat16* pos;
    const int*           src;
    const int*           dst;
    const __nv_bfloat16* freqs;
    const __nv_bfloat16* w1;
    const __nv_bfloat16* w2;
    const __nv_bfloat16* wr;
    __nv_bfloat16*       out;
    int N, E, ncta, npc;
    uint32_t npc_magic;
    int quads_per_cta;
};

__device__ __forceinline__ uint32_t smem_u32(const void* p) { return (uint32_t)__cvta_generic_to_shared(p); }
__device__ __forceinline__ float bf_lo(uint32_t v) { return __uint_as_float(v << 16); }
__device__ __forceinline__ float bf_hi(uint32_t v) { return __uint_as_float(v & 0xffff0000u); }
__device__ __forceinline__ float bf_u16(uint16_t v) { return __uint_as_float((uint32_t)v << 16); }
__device__ __forceinline__ uint32_t pack_bf(float lo, float hi) {
    uint32_t r;
    asm("cvt.rn.bf16x2.f32 %0, %1, %2;" : "=r"(r) : "f"(hi), "f"(lo));
    return r;
}
__device__ __forceinline__ float rbf(float x) { return bf_lo(pack_bf(x, 0.f)); }
__device__ __forceinline__ uint32_t hmul2(uint32_t a, uint32_t b) {
    uint32_t r;
    asm("mul.rn.bf16x2 %0, %1, %2;" : "=r"(r) : "r"(a), "r"(b));
    return r;
}
__device__ __forceinline__ uint32_t hsub2(uint32_t a, uint32_t b) {
    uint32_t r;
    asm("sub.rn.bf16x2 %0, %1, %2;" : "=r"(r) : "r"(a), "r"(b));
    return r;
}
__device__ __forceinline__ uint32_t lds32(uint32_t a) { uint32_t v; asm volatile("ld.shared.u32 %0, [%1];" : "=r"(v) : "r"(a)); return v; }
__device__ __forceinline__ uint32_t lds16(uint32_t a) { uint16_t v; asm volatile("ld.shared.u16 %0, [%1];" : "=h"(v) : "r"(a)); return v; }
__device__ __forceinline__ uint2 lds64(uint32_t a) { uint2 v; asm volatile("ld.shared.v2.u32 {%0,%1}, [%2];" : "=r"(v.x), "=r"(v.y) : "r"(a)); return v; }
__device__ __forceinline__ uint4 lds128(uint32_t a) { uint4 v; asm volatile("ld.shared.v4.u32 {%0,%1,%2,%3}, [%4];" : "=r"(v.x), "=r"(v.y), "=r"(v.z), "=r"(v.w) : "r"(a)); return v; }
__device__ __forceinline__ void sts32(uint32_t a, uint32_t v) { asm volatile("st.shared.u32 [%0], %1;" ::"r"(a), "r"(v) : "memory"); }
__device__ __forceinline__ void sts128(uint32_t a, uint4 v) { asm volatile("st.shared.v4.u32 [%0], {%1,%2,%3,%4};" ::"r"(a), "r"(v.x), "r"(v.y), "r"(v.z), "r"(v.w) : "memory"); }
__device__ __forceinline__ void mbar_init(uint32_t bar, int cnt) { asm volatile("mbarrier.init.shared::cta.b64 [%0], %1;" ::"r"(bar), "r"(cnt) : "memory"); }
__device__ __forceinline__ void mbar_expect_tx(uint32_t bar, uint32_t bytes) { asm volatile("mbarrier.arrive.expect_tx.shared::cta.b64 _, [%0], %1;" ::"r"(bar), "r"(bytes) : "memory"); }
__device__ __forceinline__ void mbar_arrive(uint32_t bar) { asm volatile("mbarrier.arrive.shared::cta.b64 _, [%0];" ::"r"(bar) : "memory"); }
__device__ __forceinline__ void mbar_wait(uint32_t bar, uint32_t parity) {
    uint32_t done;
    int spins = 0;
    do {
        asm volatile("{\n.reg .pred p;\nmbarrier.try_wait.parity.shared::cta.b64 p, [%1], %2;\nselp.u32 %0, 1, 0, p;\n}"
                     : "=r"(done) : "r"(bar), "r"(parity) : "memory");
    } while (!done && ++spins < (1 << 22));
}
__device__ __forceinline__ void bulk_g2s(uint32_t dst, const void* src, uint32_t bytes, uint32_t bar) {
    asm volatile("cp.async.bulk.shared::cluster.global.mbarrier::complete_tx::bytes [%0], [%1], %2, [%3];"
                 ::"r"(dst), "l"(src), "r"(bytes), "r"(bar) : "memory");
}
__device__ __forceinline__ void tma_load(uint32_t dst, const CUtensorMap* tm, int line, uint32_t bar) {
    asm volatile("cp.async.bulk.tensor.2d.shared::cluster.global.mbarrier::complete_tx::bytes [%0], [%1, {%3, %4}], [%2];"
                 ::"r"(dst), "l"(tm), "r"(bar), "r"(0), "r"(line) : "memory");
}
__device__ __forceinline__ void tma_store(const CUtensorMap* tm, int line, uint32_t src) {
    asm volatile("cp.async.bulk.tensor.2d.global.shared::cta.bulk_group [%0, {%2, %3}], [%1];"
                 ::"l"(tm), "r"(src), "r"(0), "r"(line) : "memory");
}
__device__ __forceinline__ void fence_async_smem() { asm volatile("fence.proxy.async.shared::cta;" ::: "memory"); }
__device__ __forceinline__ void named_barrier(int id) { asm volatile("bar.sync %0, 128;" ::"r"(id) : "memory"); }
__device__ __forceinline__ void ldsm4(uint32_t (&r)[4], uint32_t a) {
    asm volatile("ldmatrix.sync.aligned.m8n8.x4.shared.b16 {%0,%1,%2,%3}, [%4];" : "=r"(r[0]), "=r"(r[1]), "=r"(r[2]), "=r"(r[3]) : "r"(a) : "memory");
}
__device__ __forceinline__ void ldsm4t(uint32_t (&r)[4], uint32_t a) {
    asm volatile("ldmatrix.sync.aligned.m8n8.x4.trans.shared.b16 {%0,%1,%2,%3}, [%4];" : "=r"(r[0]), "=r"(r[1]), "=r"(r[2]), "=r"(r[3]) : "r"(a) : "memory");
}
__device__ __forceinline__ void stsm4(uint32_t a, uint32_t r0, uint32_t r1, uint32_t r2, uint32_t r3) {
    asm volatile("stmatrix.sync.aligned.m8n8.x4.shared.b16 [%0], {%1,%2,%3,%4};" ::"r"(a), "r"(r0), "r"(r1), "r"(r2), "r"(r3) : "memory");
}
__device__ __forceinline__ void mma16816(float (&c)[4], const uint32_t (&a)[4], uint32_t b0, uint32_t b1) {
    asm volatile("mma.sync.aligned.m16n8k16.row.col.f32.bf16.bf16.f32 {%0,%1,%2,%3}, {%4,%5,%6,%7}, {%8,%9}, {%0,%1,%2,%3};"
                 : "+f"(c[0]), "+f"(c[1]), "+f"(c[2]), "+f"(c[3])
                 : "r"(a[0]), "r"(a[1]), "r"(a[2]), "r"(a[3]), "r"(b0), "r"(b1));
}

__device__ __forceinline__ uint32_t desc_lo(uint32_t saddr) { return ((saddr & 0x3FFFF) >> 4) | (1u << 16); }
#define DESC_HI "0x40000040"
__device__ __forceinline__ void wg_fence() { asm volatile("wgmma.fence.sync.aligned;" ::: "memory"); }
__device__ __forceinline__ void wg_commit() { asm volatile("wgmma.commit_group.sync.aligned;" ::: "memory"); }
__device__ __forceinline__ void wg_wait0() { asm volatile("wgmma.wait_group.sync.aligned 0;" ::: "memory"); }

__device__ __forceinline__ void wgmma_n64(float (&d)[8], float (&e)[24], const uint32_t (&a)[4], uint32_t bdesc, int scale) {
    asm volatile("{\n.reg .pred p;\n.reg .b64 b;\nsetp.ne.b32 p, %37, 0;\nmov.b64 b, {%36, " DESC_HI "};\n"
                 "wgmma.mma_async.sync.aligned.m64n64k16.f32.bf16.bf16 "
                 "{%0,%1,%2,%3,%4,%5,%6,%7,%8,%9,%10,%11,%12,%13,%14,%15,%16,%17,%18,%19,%20,%21,%22,%23,%24,%25,%26,%27,%28,%29,%30,%31}, "
                 "{%32,%33,%34,%35}, b, p, 1, 1, 1;\n}"
                 : "+f"(d[0]), "+f"(d[1]), "+f"(d[2]), "+f"(d[3]), "+f"(d[4]), "+f"(d[5]), "+f"(d[6]), "+f"(d[7]),
                   "+f"(e[0]), "+f"(e[1]), "+f"(e[2]), "+f"(e[3]), "+f"(e[4]), "+f"(e[5]), "+f"(e[6]), "+f"(e[7]),
                   "+f"(e[8]), "+f"(e[9]), "+f"(e[10]), "+f"(e[11]), "+f"(e[12]), "+f"(e[13]), "+f"(e[14]), "+f"(e[15]),
                   "+f"(e[16]), "+f"(e[17]), "+f"(e[18]), "+f"(e[19]), "+f"(e[20]), "+f"(e[21]), "+f"(e[22]), "+f"(e[23])
                 : "r"(a[0]), "r"(a[1]), "r"(a[2]), "r"(a[3]), "r"(bdesc), "r"(scale));
}
__device__ __forceinline__ void wgmma_n48(float (&e)[24], const uint32_t (&a)[4], uint32_t bdesc, int scale) {
    asm volatile("{\n.reg .pred p;\n.reg .b64 b;\nsetp.ne.b32 p, %29, 0;\nmov.b64 b, {%28, " DESC_HI "};\n"
                 "wgmma.mma_async.sync.aligned.m64n48k16.f32.bf16.bf16 "
                 "{%0,%1,%2,%3,%4,%5,%6,%7,%8,%9,%10,%11,%12,%13,%14,%15,%16,%17,%18,%19,%20,%21,%22,%23}, "
                 "{%24,%25,%26,%27}, b, p, 1, 1, 1;\n}"
                 : "+f"(e[0]), "+f"(e[1]), "+f"(e[2]), "+f"(e[3]), "+f"(e[4]), "+f"(e[5]), "+f"(e[6]), "+f"(e[7]),
                   "+f"(e[8]), "+f"(e[9]), "+f"(e[10]), "+f"(e[11]), "+f"(e[12]), "+f"(e[13]), "+f"(e[14]), "+f"(e[15]),
                   "+f"(e[16]), "+f"(e[17]), "+f"(e[18]), "+f"(e[19]), "+f"(e[20]), "+f"(e[21]), "+f"(e[22]), "+f"(e[23])
                 : "r"(a[0]), "r"(a[1]), "r"(a[2]), "r"(a[3]), "r"(bdesc), "r"(scale));
}
__device__ __forceinline__ void wgmma_n16(float (&d)[8], const uint32_t (&a)[4], uint32_t bdesc, int scale) {
    asm volatile("{\n.reg .pred p;\n.reg .b64 b;\nsetp.ne.b32 p, %13, 0;\nmov.b64 b, {%12, " DESC_HI "};\n"
                 "wgmma.mma_async.sync.aligned.m64n16k16.f32.bf16.bf16 {%0,%1,%2,%3,%4,%5,%6,%7}, {%8,%9,%10,%11}, b, p, 1, 1, 1;\n}"
                 : "+f"(d[0]), "+f"(d[1]), "+f"(d[2]), "+f"(d[3]), "+f"(d[4]), "+f"(d[5]), "+f"(d[6]), "+f"(d[7])
                 : "r"(a[0]), "r"(a[1]), "r"(a[2]), "r"(a[3]), "r"(bdesc), "r"(scale));
}

__device__ __forceinline__ uint32_t edge_dist(uint32_t sxy, uint32_t sz, uint32_t dxy, uint32_t dz, uint32_t& rxy, uint32_t& rz) {
    rxy = hsub2(sxy, dxy);
    rz  = hsub2(sz, dz);
    uint32_t qxy = hmul2(rxy, rxy), qz = hmul2(rz, rz);
    float ss = rbf((bf_lo(qxy) + bf_hi(qxy)) + bf_lo(qz));
    float s2 = rbf(ss + 1e-8f);
    float d;
    asm("sqrt.approx.ftz.f32 %0, %1;" : "=f"(d) : "f"(s2));
    return pack_bf(d, 0.f) & 0xffffu;
}

__device__ __forceinline__ void load_pos(uint32_t sm_pos, int i, uint32_t& xy, uint32_t& z) {
    uint32_t a  = (sm_pos + 6u * (uint32_t)i) & ~3u;
    uint32_t w0 = lds32(a), w1 = lds32(a + 4);
    uint32_t sh = (uint32_t)i << 4;
    xy = __funnelshift_r(w0, w1, sh);
    z  = __funnelshift_r(w1, w1, sh);
}

__device__ __noinline__ float radial_value(float d, float f) {
    float arg = rbf(d * f);
    float sn  = rbf(sinf(arg));
    float rb  = rbf(__fdiv_rn(sn, d));
    float c   = rbf(cosf(rbf(__fdiv_rn(rbf(d * 3.14159265358979323846f), 5.0f))));
    float fc  = rbf(0.5f * rbf(c + 1.0f));
    return rb * fc;
}

__global__ void __launch_bounds__(NT, 1)
painn_kernel(const Params p, const __grid_constant__ CUtensorMap tmF, const __grid_constant__ CUtensorMap tmSV,
             const __grid_constant__ CUtensorMap tmW1, const __grid_constant__ CUtensorMap tmW2) {
    extern __shared__ __align__(1024) uint8_t smem[];
    const uint32_t sb   = smem_u32(smem);
    const int tid  = threadIdx.x, lane = tid & 31, warp = __shfl_sync(0xffffffffu, tid >> 5, 0);
    const int cta  = blockIdx.x;
    const int g    = lane >> 2, t = lane & 3;
    int* binCnt = (int*)(smem + SM_BINCNT);
    int* binOff = (int*)(smem + SM_BINOFF);
    int* nCnt   = (int*)(smem + SM_NCNT);
    uint32_t* nInfo = (uint32_t*)(smem + SM_NINFO);
    volatile int* ctrl = (volatile int*)(smem + SM_CTRL);
    const uint32_t bar_pos = sb + SM_BARS, bar_mlp = bar_pos + 8, bar_rec = bar_pos + 16;
    const uint32_t bar_full = bar_pos + 32, bar_empty = bar_full + NCWG * MAX_STAGE * 8;

    const int node0  = cta * p.npc;
    const int nnodes = max(0, min(p.npc, p.N - node0));

    STAMP(0);
    if (tid == 0) {
        mbar_init(bar_pos, 1);
        mbar_init(bar_mlp, 1);
        mbar_init(bar_rec, 1);
        for (int i = 0; i < NCWG * MAX_STAGE; i++) { mbar_init(bar_full + 8 * i, 1); mbar_init(bar_empty + 8 * i, 4); }
        asm volatile("fence.mbarrier_init.release.cluster;" ::: "memory");
        uint32_t pos_bytes = (uint32_t)(p.N * 6 + 15) & ~15u;
        mbar_expect_tx(bar_pos, pos_bytes);
        bulk_g2s(sb + P1_POS, p.pos, pos_bytes, bar_pos);
        mbar_expect_tx(bar_mlp, 2u * 160u * 128u + 8192u + 24576u);
        tma_load(sb + P1_SV, &tmSV, node0 * 4, bar_mlp);
        tma_load(sb + P1_SV + 160 * 128, &tmSV, node0 * 4 + 160, bar_mlp);
        tma_load(sb + P1_W1, &tmW1, 0, bar_mlp);
        tma_load(sb + P1_W2, &tmW2, 0, bar_mlp);
    }
    const bool mlp_warp = warp >= 11;
    int4 s4[3], d4[3];
    const int q0 = cta * p.quads_per_cta;
    const int qend = min(q0 + p.quads_per_cta, p.E >> 2);
    if (!mlp_warp) {
#pragma unroll
        for (int k = 0; k < 3; k++) {
            int q = q0 + (warp + 11 * k) * 32 + lane;
            bool ok = q < qend;
            s4[k] = ok ? __ldg((const int4*)p.src + q) : make_int4(-1, -1, -1, -1);
            d4[k] = ok ? __ldg((const int4*)p.dst + q) : make_int4(0, 0, 0, 0);
        }
    } else {
        int q = q0 + (33 + warp - 11) * 32 + lane;
        if (q < qend && (lane & 7) == 0) {
            asm volatile("prefetch.global.L2 [%0];" ::"l"((const int4*)p.src + q));
            asm volatile("prefetch.global.L2 [%0];" ::"l"((const int4*)p.dst + q));
        }
    }
    if (tid < MAX_CTA) binCnt[tid] = 0;
    if (tid < MAX_NPC) nCnt[tid] = 0;
    if (tid < 16) ctrl[tid] = 0;
    if (tid >= 448 && tid < 448 + 48) {
        asm volatile("prefetch.global.L2 [%0];" ::"l"((const uint8_t*)p.wr + (tid - 448) * 128));
    }
    __syncthreads();

    if (mlp_warp) {
        const int rows_per = (TAB_ROWS + 1 + p.ncta - 1) / p.ncta;
        for (int i = tid - 11 * 32; i < rows_per * 8; i += 5 * 32) {
            int row = cta * rows_per + (i >> 3), kp = i & 7;
            if (row <= TAB_ROWS) {
                uint32_t val = 0;
                if (row < TAB_ROWS) {
                    float d = __uint_as_float((D_MIN_BITS + row) << 16);
                    uint32_t f2 = __ldg((const uint32_t*)p.freqs + kp);
                    val = pack_bf(radial_value(d, bf_lo(f2)), radial_value(d, bf_hi(f2)));
                }
                ((uint32_t*)g_table)[row * 8 + kp] = val;
            }
        }
        const int mt = warp - 11;
        if (mt * 16 < nnodes) {
            mbar_wait(bar_mlp, 0);
            float acc[8][4];
#pragma unroll
            for (int i = 0; i < 8; i++) { acc[i][0] = acc[i][1] = acc[i][2] = acc[i][3] = 0.f; }
            const int lrow = (lane & 7) + ((lane >> 3) & 1) * 8, lch = lane >> 4;
#pragma unroll
            for (int ks = 0; ks < 4; ks++) {
                uint32_t a[4];
                const int line = 4 * (mt * 16 + lrow);
                ldsm4(a, sb + P1_SV + line * 128 + (((2 * ks + lch) ^ (line & 7)) << 4));
                const int kk = 16 * ks + lrow;
#pragma unroll
                for (int nt = 0; nt < 8; nt += 2) {
                    uint32_t b[4];
                    ldsm4t(b, sb + P1_W1 + kk * 128 + (((nt + lch) ^ (kk & 7)) << 4));
                    mma16816(acc[nt], a, b[0], b[1]);
                    mma16816(acc[nt + 1], a, b[2], b[3]);
                }
            }
            uint32_t hp[8][2];
#pragma unroll
            for (int i = 0; i < 8; i++) {
                float h[4];
#pragma unroll
                for (int q = 0; q < 4; q++) {
                    float x = rbf(acc[i][q]);
                    h[q] = __fdividef(x, 1.0f + __expf(-x));
                    acc[i][q] = 0.f;
                }
                hp[i][0] = pack_bf(h[0], h[1]);
                hp[i][1] = pack_bf(h[2], h[3]);
            }
#pragma unroll
            for (int ks = 0; ks < 4; ks++) {
                uint32_t a[4] = {hp[2 * ks][0], hp[2 * ks][1], hp[2 * ks + 1][0], hp[2 * ks + 1][1]};
                const int line = 3 * (16 * ks + lrow) + 1;
#pragma unroll
                for (int nt = 0; nt < 8; nt += 2) {
                    uint32_t b[4];
                    ldsm4t(b, sb + P1_W2 + line * 128 + (((nt + lch) ^ (line & 7)) << 4));
                    mma16816(acc[nt], a, b[0], b[1]);
                    mma16816(acc[nt + 1], a, b[2], b[3]);
                }
            }
            uint32_t q[3][8][2];
#pragma unroll
            for (int rh = 0; rh < 2; rh++) {
                const int row = mt * 16 + g + 8 * rh;
#pragma unroll
                for (int i = 0; i < 8; i++) {
                    const uint32_t ph = pack_bf(acc[i][2 * rh], acc[i][2 * rh + 1]);
#pragma unroll
                    for (int a = 0; a < 3; a++) {
                        const int line = 4 * row + 1 + a;
                        q[a][i][rh] = hmul2(ph, lds32(sb + P1_SV + line * 128 + ((i ^ (line & 7)) << 4) + 4 * t));
                    }
                }
            }
            __syncwarp();
            {
                const int row = mt * 16 + (lane & 7) + ((lane >> 3) & 1) * 8;
#pragma unroll
                for (int c = 0; c < 4; c++) {
                    const int line = 4 * row + c;
                    const uint32_t lb = sb + P1_SV + line * 128;
#pragma unroll
                    for (int i = 0; i < 8; i += 2) {
                        const uint32_t a = lb + (((i + lch) ^ (line & 7)) << 4);
                        if (c == 0) stsm4(a, hp[i][0], hp[i][1], hp[i + 1][0], hp[i + 1][1]);
                        else        stsm4(a, q[c - 1][i][0], q[c - 1][i][1], q[c - 1][i + 1][0], q[c - 1][i + 1][1]);
                    }
                }
            }
            fence_async_smem();
            __syncwarp();
            if (lane < 16 && mt * 16 + lane < nnodes) tma_store(&tmF, (node0 + mt * 16 + lane) * 4, sb + P1_SV + (mt * 16 + lane) * 512);
            asm volatile("cp.async.bulk.commit_group;" ::: "memory");
        }
        const int q = q0 + (33 + warp - 11) * 32 + lane;
        const bool ok = q < qend;
        s4[0] = ok ? __ldg((const int4*)p.src + q) : make_int4(-1, -1, -1, -1);
        d4[0] = ok ? __ldg((const int4*)p.dst + q) : make_int4(0, 0, 0, 0);
        s4[1] = s4[2] = make_int4(-1, -1, -1, -1);
        d4[1] = d4[2] = make_int4(0, 0, 0, 0);
    }
    mbar_wait(bar_pos, 0);
    STAMP(1);

    uint32_t r0[12], r1[12], r2[12], rk[12];
#pragma unroll
    for (int k = 0; k < 3; k++) {
        const int ss[4] = {s4[k].x, s4[k].y, s4[k].z, s4[k].w};
        const int dd[4] = {d4[k].x, d4[k].y, d4[k].z, d4[k].w};
#pragma unroll
        for (int j = 0; j < 4; j++) rk[k * 4 + j] = 0xffffffffu;
        if (ss[0] >= 0) {
#pragma unroll
            for (int j = 0; j < 4; j++) {
                const int e = k * 4 + j;
                const int s = ss[j], d = dd[j];
                uint32_t sxy, sz, dxy, dz, rxy, rz;
                load_pos(sb + P1_POS, s, sxy, sz);
                load_pos(sb + P1_POS, d, dxy, dz);
                uint32_t db = edge_dist(sxy, sz, dxy, dz, rxy, rz);
                float inv;
                asm("rcp.approx.ftz.f32 %0, %1;" : "=f"(inv) : "f"(__uint_as_float(db << 16)));
                uint32_t bin = __umulhi((uint32_t)d, p.npc_magic);
                uint32_t dl  = (uint32_t)d - bin * (uint32_t)p.npc;
                r0[e] = (uint32_t)s | ((db - D_MIN_BITS) << 16);
                r1[e] = pack_bf(bf_lo(rxy) * inv, bf_hi(rxy) * inv);
                r2[e] = __byte_perm(pack_bf(bf_lo(rz) * inv, 0.f), dl, 0x5410);
                if (db <= D_MAX_BITS) rk[e] = (uint32_t)atomicAdd(&binCnt[bin], 1) | (bin << 16);
            }
        }
    }
    STAMP(2);
    __syncthreads();
    STAMP(3);
    if (warp == 0) {
        int c[5], s = 0;
#pragma unroll
        for (int i = 0; i < 5; i++) { int b = lane * 5 + i; c[i] = b < p.ncta ? binCnt[b] : 0; s += c[i]; }
        int x = s;
#pragma unroll
        for (int o = 1; o < 32; o <<= 1) { int y = __shfl_up_sync(0xffffffffu, x, o); if (lane >= o) x += y; }
        int off = x - s;
#pragma unroll
        for (int i = 0; i < 5; i++) {
            int b = lane * 5 + i;
            if (b < p.ncta) { binOff[b] = off; g_offs[cta * MAX_CTA + b] = (uint32_t)off | ((uint32_t)c[i] << 16); }
            off += c[i];
        }
        if (lane == 31) ctrl[8] = x;
    }
    __syncthreads();
#pragma unroll
    for (int e = 0; e < 12; e++) {
        if (rk[e] != 0xffffffffu) {
            int pos = binOff[rk[e] >> 16] + (int)(rk[e] & 0xffffu);
            sts128(sb + P1_STAGE + pos * 16, make_uint4(r0[e], r1[e], r2[e], 0u));
        }
    }
    fence_async_smem();
    __syncthreads();
    if (tid == 0) {
        const uint32_t bytes = (uint32_t)ctrl[8] * 16u;
        if (bytes) asm volatile("cp.async.bulk.global.shared::cta.bulk_group [%0], [%1], %2;"
                                ::"l"(g_rec + (size_t)cta * REC_CAP), "r"(sb + P1_STAGE), "r"(bytes) : "memory");
        asm volatile("cp.async.bulk.commit_group;" ::: "memory");
    }
    asm volatile("cp.async.bulk.wait_group 0;" ::: "memory");
    asm volatile("fence.proxy.async;" ::: "memory");

    __syncthreads();
    STAMP(4);
    unsigned bar_target = 0;
    if (tid == 0) {
        unsigned old;
        __threadfence();
        asm volatile("atom.add.release.gpu.global.u32 %0, [%1], 1;" : "=r"(old) : "l"(&g_bar) : "memory");
        bar_target = (old / (unsigned)p.ncta + 1u) * (unsigned)p.ncta;
    }
    if (tid == 0) {
        unsigned cur;
        int spins = 0;
        do {
            asm volatile("ld.acquire.gpu.global.u32 %0, [%1];" : "=r"(cur) : "l"(&g_bar) : "memory");
        } while ((int)(cur - bar_target) < 0 && ++spins < (1 << 24));
        asm volatile("fence.proxy.async;" ::: "memory");
    }
    __syncthreads();
    STAMP(5);

    if (warp == 0) {
        uint32_t v[5];
        int s = 0;
#pragma unroll
        for (int i = 0; i < 5; i++) {
            int b = lane * 5 + i;
            v[i] = b < p.ncta ? __ldcg(&g_offs[b * MAX_CTA + cta]) : 0u;
        }
#pragma unroll
        for (int i = 0; i < 5; i++) s += (int)(v[i] >> 16);
        int x = s;
#pragma unroll
        for (int o = 1; o < 32; o <<= 1) { int y = __shfl_up_sync(0xffffffffu, x, o); if (lane >= o) x += y; }
        const int total = __shfl_sync(0xffffffffu, x, 31);
        int off = x - s;
#pragma unroll
        for (int i = 0; i < 5; i++) {
            int b = lane * 5 + i;
            if (b < p.ncta) { binCnt[b] = (int)v[i]; binOff[b] = off; }
            off += (int)(v[i] >> 16);
        }
        if (lane == 0) {
            ctrl[8] = total;
            if (total > STAGE_CAP) ctrl[1] = 1;
            mbar_expect_tx(bar_rec, total > STAGE_CAP ? 0u : (uint32_t)total * 16u);
        }
    }
    __syncthreads();
    const int total = ctrl[8];
    if (ctrl[1] == 0) {
        const int b = (lane << 4) | warp;
        if (lane < 9 && b < p.ncta) {
            const uint32_t v = (uint32_t)binCnt[b], c = v >> 16;
            if (c) {
                asm volatile("fence.proxy.async;" ::: "memory");
                bulk_g2s(sb + SM_STAGE2 + (uint32_t)binOff[b] * 16u, g_rec + (size_t)b * REC_CAP + (v & 0xffffu), c * 16u, bar_rec);
            }
        }
    }
    mbar_wait(bar_rec, 0);
    if (ctrl[1] == 0) {
        for (int i = tid; i < total; i += NT) {
            uint32_t dl = lds32(sb + SM_STAGE2 + i * 16 + 8) >> 16;
            sts32(sb + SM_STAGE2 + i * 16 + 12, (uint32_t)atomicAdd(&nCnt[dl], 1));
        }
    }
    __syncthreads();
    if (warp == 0) {
        int c[3], s = 0;
#pragma unroll
        for (int i = 0; i < 3; i++) {
            int b = lane * 3 + i;
            c[i] = b < nnodes ? max(16, (nCnt[b] + 15) & ~15) : 0;
            s += c[i];
        }
        int x = s;
#pragma unroll
        for (int o = 1; o < 32; o <<= 1) { int y = __shfl_up_sync(0xffffffffu, x, o); if (lane >= o) x += y; }
        const int slots = __shfl_sync(0xffffffffu, x, 31);
        int off = x - s, below1 = 0, below2 = 0;
#pragma unroll
        for (int i = 0; i < 3; i++) {
            int b = lane * 3 + i;
            if (b < nnodes) {
                nInfo[b] = (uint32_t)off | ((uint32_t)c[i] << 16);
                const int centre3 = 3 * (2 * off + c[i]);
                below1 += centre3 < 2 * slots;
                below2 += centre3 < 4 * slots;
            }
            off += c[i];
        }
        below1 = __reduce_add_sync(0xffffffffu, below1);
        below2 = __reduce_add_sync(0xffffffffu, below2);
        if (lane == 0) {
            ctrl[2] = below1;
            ctrl[3] = below2;
            ctrl[4] = slots;
            if (slots > SLOT_CAP) ctrl[1] = 1;
        }
    }
    __syncthreads();
    if (ctrl[1] == 0) {
        uint16_t* sid = (uint16_t*)(smem + SM_SID);
        uint2* meta = (uint2*)(smem + SM_META);
        for (int i = tid; i < total; i += NT) {
            uint4 r = lds128(sb + SM_STAGE2 + i * 16);
            int pos = (int)(nInfo[r.z >> 16] & 0xffffu) + (int)r.w;
            sid[pos]  = (uint16_t)(r.x & 0xffffu);
            meta[pos] = make_uint2(((r.x >> 16) << 5) | (r.z << 16), r.y);
        }
        for (int i = tid; i < nnodes * 16; i += NT) {
            int nl = i >> 4, c = nCnt[nl];
            int j = (c & ~15) + (i & 15);
            if (j >= c && (j < 16 || (c & 15))) {
                int pos = (int)(nInfo[nl] & 0xffffu) + j;
                sid[pos]  = 0xffffu;
                meta[pos] = make_uint2((uint32_t)TAB_ZERO << 5, 0u);
            }
        }
    }
    fence_async_smem();
    __syncthreads();
    STAMP(6);

    if (__shfl_sync(0xffffffffu, ctrl[1], 0) != 0) {
        float* acc = (float*)(smem + P1_POS);
        for (int i = tid; i < nnodes * 256; i += NT) acc[i] = 0.f;
        __syncthreads();
        const uint16_t* posu = (const uint16_t*)p.pos;
        const uint32_t* tabg = (const uint32_t*)g_table;
        const uint32_t* Fw = (const uint32_t*)g_F;
        for (int e0 = warp * 32; e0 < p.E; e0 += NT) {
            int e = e0 + lane;
            int s = 0, d = 0;
            uint32_t db = 0xffff, rxy = 0, rz = 0;
            bool act = false;
            if (e < p.E) {
                s = p.src[e]; d = p.dst[e];
                if (d >= node0 && d < node0 + nnodes) {
                    uint32_t sxy = posu[s * 3] | ((uint32_t)posu[s * 3 + 1] << 16), sz = posu[s * 3 + 2];
                    uint32_t dxy = posu[d * 3] | ((uint32_t)posu[d * 3 + 1] << 16), dz = posu[d * 3 + 2];
                    db  = edge_dist(sxy, sz, dxy, dz, rxy, rz);
                    act = db <= D_MAX_BITS;
                }
            }
            unsigned m = __ballot_sync(0xffffffffu, act);
            while (m) {
                int l = __ffs(m) - 1;
                m &= m - 1;
                int es = __shfl_sync(0xffffffffu, s, l), ed = __shfl_sync(0xffffffffu, d, l);
                uint32_t edb = __shfl_sync(0xffffffffu, db, l), exy = __shfl_sync(0xffffffffu, rxy, l), ez = __shfl_sync(0xffffffffu, rz, l);
                float inv = 1.0f / __uint_as_float(edb << 16);
                float rh[3] = {rbf(bf_lo(exy) * inv), rbf(bf_hi(exy) * inv), rbf(bf_lo(ez) * inv)};
                const uint32_t* fr = Fw + (size_t)es * 128 + lane;
                const uint32_t fh = __ldcg(fr);
                const uint32_t q[3] = {__ldcg(fr + 32), __ldcg(fr + 64), __ldcg(fr + 96)};
                float ps0 = 0.f, ps1 = 0.f, pr0 = 0.f, pr1 = 0.f;
                for (int j2 = 0; j2 < 32; j2++) {
                    uint32_t hj = __shfl_sync(0xffffffffu, fh, j2);
                    uint32_t a0 = *(const uint32_t*)(p.w2 + (2 * j2) * 192 + 2 * lane), a1 = *(const uint32_t*)(p.w2 + (2 * j2 + 1) * 192 + 2 * lane);
                    uint32_t b0 = *(const uint32_t*)(p.w2 + (2 * j2) * 192 + 128 + 2 * lane), b1 = *(const uint32_t*)(p.w2 + (2 * j2 + 1) * 192 + 128 + 2 * lane);
                    ps0 += bf_lo(hj) * bf_lo(a0) + bf_hi(hj) * bf_lo(a1);
                    ps1 += bf_lo(hj) * bf_hi(a0) + bf_hi(hj) * bf_hi(a1);
                    pr0 += bf_lo(hj) * bf_lo(b0) + bf_hi(hj) * bf_lo(b1);
                    pr1 += bf_lo(hj) * bf_hi(b0) + bf_hi(hj) * bf_hi(b1);
                }
                float ws0 = 0.f, ws1 = 0.f, wv0 = 0.f, wv1 = 0.f, wr0 = 0.f, wr1 = 0.f;
                for (int k2 = 0; k2 < 8; k2++) {
                    uint32_t rk2 = __ldcg(tabg + (edb - D_MIN_BITS) * 8 + k2);
#pragma unroll
                    for (int h = 0; h < 2; h++) {
                        float rv = h ? bf_hi(rk2) : bf_lo(rk2);
                        const __nv_bfloat16* wrow = p.wr + (2 * k2 + h) * 192 + 2 * lane;
                        uint32_t a = *(const uint32_t*)wrow, b = *(const uint32_t*)(wrow + 64), c = *(const uint32_t*)(wrow + 128);
                        ws0 += rv * bf_lo(a); ws1 += rv * bf_hi(a);
                        wv0 += rv * bf_lo(b); wv1 += rv * bf_hi(b);
                        wr0 += rv * bf_lo(c); wr1 += rv * bf_hi(c);
                    }
                }
                float* a = acc + (ed - node0) * 256 + 2 * lane;
                atomicAdd(a, ps0 * ws0); atomicAdd(a + 1, ps1 * ws1);
#pragma unroll
                for (int c = 0; c < 3; c++) {
                    atomicAdd(a + 64 * (c + 1), wv0 * bf_lo(q[c]) + pr0 * wr0 * rh[c]);
                    atomicAdd(a + 64 * (c + 1) + 1, wv1 * bf_hi(q[c]) + pr1 * wr1 * rh[c]);
                }
            }
        }
        __syncthreads();
        for (int i = tid; i < nnodes * 128; i += NT) {
            uint32_t r = *(const uint32_t*)(p.sv + (size_t)node0 * 256 + 2 * i);
            *(uint32_t*)(p.out + (size_t)node0 * 256 + 2 * i) = pack_bf(bf_lo(r) + acc[2 * i], bf_hi(r) + acc[2 * i + 1]);
        }
        return;
    }

    const int slots = ctrl[4];
    const int nstage = slots <= SLOT_CAP4 ? 4 : 3;
    const uint32_t ring = sb + (nstage == 4 ? SM_RING4 : SM_RING3);
    if (warp >= 4 * NCWG) {
        asm volatile("setmaxnreg.dec.sync.aligned.u32 56;");
        const int wg = warp - 4 * NCWG;
        if (wg < NCWG) {
            const int nb = wg == 0 ? 0 : ctrl[1 + wg], ne = wg == NCWG - 1 ? nnodes : ctrl[2 + wg];
            const int g0 = (nb < nnodes ? (int)(nInfo[nb] & 0xffffu) : slots) >> 4;
            const int g1 = (ne < nnodes ? (int)(nInfo[ne] & 0xffffu) : slots) >> 4;
            const int e = lane >> 1, half = lane & 1;
            const uint32_t coef_off = e * 128 + ((half ^ (e & 7)) << 4);
            int stage = 0, phase = 1;
            uint2 m = make_uint2(0u, 0u);
            uint4 tv = make_uint4(0u, 0u, 0u, 0u);
            if (g0 < g1) {
                m  = lds64(sb + SM_META + (g0 * 16 + e) * 8);
                tv = __ldg((const uint4*)((const uint8_t*)g_table + (m.x & 0xffffu) + half * 16));
            }
            for (int gi = g0; gi < g1; gi++) {
                const uint32_t st = ring + (wg * nstage + stage) * STAGE_B;
                const uint32_t fb = bar_full + (wg * MAX_STAGE + stage) * 8;
                const uint2 mc = m;
                const uint4 tc = tv;
                if (gi + 1 < g1) {
                    m  = lds64(sb + SM_META + ((gi + 1) * 16 + e) * 8);
                    tv = __ldg((const uint4*)((const uint8_t*)g_table + (m.x & 0xffffu) + half * 16));
                }
                const uint4 ia = lds128(sb + SM_SID + gi * 32), ib = lds128(sb + SM_SID + gi * 32 + 16);
                mbar_wait(bar_empty + (wg * MAX_STAGE + stage) * 8, phase);
                uint32_t leader;
                asm volatile("{\n.reg .pred p;\nelect.sync _|p, 0xffffffff;\nselp.u32 %0, 1, 0, p;\n}" : "=r"(leader));
                if (leader) {
                    const uint32_t id2[8] = {ia.x, ia.y, ia.z, ia.w, ib.x, ib.y, ib.z, ib.w};
#pragma unroll
                    for (int i = 0; i < 8; i++) {
                        tma_load(st + 2048 + (2 * i) * 640, &tmF, (int)(id2[i] & 0xffffu) * 4, fb);
                        tma_load(st + 2048 + (2 * i + 1) * 640, &tmF, (int)(id2[i] >> 16) * 4, fb);
                    }
                }
                __syncwarp();
                const uint32_t mx = __byte_perm(mc.y, 0, 0x1010), my = __byte_perm(mc.y, 0, 0x3232), mz = __byte_perm(mc.x, 0, 0x3232);
                const uint32_t a = st + coef_off;
                sts128(a, tc);
                sts128(a ^ 0x20, make_uint4(hmul2(tc.x, mx), hmul2(tc.y, mx), hmul2(tc.z, mx), hmul2(tc.w, mx)));
                sts128(a ^ 0x40, make_uint4(hmul2(tc.x, my), hmul2(tc.y, my), hmul2(tc.z, my), hmul2(tc.w, my)));
                sts128(a ^ 0x60, make_uint4(hmul2(tc.x, mz), hmul2(tc.y, mz), hmul2(tc.z, mz), hmul2(tc.w, mz)));
                fence_async_smem();
                __syncwarp();
                if (lane == 0) mbar_expect_tx(fb, 16 * 512);
                if (++stage == nstage) { stage = 0; phase ^= 1; }
            }
        }
    } else {
        asm volatile("setmaxnreg.inc.sync.aligned.u32 152;");
        const int wg = warp >> 2, w = warp & 3;
        const int n_begin = wg == 0 ? 0 : ctrl[1 + wg], n_end = wg == NCWG - 1 ? nnodes : ctrl[2 + wg];
        uint32_t wA[2][4][4];
        uint32_t wp[3][4];
        {
            const uint16_t* w2 = (const uint16_t*)p.w2 + 16 * w + g;
#pragma unroll
            for (int m = 0; m < 2; m++) {
#pragma unroll
                for (int ks = 0; ks < 4; ks++) {
#pragma unroll
                    for (int i = 0; i < 4; i++) {
                        const uint16_t* q = w2 + (16 * ks + 2 * t + 8 * (i >> 1)) * 192 + m * 128 + 8 * (i & 1);
                        wA[m][ks][i] = (uint32_t)__ldg(q) | ((uint32_t)__ldg(q + 192) << 16);
                    }
                }
            }
            const uint16_t* wr = (const uint16_t*)p.wr + 16 * w + g;
#pragma unroll
            for (int ty = 0; ty < 3; ty++) {
#pragma unroll
                for (int i = 0; i < 4; i++) {
                    const uint16_t* q = wr + (8 * (i >> 1) + 2 * t) * 192 + ty * 64 + 8 * (i & 1);
                    wp[ty][i] = (uint32_t)__ldg(q) | ((uint32_t)__ldg(q + 192) << 16);
                }
            }
        }
        uint32_t aoff[4];
        {
            const int e = (lane & 7) + 8 * (lane >> 4), ch = 2 * w + ((lane >> 3) & 1);
#pragma unroll
            for (int b = 0; b < 4; b++) aoff[b] = 2048 + e * 640 + b * 128 + ((ch ^ ((5 * e + b) & 7)) << 4);
        }
        const uint32_t ht = sb + SM_HT + wg * 8192;
        const uint32_t stsm_a = ht + (16 * w + (lane & 15)) * 128 + (((lane >> 4) ^ (lane & 7)) << 4);
        const uint32_t dht = desc_lo(ht);
        const uint32_t out_lane = (uint32_t)node0 * 512u + t * 128 + (16 * w + (g & 1) * 8 + (g & 6)) * 2;
        const uint32_t ring_wg = ring + wg * nstage * STAGE_B;
        const uint32_t full_wg = bar_full + wg * MAX_STAGE * 8, empty_wg = bar_empty + wg * MAX_STAGE * 8;
        float ys[8], yv[24], dQ[3][8];
#pragma unroll
        for (int i = 0; i < 24; i++) yv[i] = 0.f;
#pragma unroll
        for (int i = 0; i < 8; i++) { ys[i] = 0.f; dQ[0][i] = 0.f; dQ[1][i] = 0.f; dQ[2][i] = 0.f; }

        int left;
        {
            const int s0 = n_begin < nnodes ? (int)(nInfo[n_begin] & 0xffffu) : slots;
            const int s1 = n_end < nnodes ? (int)(nInfo[n_end] & 0xffffu) : slots;
            left = __shfl_sync(0xffffffffu, (s1 - s0) >> 4, 0);
        }
        int stage = 0, phase = 0;
        uint32_t A0[4][4];
        auto fetch = [&](uint32_t (&A)[4][4]) {
            const uint32_t st = ring_wg + stage * STAGE_B;
            mbar_wait(full_wg + stage * 8, phase);
#pragma unroll
            for (int b = 0; b < 4; b++) ldsm4t(A[b], st + aoff[b]);
            if (++stage == nstage) { stage = 0; phase ^= 1; }
        };
        int cstage = 0;
        int nl = n_begin, gi = 0, G = 0;
        uint32_t resid = 0;
        auto node_begin = [&]() {
            G = __shfl_sync(0xffffffffu, (int)(nInfo[nl] >> 20), 0);
            resid = __ldg((const uint32_t*)((const uint8_t*)p.sv + (out_lane + (uint32_t)nl * 512u)));
            gi = 0;
        };
        auto epilogue = [&]() {
            named_barrier(1 + wg);
            stsm4(stsm_a, pack_bf(ys[0], ys[1]), pack_bf(ys[2], ys[3]), pack_bf(ys[4], ys[5]), pack_bf(ys[6], ys[7]));
#pragma unroll
            for (int i = 0; i < 6; i += 2) {
                stsm4(stsm_a ^ ((i + 2) << 4),
                      pack_bf(yv[4 * i], yv[4 * i + 1]), pack_bf(yv[4 * i + 2], yv[4 * i + 3]),
                      pack_bf(yv[4 * i + 4], yv[4 * i + 5]), pack_bf(yv[4 * i + 6], yv[4 * i + 7]));
            }
            fence_async_smem();
            named_barrier(1 + wg);
            wg_fence();
#pragma unroll
            for (int ks = 0; ks < 4; ks++) {
                wgmma_n16(ys, wA[0][ks], dht + ks * 128, ks);
                wgmma_n48(yv, wA[1][ks], dht + ks * 128 + 2, ks);
            }
            wg_commit();
#pragma unroll
            for (int i = 0; i < 12; i++) asm volatile("" : "+r"(wp[i >> 2][i & 3]));
            float pr[4][2];
#pragma unroll
            for (int a = 0; a < 3; a++) {
                const float* q = dQ[a];
                pr[a + 1][0] = bf_lo(wp[1][0]) * q[0] + bf_hi(wp[1][0]) * q[1] + bf_lo(wp[1][2]) * q[4] + bf_hi(wp[1][2]) * q[5];
                pr[a + 1][1] = bf_lo(wp[1][1]) * q[2] + bf_hi(wp[1][1]) * q[3] + bf_lo(wp[1][3]) * q[6] + bf_hi(wp[1][3]) * q[7];
            }
            wg_wait0();
            pr[0][0] = bf_lo(wp[0][0]) * ys[0] + bf_hi(wp[0][0]) * ys[1] + bf_lo(wp[0][2]) * ys[4] + bf_hi(wp[0][2]) * ys[5];
            pr[0][1] = bf_lo(wp[0][1]) * ys[2] + bf_hi(wp[0][1]) * ys[3] + bf_lo(wp[0][3]) * ys[6] + bf_hi(wp[0][3]) * ys[7];
#pragma unroll
            for (int a = 0; a < 3; a++) {
                const float* y = yv + 8 * a;
                pr[a + 1][0] += bf_lo(wp[2][0]) * y[0] + bf_hi(wp[2][0]) * y[1] + bf_lo(wp[2][2]) * y[4] + bf_hi(wp[2][2]) * y[5];
                pr[a + 1][1] += bf_lo(wp[2][1]) * y[2] + bf_hi(wp[2][1]) * y[3] + bf_lo(wp[2][3]) * y[6] + bf_hi(wp[2][3]) * y[7];
            }
            const bool hi2 = t & 2, hi1 = t & 1, odd = g & 1;
            float ka0 = hi2 ? pr[2][0] : pr[0][0], ka1 = hi2 ? pr[2][1] : pr[0][1];
            float kb0 = hi2 ? pr[3][0] : pr[1][0], kb1 = hi2 ? pr[3][1] : pr[1][1];
            float sa0 = hi2 ? pr[0][0] : pr[2][0], sa1 = hi2 ? pr[0][1] : pr[2][1];
            float sb0 = hi2 ? pr[1][0] : pr[3][0], sb1 = hi2 ? pr[1][1] : pr[3][1];
            ka0 += __shfl_xor_sync(0xffffffffu, sa0, 2); ka1 += __shfl_xor_sync(0xffffffffu, sa1, 2);
            kb0 += __shfl_xor_sync(0xffffffffu, sb0, 2); kb1 += __shfl_xor_sync(0xffffffffu, sb1, 2);
            float k0 = hi1 ? kb0 : ka0, k1 = hi1 ? kb1 : ka1;
            float s0 = hi1 ? ka0 : kb0, s1 = hi1 ? ka1 : kb1;
            k0 += __shfl_xor_sync(0xffffffffu, s0, 1);
            k1 += __shfl_xor_sync(0xffffffffu, s1, 1);
            const float other = __shfl_xor_sync(0xffffffffu, odd ? k0 : k1, 4);
            const float lo = odd ? other : k0, hi = odd ? k1 : other;
            *(uint32_t*)((uint8_t*)p.out + (out_lane + (uint32_t)nl * 512u)) = pack_bf(bf_lo(resid) + lo, bf_hi(resid) + hi);
        };
        if (left > 0) node_begin();
        while (left > 0) {
            fetch(A0);
            const uint32_t bd = desc_lo(ring_wg + cstage * STAGE_B);
            wg_fence();
            wgmma_n64(ys, yv, A0[0], bd, gi);
            wgmma_n16(dQ[0], A0[1], bd, gi);
            wgmma_n16(dQ[1], A0[2], bd, gi);
            wgmma_n16(dQ[2], A0[3], bd, gi);
            wg_commit();
            wg_wait0();
            if (lane == 0) mbar_arrive(empty_wg + cstage * 8);
            if (++cstage == nstage) cstage = 0;
            --left;
            if (++gi == G) {
                epilogue();
                if (++nl < n_end) node_begin();
            }
        }
    }
    STAMP(8);
}

typedef CUresult (*EncodeFn)(CUtensorMap*, CUtensorMapDataType, cuuint32_t, void*, const cuuint64_t*, const cuuint64_t*,
                             const cuuint32_t*, const cuuint32_t*, CUtensorMapInterleave, CUtensorMapSwizzle,
                             CUtensorMapL2promotion, CUtensorMapFloatOOBfill);

void make_map(EncodeFn enc, CUtensorMap* tm, const void* base, uint64_t lines, uint32_t box) {
    cuuint64_t gd[2] = {64, lines};
    cuuint64_t gs[1] = {128};
    cuuint32_t bd[2] = {64, box};
    cuuint32_t es[2] = {1, 1};
    enc(tm, CU_TENSOR_MAP_DATA_TYPE_BFLOAT16, 2, const_cast<void*>(base), gd, gs, bd, es, CU_TENSOR_MAP_INTERLEAVE_NONE,
        CU_TENSOR_MAP_SWIZZLE_128B, CU_TENSOR_MAP_L2_PROMOTION_L2_128B, CU_TENSOR_MAP_FLOAT_OOB_FILL_NONE);
}

}

extern "C" void kernel_launch(void* const* d_in, const int* in_sizes, int n_in, void* d_out, int out_size) {
    (void)n_in; (void)out_size;
    static int n_sm = 0;
    static EncodeFn enc = nullptr;
    static void* f_ptr = nullptr;
    if (n_sm == 0) {
        int dev = 0;
        cudaGetDevice(&dev);
        cudaDeviceGetAttribute(&n_sm, cudaDevAttrMultiProcessorCount, dev);
        cudaFuncSetAttribute(painn_kernel, cudaFuncAttributeMaxDynamicSharedMemorySize, SM_TOTAL);
        void* fn = nullptr;
        cudaDriverEntryPointQueryResult qr;
        cudaGetDriverEntryPoint("cuTensorMapEncodeTiled", &fn, cudaEnableDefault, &qr);
        enc = (EncodeFn)fn;
        cudaGetSymbolAddress(&f_ptr, g_F);
    }
    Params p;
    p.sv    = (const __nv_bfloat16*)d_in[0];
    p.pos   = (const __nv_bfloat16*)d_in[1];
    p.src   = (const int*)d_in[2];
    p.dst   = (const int*)d_in[3];
    p.freqs = (const __nv_bfloat16*)d_in[4];
    p.w1    = (const __nv_bfloat16*)d_in[5];
    p.w2    = (const __nv_bfloat16*)d_in[6];
    p.wr    = (const __nv_bfloat16*)d_in[7];
    p.out   = (__nv_bfloat16*)d_out;
    p.N = in_sizes[1] / 3;
    p.E = in_sizes[2];
    p.ncta = n_sm < MAX_CTA ? n_sm : MAX_CTA;
    p.npc = (p.N + p.ncta - 1) / p.ncta;
    p.npc_magic = (uint32_t)(0x100000000ull / (uint32_t)p.npc) + 1u;
    p.quads_per_cta = ((p.E >> 2) + p.ncta - 1) / p.ncta;
    if (!enc || p.N > MAX_N || p.npc > MAX_NPC || (p.E & 3) || p.quads_per_cta > MAX_ROUNDS * 32) return;

    CUtensorMap tmF, tmSV, tmW1, tmW2;
    make_map(enc, &tmF, f_ptr, (uint64_t)p.N * 4, 4);
    make_map(enc, &tmSV, p.sv, (uint64_t)p.N * 4, 160);
    make_map(enc, &tmW1, p.w1, 64, 64);
    make_map(enc, &tmW2, p.w2, 192, 192);

    cudaLaunchConfig_t cfg = {};
    cfg.gridDim = dim3(p.ncta);
    cfg.blockDim = dim3(NT);
    cfg.dynamicSmemBytes = SM_TOTAL;
    cfg.stream = cudaStreamPerThread;
    cudaLaunchAttribute attr[1];
    attr[0].id = cudaLaunchAttributeCooperative;
    attr[0].val.cooperative = 1;
    cfg.attrs = attr;
    cfg.numAttrs = 1;
    cudaLaunchKernelEx(&cfg, painn_kernel, p, tmF, tmSV, tmW1, tmW2);
}
```

```cpp
#include <cuda_runtime.h>
#include <cuda.h>
#include <cuda_bf16.h>
#include <stdint.h>

namespace {

constexpr int NT        = 512;
constexpr int NCWG      = 3;
constexpr int MAX_N     = 10240;
constexpr int MAX_CTA   = 144;
constexpr int MAX_NPC   = 80;
constexpr int MAX_ROUNDS = 38;
constexpr int REC_CAP   = MAX_ROUNDS * 128;
constexpr int SLOT_CAP  = 6144;
constexpr int MAX_STAGE = 4;
constexpr int STAGE_B   = 12288;

constexpr uint32_t D_MIN_BITS = 0x38D2;
constexpr uint32_t D_MAX_BITS = 0x409C;
constexpr int TAB_ROWS  = (int)(D_MAX_BITS - D_MIN_BITS) + 1;
constexpr int TAB_ZERO  = TAB_ROWS;
constexpr int TAB_BYTES = (TAB_ROWS + 1) * 32;

constexpr int SM_BINCNT = 0;
constexpr int SM_BINOFF = SM_BINCNT + MAX_CTA * 4;
constexpr int SM_NCNT   = SM_BINOFF + MAX_CTA * 4;
constexpr int SM_NINFO  = SM_NCNT + MAX_NPC * 4;
constexpr int SM_CTRL   = SM_NINFO + MAX_NPC * 4;
constexpr int SM_BARS   = SM_CTRL + 64;
constexpr int SM_SID    = 2048 + 128;
constexpr int SM_META   = SM_SID + SLOT_CAP * 2;
constexpr int SM_TOTAL  = 232448;
constexpr int SM_HT     = (SM_TOTAL - NCWG * 8192) / 1024 * 1024;
constexpr int SM_RING4  = SM_HT - NCWG * 4 * STAGE_B;
constexpr int SM_RING3  = SM_HT - NCWG * 3 * STAGE_B;
constexpr int SLOT_CAP4 = (SM_RING4 - SM_META) / 8;
constexpr int SM_STAGE2 = SM_RING3 - 0;
constexpr int STAGE_CAP = (SM_TOTAL - SM_RING3) / 16;
constexpr int P1_POS    = 3072;
constexpr int P1_STAGE  = P1_POS + 61440;
constexpr int P1_SV     = (P1_STAGE + REC_CAP * 16 + 1023) / 1024 * 1024;
constexpr int P1_W1     = P1_SV + MAX_NPC * 512;
constexpr int P1_W2     = P1_W1 + 8192;
constexpr int P1_END    = P1_W2 + 24576;
static_assert(SM_BARS + (4 + 2 * NCWG * MAX_STAGE) * 8 <= SM_SID, "misc block");
static_assert(SM_SID + SLOT_CAP * 2 <= P1_POS + 61440 && SM_BARS + 256 <= P1_POS, "misc block");
static_assert(P1_END <= SM_TOTAL, "phase 1 overlay");
static_assert(SM_META + SLOT_CAP * 8 <= SM_RING3, "CSR");
static_assert(SM_RING4 % 1024 == 0 && SM_RING3 % 1024 == 0 && SM_HT % 1024 == 0, "alignment");
static_assert(SM_BARS % 8 == 0 && SM_META % 8 == 0, "alignment");
static_assert(MAX_N * 6 <= 61440, "pos");
static_assert(SM_SID + MAX_NPC * 1024 <= SM_TOTAL, "slow path accumulators");

__device__ __align__(1024) uint4 g_F[MAX_N * 32];
__device__ uint4    g_rec[MAX_CTA * REC_CAP];
__device__ uint32_t g_offs[MAX_CTA * MAX_CTA];
__device__ uint4    g_table[(TAB_BYTES + 15) / 16];
__device__ unsigned g_bar;
#define STAMP(k)

struct Params {
    const __nv_bfloat16* sv;
    const __nv_bfloat16* pos;
    const int*           src;
    const int*           dst;
    const __nv_bfloat16* freqs;
    const __nv_bfloat16* w1;
    const __nv_bfloat16* w2;
    const __nv_bfloat16* wr;
    __nv_bfloat16*       out;
    int N, E, ncta, npc;
    uint32_t npc_magic;
    int quads_per_cta;
};

__device__ __forceinline__ uint32_t smem_u32(const void* p) { return (uint32_t)__cvta_generic_to_shared(p); }
__device__ __forceinline__ float bf_lo(uint32_t v) { return __uint_as_float(v << 16); }
__device__ __forceinline__ float bf_hi(uint32_t v) { return __uint_as_float(v & 0xffff0000u); }
__device__ __forceinline__ float bf_u16(uint16_t v) { return __uint_as_float((uint32_t)v << 16); }
__device__ __forceinline__ uint32_t pack_bf(float lo, float hi) {
    uint32_t r;
    asm("cvt.rn.bf16x2.f32 %0, %1, %2;" : "=r"(r) : "f"(hi), "f"(lo));
    return r;
}
__device__ __forceinline__ float rbf(float x) { return bf_lo(pack_bf(x, 0.f)); }
__device__ __forceinline__ uint32_t hmul2(uint32_t a, uint32_t b) {
    uint32_t r;
    asm("mul.rn.bf16x2 %0, %1, %2;" : "=r"(r) : "r"(a), "r"(b));
    return r;
}
__device__ __forceinline__ uint32_t hsub2(uint32_t a, uint32_t b) {
    uint32_t r;
    asm("sub.rn.bf16x2 %0, %1, %2;" : "=r"(r) : "r"(a), "r"(b));
    return r;
}
__device__ __forceinline__ uint32_t lds32(uint32_t a) { uint32_t v; asm volatile("ld.shared.u32 %0, [%1];" : "=r"(v) : "r"(a)); return v; }
__device__ __forceinline__ uint32_t lds16(uint32_t a) { uint16_t v; asm volatile("ld.shared.u16 %0, [%1];" : "=h"(v) : "r"(a)); return v; }
__device__ __forceinline__ uint2 lds64(uint32_t a) { uint2 v; asm volatile("ld.shared.v2.u32 {%0,%1}, [%2];" : "=r"(v.x), "=r"(v.y) : "r"(a)); return v; }
__device__ __forceinline__ uint4 lds128(uint32_t a) { uint4 v; asm volatile("ld.shared.v4.u32 {%0,%1,%2,%3}, [%4];" : "=r"(v.x), "=r"(v.y), "=r"(v.z), "=r"(v.w) : "r"(a)); return v; }
__device__ __forceinline__ void sts32(uint32_t a, uint32_t v) { asm volatile("st.shared.u32 [%0], %1;" ::"r"(a), "r"(v) : "memory"); }
__device__ __forceinline__ void sts128(uint32_t a, uint4 v) { asm volatile("st.shared.v4.u32 [%0], {%1,%2,%3,%4};" ::"r"(a), "r"(v.x), "r"(v.y), "r"(v.z), "r"(v.w) : "memory"); }
__device__ __forceinline__ void mbar_init(uint32_t bar, int cnt) { asm volatile("mbarrier.init.shared::cta.b64 [%0], %1;" ::"r"(bar), "r"(cnt) : "memory"); }
__device__ __forceinline__ void mbar_expect_tx(uint32_t bar, uint32_t bytes) { asm volatile("mbarrier.arrive.expect_tx.shared::cta.b64 _, [%0], %1;" ::"r"(bar), "r"(bytes) : "memory"); }
__device__ __forceinline__ void mbar_arrive(uint32_t bar) { asm volatile("mbarrier.arrive.shared::cta.b64 _, [%0];" ::"r"(bar) : "memory"); }
__device__ __forceinline__ void mbar_wait(uint32_t bar, uint32_t parity) {
    uint32_t done;
    int spins = 0;
    do {
        asm volatile("{\n.reg .pred p;\nmbarrier.try_wait.parity.shared::cta.b64 p, [%1], %2;\nselp.u32 %0, 1, 0, p;\n}"
                     : "=r"(done) : "r"(bar), "r"(parity) : "memory");
    } while (!done && ++spins < (1 << 22));
}
__device__ __forceinline__ void bulk_g2s(uint32_t dst, const void* src, uint32_t bytes, uint32_t bar) {
    asm volatile("cp.async.bulk.shared::cluster.global.mbarrier::complete_tx::bytes [%0], [%1], %2, [%3];"
                 ::"r"(dst), "l"(src), "r"(bytes), "r"(bar) : "memory");
}
__device__ __forceinline__ void tma_load(uint32_t dst, const CUtensorMap* tm, int line, uint32_t bar) {
    asm volatile("cp.async.bulk.tensor.2d.shared::cluster.global.mbarrier::complete_tx::bytes [%0], [%1, {%3, %4}], [%2];"
                 ::"r"(dst), "l"(tm), "r"(bar), "r"(0), "r"(line) : "memory");
}
__device__ __forceinline__ void tma_store(const CUtensorMap* tm, int line, uint32_t src) {
    asm volatile("cp.async.bulk.tensor.2d.global.shared::cta.bulk_group [%0, {%2, %3}], [%1];"
                 ::"l"(tm), "r"(src), "r"(0), "r"(line) : "memory");
}
__device__ __forceinline__ void fence_async_smem() { asm volatile("fence.proxy.async.shared::cta;" ::: "memory"); }
__device__ __forceinline__ void named_barrier(int id) { asm volatile("bar.sync %0, 128;" ::"r"(id) : "memory"); }
__device__ __forceinline__ void ldsm4(uint32_t (&r)[4], uint32_t a) {
    asm volatile("ldmatrix.sync.aligned.m8n8.x4.shared.b16 {%0,%1,%2,%3}, [%4];" : "=r"(r[0]), "=r"(r[1]), "=r"(r[2]), "=r"(r[3]) : "r"(a) : "memory");
}
__device__ __forceinline__ void ldsm4t(uint32_t (&r)[4], uint32_t a) {
    asm volatile("ldmatrix.sync.aligned.m8n8.x4.trans.shared.b16 {%0,%1,%2,%3}, [%4];" : "=r"(r[0]), "=r"(r[1]), "=r"(r[2]), "=r"(r[3]) : "r"(a) : "memory");
}
__device__ __forceinline__ void stsm4(uint32_t a, uint32_t r0, uint32_t r1, uint32_t r2, uint32_t r3) {
    asm volatile("stmatrix.sync.aligned.m8n8.x4.shared.b16 [%0], {%1,%2,%3,%4};" ::"r"(a), "r"(r0), "r"(r1), "r"(r2), "r"(r3) : "memory");
}
__device__ __forceinline__ void mma16816(float (&c)[4], const uint32_t (&a)[4], uint32_t b0, uint32_t b1) {
    asm volatile("mma.sync.aligned.m16n8k16.row.col.f32.bf16.bf16.f32 {%0,%1,%2,%3}, {%4,%5,%6,%7}, {%8,%9}, {%0,%1,%2,%3};"
                 : "+f"(c[0]), "+f"(c[1]), "+f"(c[2]), "+f"(c[3])
                 : "r"(a[0]), "r"(a[1]), "r"(a[2]), "r"(a[3]), "r"(b0), "r"(b1));
}

__device__ __forceinline__ uint32_t desc_lo(uint32_t saddr) { return ((saddr & 0x3FFFF) >> 4) | (1u << 16); }
#define DESC_HI "0x40000040"
__device__ __forceinline__ void wg_fence() { asm volatile("wgmma.fence.sync.aligned;" ::: "memory"); }
__device__ __forceinline__ void wg_commit() { asm volatile("wgmma.commit_group.sync.aligned;" ::: "memory"); }
__device__ __forceinline__ void wg_wait0() { asm volatile("wgmma.wait_group.sync.aligned 0;" ::: "memory"); }

__device__ __forceinline__ void wgmma_n64(float (&d)[8], float (&e)[24], const uint32_t (&a)[4], uint32_t bdesc, int scale) {
    asm volatile("{\n.reg .pred p;\n.reg .b64 b;\nsetp.ne.b32 p, %37, 0;\nmov.b64 b, {%36, " DESC_HI "};\n"
                 "wgmma.mma_async.sync.aligned.m64n64k16.f32.bf16.bf16 "
                 "{%0,%1,%2,%3,%4,%5,%6,%7,%8,%9,%10,%11,%12,%13,%14,%15,%16,%17,%18,%19,%20,%21,%22,%23,%24,%25,%26,%27,%28,%29,%30,%31}, "
                 "{%32,%33,%34,%35}, b, p, 1, 1, 1;\n}"
                 : "+f"(d[0]), "+f"(d[1]), "+f"(d[2]), "+f"(d[3]), "+f"(d[4]), "+f"(d[5]), "+f"(d[6]), "+f"(d[7]),
                   "+f"(e[0]), "+f"(e[1]), "+f"(e[2]), "+f"(e[3]), "+f"(e[4]), "+f"(e[5]), "+f"(e[6]), "+f"(e[7]),
                   "+f"(e[8]), "+f"(e[9]), "+f"(e[10]), "+f"(e[11]), "+f"(e[12]), "+f"(e[13]), "+f"(e[14]), "+f"(e[15]),
                   "+f"(e[16]), "+f"(e[17]), "+f"(e[18]), "+f"(e[19]), "+f"(e[20]), "+f"(e[21]), "+f"(e[22]), "+f"(e[23])
                 : "r"(a[0]), "r"(a[1]), "r"(a[2]), "r"(a[3]), "r"(bdesc), "r"(scale));
}
__device__ __forceinline__ void wgmma_n48(float (&e)[24], const uint32_t (&a)[4], uint32_t bdesc, int scale) {
    asm volatile("{\n.reg .pred p;\n.reg .b64 b;\nsetp.ne.b32 p, %29, 0;\nmov.b64 b, {%28, " DESC_HI "};\n"
                 "wgmma.mma_async.sync.aligned.m64n48k16.f32.bf16.bf16 "
                 "{%0,%1,%2,%3,%4,%5,%6,%7,%8,%9,%10,%11,%12,%13,%14,%15,%16,%17,%18,%19,%20,%21,%22,%23}, "
                 "{%24,%25,%26,%27}, b, p, 1, 1, 1;\n}"
                 : "+f"(e[0]), "+f"(e[1]), "+f"(e[2]), "+f"(e[3]), "+f"(e[4]), "+f"(e[5]), "+f"(e[6]), "+f"(e[7]),
                   "+f"(e[8]), "+f"(e[9]), "+f"(e[10]), "+f"(e[11]), "+f"(e[12]), "+f"(e[13]), "+f"(e[14]), "+f"(e[15]),
                   "+f"(e[16]), "+f"(e[17]), "+f"(e[18]), "+f"(e[19]), "+f"(e[20]), "+f"(e[21]), "+f"(e[22]), "+f"(e[23])
                 : "r"(a[0]), "r"(a[1]), "r"(a[2]), "r"(a[3]), "r"(bdesc), "r"(scale));
}
__device__ __forceinline__ void wgmma_n16(float (&d)[8], const uint32_t (&a)[4], uint32_t bdesc, int scale) {
    asm volatile("{\n.reg .pred p;\n.reg .b64 b;\nsetp.ne.b32 p, %13, 0;\nmov.b64 b, {%12, " DESC_HI "};\n"
                 "wgmma.mma_async.sync.aligned.m64n16k16.f32.bf16.bf16 {%0,%1,%2,%3,%4,%5,%6,%7}, {%8,%9,%10,%11}, b, p, 1, 1, 1;\n}"
                 : "+f"(d[0]), "+f"(d[1]), "+f"(d[2]), "+f"(d[3]), "+f"(d[4]), "+f"(d[5]), "+f"(d[6]), "+f"(d[7])
                 : "r"(a[0]), "r"(a[1]), "r"(a[2]), "r"(a[3]), "r"(bdesc), "r"(scale));
}

__device__ __forceinline__ uint32_t edge_dist(uint32_t sxy, uint32_t sz, uint32_t dxy, uint32_t dz, uint32_t& rxy, uint32_t& rz) {
    rxy = hsub2(sxy, dxy);
    rz  = hsub2(sz, dz);
    uint32_t qxy = hmul2(rxy, rxy), qz = hmul2(rz, rz);
    float ss = rbf((bf_lo(qxy) + bf_hi(qxy)) + bf_lo(qz));
    float s2 = rbf(ss + 1e-8f);
    float d;
    asm("sqrt.approx.ftz.f32 %0, %1;" : "=f"(d) : "f"(s2));
    return pack_bf(d, 0.f) & 0xffffu;
}

__device__ __forceinline__ void load_pos(uint32_t sm_pos, int i, uint32_t& xy, uint32_t& z) {
    uint32_t a  = (sm_pos + 6u * (uint32_t)i) & ~3u;
    uint32_t w0 = lds32(a), w1 = lds32(a + 4);
    uint32_t sh = (uint32_t)i << 4;
    xy = __funnelshift_r(w0, w1, sh);
    z  = __funnelshift_r(w1, w1, sh);
}

__device__ __noinline__ float radial_value(float d, float f) {
    float arg = rbf(d * f);
    float sn  = rbf(sinf(arg));
    float rb  = rbf(__fdiv_rn(sn, d));
    float c   = rbf(cosf(rbf(__fdiv_rn(rbf(d * 3.14159265358979323846f), 5.0f))));
    float fc  = rbf(0.5f * rbf(c + 1.0f));
    return rb * fc;
}

__global__ void __launch_bounds__(NT, 1)
painn_kernel(const Params p, const __grid_constant__ CUtensorMap tmF, const __grid_constant__ CUtensorMap tmSV,
             const __grid_constant__ CUtensorMap tmW1, const __grid_constant__ CUtensorMap tmW2) {
    extern __shared__ __align__(1024) uint8_t smem[];
    const uint32_t sb   = smem_u32(smem);
    const int tid  = threadIdx.x, lane = tid & 31, warp = __shfl_sync(0xffffffffu, tid >> 5, 0);
    const int cta  = blockIdx.x;
    const int g    = lane >> 2, t = lane & 3;
    int* binCnt = (int*)(smem + SM_BINCNT);
    int* binOff = (int*)(smem + SM_BINOFF);
    int* nCnt   = (int*)(smem + SM_NCNT);
    uint32_t* nInfo = (uint32_t*)(smem + SM_NINFO);
    volatile int* ctrl = (volatile int*)(smem + SM_CTRL);
    const uint32_t bar_pos = sb + SM_BARS, bar_mlp = bar_pos + 8, bar_rec = bar_pos + 16;
    const uint32_t bar_full = bar_pos + 32, bar_empty = bar_full + NCWG * MAX_STAGE * 8;

    const int node0  = cta * p.npc;
    const int nnodes = max(0, min(p.npc, p.N - node0));

    STAMP(0);
    if (tid == 0) {
        mbar_init(bar_pos, 1);
        mbar_init(bar_mlp, 1);
        mbar_init(bar_rec, 1);
        for (int i = 0; i < NCWG * MAX_STAGE; i++) { mbar_init(bar_full + 8 * i, 5); mbar_init(bar_empty + 8 * i, 4); }
        asm volatile("fence.mbarrier_init.release.cluster;" ::: "memory");
        uint32_t pos_bytes = (uint32_t)(p.N * 6 + 15) & ~15u;
        mbar_expect_tx(bar_pos, pos_bytes);
        bulk_g2s(sb + P1_POS, p.pos, pos_bytes, bar_pos);
        mbar_expect_tx(bar_mlp, 2u * 160u * 128u + 8192u + 24576u);
        tma_load(sb + P1_SV, &tmSV, node0 * 4, bar_mlp);
        tma_load(sb + P1_SV + 160 * 128, &tmSV, node0 * 4 + 160, bar_mlp);
        tma_load(sb + P1_W1, &tmW1, 0, bar_mlp);
        tma_load(sb + P1_W2, &tmW2, 0, bar_mlp);
    }
    const bool mlp_warp = warp >= 11;
    int4 s4[3], d4[3];
    const int q0 = cta * p.quads_per_cta;
    const int qend = min(q0 + p.quads_per_cta, p.E >> 2);
    if (!mlp_warp) {
#pragma unroll
        for (int k = 0; k < 3; k++) {
            int q = q0 + (warp + 11 * k) * 32 + lane;
            bool ok = q < qend;
            s4[k] = ok ? __ldg((const int4*)p.src + q) : make_int4(-1, -1, -1, -1);
            d4[k] = ok ? __ldg((const int4*)p.dst + q) : make_int4(0, 0, 0, 0);
        }
    } else {
        int q = q0 + (33 + warp - 11) * 32 + lane;
        if (q < qend && (lane & 7) == 0) {
            asm volatile("prefetch.global.L2 [%0];" ::"l"((const int4*)p.src + q));
            asm volatile("prefetch.global.L2 [%0];" ::"l"((const int4*)p.dst + q));
        }
    }
    if (tid < MAX_CTA) binCnt[tid] = 0;
    if (tid < MAX_NPC) nCnt[tid] = 0;
    if (tid < 16) ctrl[tid] = 0;
    if (tid >= 448 && tid < 448 + 48) {
        asm volatile("prefetch.global.L2 [%0];" ::"l"((const uint8_t*)p.wr + (tid - 448) * 128));
    }
    __syncthreads();

    if (mlp_warp) {
        const int rows_per = (TAB_ROWS + 1 + p.ncta - 1) / p.ncta;
        for (int i = tid - 11 * 32; i < rows_per * 8; i += 5 * 32) {
            int row = cta * rows_per + (i >> 3), kp = i & 7;
            if (row <= TAB_ROWS) {
                uint32_t val = 0;
                if (row < TAB_ROWS) {
                    float d = __uint_as_float((D_MIN_BITS + row) << 16);
                    uint32_t f2 = __ldg((const uint32_t*)p.freqs + kp);
                    val = pack_bf(radial_value(d, bf_lo(f2)), radial_value(d, bf_hi(f2)));
                }
                ((uint32_t*)g_table)[row * 8 + kp] = val;
            }
        }
        const int mt = warp - 11;
        if (mt * 16 < nnodes) {
            mbar_wait(bar_mlp, 0);
            float acc[8][4];
#pragma unroll
            for (int i = 0; i < 8; i++) { acc[i][0] = acc[i][1] = acc[i][2] = acc[i][3] = 0.f; }
            const int lrow = (lane & 7) + ((lane >> 3) & 1) * 8, lch = lane >> 4;
#pragma unroll
            for (int ks = 0; ks < 4; ks++) {
                uint32_t a[4];
                const int line = 4 * (mt * 16 + lrow);
                ldsm4(a, sb + P1_SV + line * 128 + (((2 * ks + lch) ^ (line & 7)) << 4));
                const int kk = 16 * ks + lrow;
#pragma unroll
                for (int nt = 0; nt < 8; nt += 2) {
                    uint32_t b[4];
                    ldsm4t(b, sb + P1_W1 + kk * 128 + (((nt + lch) ^ (kk & 7)) << 4));
                    mma16816(acc[nt], a, b[0], b[1]);
                    mma16816(acc[nt + 1], a, b[2], b[3]);
                }
            }
            uint32_t hp[8][2];
#pragma unroll
            for (int i = 0; i < 8; i++) {
                float h[4];
#pragma unroll
                for (int q = 0; q < 4; q++) {
                    float x = rbf(acc[i][q]);
                    h[q] = __fdividef(x, 1.0f + __expf(-x));
                    acc[i][q] = 0.f;
                }
                hp[i][0] = pack_bf(h[0], h[1]);
                hp[i][1] = pack_bf(h[2], h[3]);
            }
#pragma unroll
            for (int ks = 0; ks < 4; ks++) {
                uint32_t a[4] = {hp[2 * ks][0], hp[2 * ks][1], hp[2 * ks + 1][0], hp[2 * ks + 1][1]};
                const int line = 3 * (16 * ks + lrow) + 1;
#pragma unroll
                for (int nt = 0; nt < 8; nt += 2) {
                    uint32_t b[4];
                    ldsm4t(b, sb + P1_W2 + line * 128 + (((nt + lch) ^ (line & 7)) << 4));
                    mma16816(acc[nt], a, b[0], b[1]);
                    mma16816(acc[nt + 1], a, b[2], b[3]);
                }
            }
            uint32_t q[3][8][2];
#pragma unroll
            for (int rh = 0; rh < 2; rh++) {
                const int row = mt * 16 + g + 8 * rh;
#pragma unroll
                for (int i = 0; i < 8; i++) {
                    const uint32_t ph = pack_bf(acc[i][2 * rh], acc[i][2 * rh + 1]);
#pragma unroll
                    for (int a = 0; a < 3; a++) {
                        const int line = 4 * row + 1 + a;
                        q[a][i][rh] = hmul2(ph, lds32(sb + P1_SV + line * 128 + ((i ^ (line & 7)) << 4) + 4 * t));
                    }
                }
            }
            __syncwarp();
            {
                const int row = mt * 16 + (lane & 7) + ((lane >> 3) & 1) * 8;
#pragma unroll
                for (int c = 0; c < 4; c++) {
                    const int line = 4 * row + c;
                    const uint32_t lb = sb + P1_SV + line * 128;
#pragma unroll
                    for (int i = 0; i < 8; i += 2) {
                        const uint32_t a = lb + (((i + lch) ^ (line & 7)) << 4);
                        if (c == 0) stsm4(a, hp[i][0], hp[i][1], hp[i + 1][0], hp[i + 1][1]);
                        else        stsm4(a, q[c - 1][i][0], q[c - 1][i][1], q[c - 1][i + 1][0], q[c - 1][i + 1][1]);
                    }
                }
            }
            fence_async_smem();
            __syncwarp();
            if (lane < 16 && mt * 16 + lane < nnodes) tma_store(&tmF, (node0 + mt * 16 + lane) * 4, sb + P1_SV + (mt * 16 + lane) * 512);
            asm volatile("cp.async.bulk.commit_group;" ::: "memory");
        }
        const int q = q0 + (33 + warp - 11) * 32 + lane;
        const bool ok = q < qend;
        s4[0] = ok ? __ldg((const int4*)p.src + q) : make_int4(-1, -1, -1, -1);
        d4[0] = ok ? __ldg((const int4*)p.dst + q) : make_int4(0, 0, 0, 0);
        s4[1] = s4[2] = make_int4(-1, -1, -1, -1);
        d4[1] = d4[2] = make_int4(0, 0, 0, 0);
    }
    mbar_wait(bar_pos, 0);
    STAMP(1);

    uint32_t r0[12], r1[12], r2[12], rk[12];
#pragma unroll
    for (int k = 0; k < 3; k++) {
        const int ss[4] = {s4[k].x, s4[k].y, s4[k].z, s4[k].w};
        const int dd[4] = {d4[k].x, d4[k].y, d4[k].z, d4[k].w};
#pragma unroll
        for (int j = 0; j < 4; j++) rk[k * 4 + j] = 0xffffffffu;
        if (ss[0] >= 0) {
#pragma unroll
            for (int j = 0; j < 4; j++) {
                const int e = k * 4 + j;
                const int s = ss[j], d = dd[j];
                uint32_t sxy, sz, dxy, dz, rxy, rz;
                load_pos(sb + P1_POS, s, sxy, sz);
                load_pos(sb + P1_POS, d, dxy, dz);
                uint32_t db = edge_dist(sxy, sz, dxy, dz, rxy, rz);
                float inv;
                asm("rcp.approx.ftz.f32 %0, %1;" : "=f"(inv) : "f"(__uint_as_float(db << 16)));
                uint32_t bin = __umulhi((uint32_t)d, p.npc_magic);
                uint32_t dl  = (uint32_t)d - bin * (uint32_t)p.npc;
                r0[e] = (uint32_t)s | ((db - D_MIN_BITS) << 16);
                r1[e] = pack_bf(bf_lo(rxy) * inv, bf_hi(rxy) * inv);
                r2[e] = __byte_perm(pack_bf(bf_lo(rz) * inv, 0.f), dl, 0x5410);
                if (db <= D_MAX_BITS) rk[e] = (uint32_t)atomicAdd(&binCnt[bin], 1) | (bin << 16);
            }
        }
    }
    STAMP(2);
    __syncthreads();
    STAMP(3);
    if (warp == 0) {
        int c[5], s = 0;
#pragma unroll
        for (int i = 0; i < 5; i++) { int b = lane * 5 + i; c[i] = b < p.ncta ? binCnt[b] : 0; s += c[i]; }
        int x = s;
#pragma unroll
        for (int o = 1; o < 32; o <<= 1) { int y = __shfl_up_sync(0xffffffffu, x, o); if (lane >= o) x += y; }
        int off = x - s;
#pragma unroll
        for (int i = 0; i < 5; i++) {
            int b = lane * 5 + i;
            if (b < p.ncta) { binOff[b] = off; g_offs[cta * MAX_CTA + b] = (uint32_t)off | ((uint32_t)c[i] << 16); }
            off += c[i];
        }
        if (lane == 31) ctrl[8] = x;
    }
    __syncthreads();
#pragma unroll
    for (int e = 0; e < 12; e++) {
        if (rk[e] != 0xffffffffu) {
            int pos = binOff[rk[e] >> 16] + (int)(rk[e] & 0xffffu);
            sts128(sb + P1_STAGE + pos * 16, make_uint4(r0[e], r1[e], r2[e], 0u));
        }
    }
    fence_async_smem();
    __syncthreads();
    if (tid == 0) {
        const uint32_t bytes = (uint32_t)ctrl[8] * 16u;
        if (bytes) asm volatile("cp.async.bulk.global.shared::cta.bulk_group [%0], [%1], %2;"
                                ::"l"(g_rec + (size_t)cta * REC_CAP), "r"(sb + P1_STAGE), "r"(bytes) : "memory");
        asm volatile("cp.async.bulk.commit_group;" ::: "memory");
    }
    asm volatile("cp.async.bulk.wait_group 0;" ::: "memory");
    asm volatile("fence.proxy.async;" ::: "memory");

    __syncthreads();
    STAMP(4);
    unsigned bar_target = 0;
    if (tid == 0) {
        unsigned old;
        __threadfence();
        asm volatile("atom.add.release.gpu.global.u32 %0, [%1], 1;" : "=r"(old) : "l"(&g_bar) : "memory");
        bar_target = (old / (unsigned)p.ncta + 1u) * (unsigned)p.ncta;
    }
    if (tid == 0) {
        unsigned cur;
        int spins = 0;
        do {
            asm volatile("ld.acquire.gpu.global.u32 %0, [%1];" : "=r"(cur) : "l"(&g_bar) : "memory");
        } while ((int)(cur - bar_target) < 0 && ++spins < (1 << 24));
        asm volatile("fence.proxy.async;" ::: "memory");
    }
    __syncthreads();
    STAMP(5);

    if (warp == 0) {
        uint32_t v[5];
        int s = 0;
#pragma unroll
        for (int i = 0; i < 5; i++) {
            int b = lane * 5 + i;
            v[i] = b < p.ncta ? __ldcg(&g_offs[b * MAX_CTA + cta]) : 0u;
        }
#pragma unroll
        for (int i = 0; i < 5; i++) s += (int)(v[i] >> 16);
        int x = s;
#pragma unroll
        for (int o = 1; o < 32; o <<= 1) { int y = __shfl_up_sync(0xffffffffu, x, o); if (lane >= o) x += y; }
        const int total = __shfl_sync(0xffffffffu, x, 31);
        int off = x - s;
#pragma unroll
        for (int i = 0; i < 5; i++) {
            int b = lane * 5 + i;
            if (b < p.ncta) { binCnt[b] = (int)v[i]; binOff[b] = off; }
            off += (int)(v[i] >> 16);
        }
        if (lane == 0) {
            ctrl[8] = total;
            if (total > STAGE_CAP) ctrl[1] = 1;
            mbar_expect_tx(bar_rec, total > STAGE_CAP ? 0u : (uint32_t)total * 16u);
        }
    }
    __syncthreads();
    const int total = ctrl[8];
    if (ctrl[1] == 0) {
        const int b = (lane << 4) | warp;
        if (lane < 9 && b < p.ncta) {
            const uint32_t v = (uint32_t)binCnt[b], c = v >> 16;
            if (c) {
                asm volatile("fence.proxy.async;" ::: "memory");
                bulk_g2s(sb + SM_STAGE2 + (uint32_t)binOff[b] * 16u, g_rec + (size_t)b * REC_CAP + (v & 0xffffu), c * 16u, bar_rec);
            }
        }
    }
    mbar_wait(bar_rec, 0);
    if (ctrl[1] == 0) {
        for (int i = tid; i < total; i += NT) {
            uint32_t dl = lds32(sb + SM_STAGE2 + i * 16 + 8) >> 16;
            sts32(sb + SM_STAGE2 + i * 16 + 12, (uint32_t)atomicAdd(&nCnt[dl], 1));
        }
    }
    __syncthreads();
    if (warp == 0) {
        int c[3], s = 0;
#pragma unroll
        for (int i = 0; i < 3; i++) {
            int b = lane * 3 + i;
            c[i] = b < nnodes ? max(16, (nCnt[b] + 15) & ~15) : 0;
            s += c[i];
        }
        int x = s;
#pragma unroll
        for (int o = 1; o < 32; o <<= 1) { int y = __shfl_up_sync(0xffffffffu, x, o); if (lane >= o) x += y; }
        const int slots = __shfl_sync(0xffffffffu, x, 31);
        int off = x - s, below1 = 0, below2 = 0;
#pragma unroll
        for (int i = 0; i < 3; i++) {
            int b = lane * 3 + i;
            if (b < nnodes) {
                nInfo[b] = (uint32_t)off | ((uint32_t)c[i] << 16);
                const int centre3 = 3 * (2 * off + c[i]);
                below1 += centre3 < 2 * slots;
                below2 += centre3 < 4 * slots;
            }
            off += c[i];
        }
        below1 = __reduce_add_sync(0xffffffffu, below1);
        below2 = __reduce_add_sync(0xffffffffu, below2);
        if (lane == 0) {
            ctrl[2] = below1;
            ctrl[3] = below2;
            ctrl[4] = slots;
            if (slots > SLOT_CAP) ctrl[1] = 1;
        }
    }
    __syncthreads();
    if (ctrl[1] == 0) {
        uint16_t* sid = (uint16_t*)(smem + SM_SID);
        uint2* meta = (uint2*)(smem + SM_META);
        for (int i = tid; i < total; i += NT) {
            uint4 r = lds128(sb + SM_STAGE2 + i * 16);
            int pos = (int)(nInfo[r.z >> 16] & 0xffffu) + (int)r.w;
            sid[pos]  = (uint16_t)(r.x & 0xffffu);
            meta[pos] = make_uint2(((r.x >> 16) << 5) | (r.z << 16), r.y);
        }
        for (int i = tid; i < nnodes * 16; i += NT) {
            int nl = i >> 4, c = nCnt[nl];
            int j = (c & ~15) + (i & 15);
            if (j >= c && (j < 16 || (c & 15))) {
                int pos = (int)(nInfo[nl] & 0xffffu) + j;
                sid[pos]  = 0xffffu;
                meta[pos] = make_uint2((uint32_t)TAB_ZERO << 5, 0u);
            }
        }
    }
    fence_async_smem();
    __syncthreads();
    STAMP(6);

    if (__shfl_sync(0xffffffffu, ctrl[1], 0) != 0) {
        float* acc = (float*)(smem + P1_POS);
        for (int i = tid; i < nnodes * 256; i += NT) acc[i] = 0.f;
        __syncthreads();
        const uint16_t* posu = (const uint16_t*)p.pos;
        const uint32_t* tabg = (const uint32_t*)g_table;
        const uint32_t* Fw = (const uint32_t*)g_F;
        for (int e0 = warp * 32; e0 < p.E; e0 += NT) {
            int e = e0 + lane;
            int s = 0, d = 0;
            uint32_t db = 0xffff, rxy = 0, rz = 0;
            bool act = false;
            if (e < p.E) {
                s = p.src[e]; d = p.dst[e];
                if (d >= node0 && d < node0 + nnodes) {
                    uint32_t sxy = posu[s * 3] | ((uint32_t)posu[s * 3 + 1] << 16), sz = posu[s * 3 + 2];
                    uint32_t dxy = posu[d * 3] | ((uint32_t)posu[d * 3 + 1] << 16), dz = posu[d * 3 + 2];
                    db  = edge_dist(sxy, sz, dxy, dz, rxy, rz);
                    act = db <= D_MAX_BITS;
                }
            }
            unsigned m = __ballot_sync(0xffffffffu, act);
            while (m) {
                int l = __ffs(m) - 1;
                m &= m - 1;
                int es = __shfl_sync(0xffffffffu, s, l), ed = __shfl_sync(0xffffffffu, d, l);
                uint32_t edb = __shfl_sync(0xffffffffu, db, l), exy = __shfl_sync(0xffffffffu, rxy, l), ez = __shfl_sync(0xffffffffu, rz, l);
                float inv = 1.0f / __uint_as_float(edb << 16);
                float rh[3] = {rbf(bf_lo(exy) * inv), rbf(bf_hi(exy) * inv), rbf(bf_lo(ez) * inv)};
                const uint32_t* fr = Fw + (size_t)es * 128 + lane;
                const uint32_t fh = __ldcg(fr);
                const uint32_t q[3] = {__ldcg(fr + 32), __ldcg(fr + 64), __ldcg(fr + 96)};
                float ps0 = 0.f, ps1 = 0.f, pr0 = 0.f, pr1 = 0.f;
                for (int j2 = 0; j2 < 32; j2++) {
                    uint32_t hj = __shfl_sync(0xffffffffu, fh, j2);
                    uint32_t a0 = *(const uint32_t*)(p.w2 + (2 * j2) * 192 + 2 * lane), a1 = *(const uint32_t*)(p.w2 + (2 * j2 + 1) * 192 + 2 * lane);
                    uint32_t b0 = *(const uint32_t*)(p.w2 + (2 * j2) * 192 + 128 + 2 * lane), b1 = *(const uint32_t*)(p.w2 + (2 * j2 + 1) * 192 + 128 + 2 * lane);
                    ps0 += bf_lo(hj) * bf_lo(a0) + bf_hi(hj) * bf_lo(a1);
                    ps1 += bf_lo(hj) * bf_hi(a0) + bf_hi(hj) * bf_hi(a1);
                    pr0 += bf_lo(hj) * bf_lo(b0) + bf_hi(hj) * bf_lo(b1);
                    pr1 += bf_lo(hj) * bf_hi(b0) + bf_hi(hj) * bf_hi(b1);
                }
                float ws0 = 0.f, ws1 = 0.f, wv0 = 0.f, wv1 = 0.f, wr0 = 0.f, wr1 = 0.f;
                for (int k2 = 0; k2 < 8; k2++) {
                    uint32_t rk2 = __ldcg(tabg + (edb - D_MIN_BITS) * 8 + k2);
#pragma unroll
                    for (int h = 0; h < 2; h++) {
                        float rv = h ? bf_hi(rk2) : bf_lo(rk2);
                        const __nv_bfloat16* wrow = p.wr + (2 * k2 + h) * 192 + 2 * lane;
                        uint32_t a = *(const uint32_t*)wrow, b = *(const uint32_t*)(wrow + 64), c = *(const uint32_t*)(wrow + 128);
                        ws0 += rv * bf_lo(a); ws1 += rv * bf_hi(a);
                        wv0 += rv * bf_lo(b); wv1 += rv * bf_hi(b);
                        wr0 += rv * bf_lo(c); wr1 += rv * bf_hi(c);
                    }
                }
                float* a = acc + (ed - node0) * 256 + 2 * lane;
                atomicAdd(a, ps0 * ws0); atomicAdd(a + 1, ps1 * ws1);
#pragma unroll
                for (int c = 0; c < 3; c++) {
                    atomicAdd(a + 64 * (c + 1), wv0 * bf_lo(q[c]) + pr0 * wr0 * rh[c]);
                    atomicAdd(a + 64 * (c + 1) + 1, wv1 * bf_hi(q[c]) + pr1 * wr1 * rh[c]);
                }
            }
        }
        __syncthreads();
        for (int i = tid; i < nnodes * 128; i += NT) {
            uint32_t r = *(const uint32_t*)(p.sv + (size_t)node0 * 256 + 2 * i);
            *(uint32_t*)(p.out + (size_t)node0 * 256 + 2 * i) = pack_bf(bf_lo(r) + acc[2 * i], bf_hi(r) + acc[2 * i + 1]);
        }
        return;
    }

    const int slots = ctrl[4];
    const int nstage = slots <= SLOT_CAP4 ? 4 : 3;
    const uint32_t ring = sb + (nstage == 4 ? SM_RING4 : SM_RING3);
    if (warp >= 4 * NCWG) {
        asm volatile("setmaxnreg.dec.sync.aligned.u32 56;");
        const int wg = warp - 4 * NCWG;
        if (wg < NCWG) {
            const int nb = wg == 0 ? 0 : ctrl[1 + wg], ne = wg == NCWG - 1 ? nnodes : ctrl[2 + wg];
            const int g0 = (nb < nnodes ? (int)(nInfo[nb] & 0xffffu) : slots) >> 4;
            const int g1 = (ne < nnodes ? (int)(nInfo[ne] & 0xffffu) : slots) >> 4;
            const int e = lane >> 1, half = lane & 1;
            const uint32_t coef_off = e * 128 + ((half ^ (e & 7)) << 4);
            int stage = 0, phase = 1;
            uint2 m = make_uint2(0u, 0u);
            uint4 tv = make_uint4(0u, 0u, 0u, 0u);
            if (g0 < g1) {
                m  = lds64(sb + SM_META + (g0 * 16 + e) * 8);
                tv = __ldg((const uint4*)((const uint8_t*)g_table + (m.x & 0xffffu) + half * 16));
            }
            for (int gi = g0; gi < g1; gi++) {
                const uint32_t st = ring + (wg * nstage + stage) * STAGE_B;
                const uint32_t fb = bar_full + (wg * MAX_STAGE + stage) * 8;
                const uint2 mc = m;
                const uint4 tc = tv;
                if (gi + 1 < g1) {
                    m  = lds64(sb + SM_META + ((gi + 1) * 16 + e) * 8);
                    tv = __ldg((const uint4*)((const uint8_t*)g_table + (m.x & 0xffffu) + half * 16));
                }
                mbar_wait(bar_empty + (wg * MAX_STAGE + stage) * 8, phase);
                const uint32_t mx = __byte_perm(mc.y, 0, 0x1010), my = __byte_perm(mc.y, 0, 0x3232), mz = __byte_perm(mc.x, 0, 0x3232);
                const uint32_t a = st + coef_off;
                sts128(a, tc);
                sts128(a ^ 0x20, make_uint4(hmul2(tc.x, mx), hmul2(tc.y, mx), hmul2(tc.z, mx), hmul2(tc.w, mx)));
                sts128(a ^ 0x40, make_uint4(hmul2(tc.x, my), hmul2(tc.y, my), hmul2(tc.z, my), hmul2(tc.w, my)));
                sts128(a ^ 0x60, make_uint4(hmul2(tc.x, mz), hmul2(tc.y, mz), hmul2(tc.z, mz), hmul2(tc.w, mz)));
                fence_async_smem();
                __syncwarp();
                if (lane == 0) mbar_arrive(fb);
                if (++stage == nstage) { stage = 0; phase ^= 1; }
            }
        }
    } else {
        asm volatile("setmaxnreg.inc.sync.aligned.u32 152;");
        const int wg = warp >> 2, w = warp & 3;
        const int n_begin = wg == 0 ? 0 : ctrl[1 + wg], n_end = wg == NCWG - 1 ? nnodes : ctrl[2 + wg];
        uint32_t wA[2][4][4];
        uint32_t wp[3][4];
        {
            const uint16_t* w2 = (const uint16_t*)p.w2 + 16 * w + g;
#pragma unroll
            for (int m = 0; m < 2; m++) {
#pragma unroll
                for (int ks = 0; ks < 4; ks++) {
#pragma unroll
                    for (int i = 0; i < 4; i++) {
                        const uint16_t* q = w2 + (16 * ks + 2 * t + 8 * (i >> 1)) * 192 + m * 128 + 8 * (i & 1);
                        wA[m][ks][i] = (uint32_t)__ldg(q) | ((uint32_t)__ldg(q + 192) << 16);
                    }
                }
            }
            const uint16_t* wr = (const uint16_t*)p.wr + 16 * w + g;
#pragma unroll
            for (int ty = 0; ty < 3; ty++) {
#pragma unroll
                for (int i = 0; i < 4; i++) {
                    const uint16_t* q = wr + (8 * (i >> 1) + 2 * t) * 192 + ty * 64 + 8 * (i & 1);
                    wp[ty][i] = (uint32_t)__ldg(q) | ((uint32_t)__ldg(q + 192) << 16);
                }
            }
        }
        uint32_t aoff[4];
        {
            const int e = (lane & 7) + 8 * (lane >> 4), ch = 2 * w + ((lane >> 3) & 1);
#pragma unroll
            for (int b = 0; b < 4; b++) aoff[b] = 2048 + e * 640 + b * 128 + ((ch ^ ((5 * e + b) & 7)) << 4);
        }
        const uint32_t ht = sb + SM_HT + wg * 8192;
        const uint32_t stsm_a = ht + (16 * w + (lane & 15)) * 128 + (((lane >> 4) ^ (lane & 7)) << 4);
        const uint32_t dht = desc_lo(ht);
        const uint32_t out_lane = (uint32_t)node0 * 512u + t * 128 + (16 * w + (g & 1) * 8 + (g & 6)) * 2;
        const uint32_t ring_wg = ring + wg * nstage * STAGE_B;
        const uint32_t full_wg = bar_full + wg * MAX_STAGE * 8, empty_wg = bar_empty + wg * MAX_STAGE * 8;
        float ys[8], yv[24], dQ[3][8];
#pragma unroll
        for (int i = 0; i < 24; i++) yv[i] = 0.f;
#pragma unroll
        for (int i = 0; i < 8; i++) { ys[i] = 0.f; dQ[0][i] = 0.f; dQ[1][i] = 0.f; dQ[2][i] = 0.f; }

        int left, gnext, gend;
        {
            const int s0 = n_begin < nnodes ? (int)(nInfo[n_begin] & 0xffffu) : slots;
            const int s1 = n_end < nnodes ? (int)(nInfo[n_end] & 0xffffu) : slots;
            gnext = __shfl_sync(0xffffffffu, s0 >> 4, 0);
            gend  = __shfl_sync(0xffffffffu, s1 >> 4, 0);
            left  = gend - gnext;
        }
        auto refill = [&](int fs) {
            uint32_t leader;
            asm volatile("{\n.reg .pred p;\nelect.sync _|p, 0xffffffff;\nselp.u32 %0, 1, 0, p;\n}" : "=r"(leader));
            if (leader) {
                const uint2 id = lds64(sb + SM_SID + gnext * 32 + w * 8);
                const uint32_t dst = ring_wg + fs * STAGE_B + 2048 + w * 4 * 640, fb = full_wg + fs * 8;
                mbar_expect_tx(fb, 4 * 512);
                tma_load(dst, &tmF, (int)(id.x & 0xffffu) * 4, fb);
                tma_load(dst + 640, &tmF, (int)(id.x >> 16) * 4, fb);
                tma_load(dst + 1280, &tmF, (int)(id.y & 0xffffu) * 4, fb);
                tma_load(dst + 1920, &tmF, (int)(id.y >> 16) * 4, fb);
            }
            __syncwarp();
            gnext++;
        };
        for (int i = 0; i < nstage && gnext < gend; i++) refill(i);
        uint32_t A0[4][4];
        int cstage = 0, cphase = 0;
        int nl = n_begin, gi = 0, G = 0;
        uint32_t resid = 0;
        auto node_begin = [&]() {
            G = __shfl_sync(0xffffffffu, (int)(nInfo[nl] >> 20), 0);
            resid = __ldg((const uint32_t*)((const uint8_t*)p.sv + (out_lane + (uint32_t)nl * 512u)));
            gi = 0;
        };
        auto epilogue = [&]() {
            named_barrier(1 + wg);
            stsm4(stsm_a, pack_bf(ys[0], ys[1]), pack_bf(ys[2], ys[3]), pack_bf(ys[4], ys[5]), pack_bf(ys[6], ys[7]));
#pragma unroll
            for (int i = 0; i < 6; i += 2) {
                stsm4(stsm_a ^ ((i + 2) << 4),
                      pack_bf(yv[4 * i], yv[4 * i + 1]), pack_bf(yv[4 * i + 2], yv[4 * i + 3]),
                      pack_bf(yv[4 * i + 4], yv[4 * i + 5]), pack_bf(yv[4 * i + 6], yv[4 * i + 7]));
            }
            fence_async_smem();
            named_barrier(1 + wg);
            wg_fence();
#pragma unroll
            for (int ks = 0; ks < 4; ks++) {
                wgmma_n16(ys, wA[0][ks], dht + ks * 128, ks);
                wgmma_n48(yv, wA[1][ks], dht + ks * 128 + 2, ks);
            }
            wg_commit();
#pragma unroll
            for (int i = 0; i < 12; i++) asm volatile("" : "+r"(wp[i >> 2][i & 3]));
            float pr[4][2];
#pragma unroll
            for (int a = 0; a < 3; a++) {
                const float* q = dQ[a];
                pr[a + 1][0] = bf_lo(wp[1][0]) * q[0] + bf_hi(wp[1][0]) * q[1] + bf_lo(wp[1][2]) * q[4] + bf_hi(wp[1][2]) * q[5];
                pr[a + 1][1] = bf_lo(wp[1][1]) * q[2] + bf_hi(wp[1][1]) * q[3] + bf_lo(wp[1][3]) * q[6] + bf_hi(wp[1][3]) * q[7];
            }
            wg_wait0();
            pr[0][0] = bf_lo(wp[0][0]) * ys[0] + bf_hi(wp[0][0]) * ys[1] + bf_lo(wp[0][2]) * ys[4] + bf_hi(wp[0][2]) * ys[5];
            pr[0][1] = bf_lo(wp[0][1]) * ys[2] + bf_hi(wp[0][1]) * ys[3] + bf_lo(wp[0][3]) * ys[6] + bf_hi(wp[0][3]) * ys[7];
#pragma unroll
            for (int a = 0; a < 3; a++) {
                const float* y = yv + 8 * a;
                pr[a + 1][0] += bf_lo(wp[2][0]) * y[0] + bf_hi(wp[2][0]) * y[1] + bf_lo(wp[2][2]) * y[4] + bf_hi(wp[2][2]) * y[5];
                pr[a + 1][1] += bf_lo(wp[2][1]) * y[2] + bf_hi(wp[2][1]) * y[3] + bf_lo(wp[2][3]) * y[6] + bf_hi(wp[2][3]) * y[7];
            }
            const bool hi2 = t & 2, hi1 = t & 1, odd = g & 1;
            float ka0 = hi2 ? pr[2][0] : pr[0][0], ka1 = hi2 ? pr[2][1] : pr[0][1];
            float kb0 = hi2 ? pr[3][0] : pr[1][0], kb1 = hi2 ? pr[3][1] : pr[1][1];
            float sa0 = hi2 ? pr[0][0] : pr[2][0], sa1 = hi2 ? pr[0][1] : pr[2][1];
            float sb0 = hi2 ? pr[1][0] : pr[3][0], sb1 = hi2 ? pr[1][1] : pr[3][1];
            ka0 += __shfl_xor_sync(0xffffffffu, sa0, 2); ka1 += __shfl_xor_sync(0xffffffffu, sa1, 2);
            kb0 += __shfl_xor_sync(0xffffffffu, sb0, 2); kb1 += __shfl_xor_sync(0xffffffffu, sb1, 2);
            float k0 = hi1 ? kb0 : ka0, k1 = hi1 ? kb1 : ka1;
            float s0 = hi1 ? ka0 : kb0, s1 = hi1 ? ka1 : kb1;
            k0 += __shfl_xor_sync(0xffffffffu, s0, 1);
            k1 += __shfl_xor_sync(0xffffffffu, s1, 1);
            const float other = __shfl_xor_sync(0xffffffffu, odd ? k0 : k1, 4);
            const float lo = odd ? other : k0, hi = odd ? k1 : other;
            *(uint32_t*)((uint8_t*)p.out + (out_lane + (uint32_t)nl * 512u)) = pack_bf(bf_lo(resid) + lo, bf_hi(resid) + hi);
        };
        if (left > 0) node_begin();
        int pstage = -1, pphase = 0;
        while (left > 0) {
            const uint32_t st = ring_wg + cstage * STAGE_B;
            mbar_wait(full_wg + cstage * 8, cphase);
#pragma unroll
            for (int b = 0; b < 4; b++) ldsm4t(A0[b], st + aoff[b]);
            const uint32_t bd = desc_lo(st);
            wg_fence();
            wgmma_n64(ys, yv, A0[0], bd, gi);
            wgmma_n16(dQ[0], A0[1], bd, gi);
            wgmma_n16(dQ[1], A0[2], bd, gi);
            wgmma_n16(dQ[2], A0[3], bd, gi);
            wg_commit();
            if (pstage >= 0 && gnext < gend) {
                mbar_wait(empty_wg + pstage * 8, pphase);
                refill(pstage);
            }
            wg_wait0();
            if (lane == 0) mbar_arrive(empty_wg + cstage * 8);
            pstage = cstage;
            pphase = cphase;
            if (++cstage == nstage) { cstage = 0; cphase ^= 1; }
            --left;
            if (++gi == G) {
                epilogue();
                if (++nl < n_end) node_begin();
            }
        }
    }
    STAMP(8);
}

typedef CUresult (*EncodeFn)(CUtensorMap*, CUtensorMapDataType, cuuint32_t, void*, const cuuint64_t*, const cuuint64_t*,
                             const cuuint32_t*, const cuuint32_t*, CUtensorMapInterleave, CUtensorMapSwizzle,
                             CUtensorMapL2promotion, CUtensorMapFloatOOBfill);

void make_map(EncodeFn enc, CUtensorMap* tm, const void* base, uint64_t lines, uint32_t box) {
    cuuint64_t gd[2] = {64, lines};
    cuuint64_t gs[1] = {128};
    cuuint32_t bd[2] = {64, box};
    cuuint32_t es[2] = {1, 1};
    enc(tm, CU_TENSOR_MAP_DATA_TYPE_BFLOAT16, 2, const_cast<void*>(base), gd, gs, bd, es, CU_TENSOR_MAP_INTERLEAVE_NONE,
        CU_TENSOR_MAP_SWIZZLE_128B, CU_TENSOR_MAP_L2_PROMOTION_L2_128B, CU_TENSOR_MAP_FLOAT_OOB_FILL_NONE);
}

}

extern "C" void kernel_launch(void* const* d_in, const int* in_sizes, int n_in, void* d_out, int out_size) {
    (void)n_in; (void)out_size;
    static int n_sm = 0;
    static EncodeFn enc = nullptr;
    static void* f_ptr = nullptr;
    if (n_sm == 0) {
        int dev = 0;
        cudaGetDevice(&dev);
        cudaDeviceGetAttribute(&n_sm, cudaDevAttrMultiProcessorCount, dev);
        cudaFuncSetAttribute(painn_kernel, cudaFuncAttributeMaxDynamicSharedMemorySize, SM_TOTAL);
        void* fn = nullptr;
        cudaDriverEntryPointQueryResult qr;
        cudaGetDriverEntryPoint("cuTensorMapEncodeTiled", &fn, cudaEnableDefault, &qr);
        enc = (EncodeFn)fn;
        cudaGetSymbolAddress(&f_ptr, g_F);
    }
    Params p;
    p.sv    = (const __nv_bfloat16*)d_in[0];
    p.pos   = (const __nv_bfloat16*)d_in[1];
    p.src   = (const int*)d_in[2];
    p.dst   = (const int*)d_in[3];
    p.freqs = (const __nv_bfloat16*)d_in[4];
    p.w1    = (const __nv_bfloat16*)d_in[5];
    p.w2    = (const __nv_bfloat16*)d_in[6];
    p.wr    = (const __nv_bfloat16*)d_in[7];
    p.out   = (__nv_bfloat16*)d_out;
    p.N = in_sizes[1] / 3;
    p.E = in_sizes[2];
    p.ncta = n_sm < MAX_CTA ? n_sm : MAX_CTA;
    p.npc = (p.N + p.ncta - 1) / p.ncta;
    p.npc_magic = (uint32_t)(0x100000000ull / (uint32_t)p.npc) + 1u;
    p.quads_per_cta = ((p.E >> 2) + p.ncta - 1) / p.ncta;
    if (!enc || p.N > MAX_N || p.npc > MAX_NPC || (p.E & 3) || p.quads_per_cta > MAX_ROUNDS * 32) return;

    CUtensorMap tmF, tmSV, tmW1, tmW2;
    make_map(enc, &tmF, f_ptr, (uint64_t)p.N * 4, 4);
    make_map(enc, &tmSV, p.sv, (uint64_t)p.N * 4, 160);
    make_map(enc, &tmW1, p.w1, 64, 64);
    make_map(enc, &tmW2, p.w2, 192, 192);

    cudaLaunchConfig_t cfg = {};
    cfg.gridDim = dim3(p.ncta);
    cfg.blockDim = dim3(NT);
    cfg.dynamicSmemBytes = SM_TOTAL;
    cfg.stream = cudaStreamPerThread;
    cudaLaunchAttribute attr[1];
    attr[0].id = cudaLaunchAttributeCooperative;
    attr[0].val.cooperative = 1;
    cfg.attrs = attr;
    cfg.numAttrs = 1;
    cudaLaunchKernelEx(&cfg, painn_kernel, p, tmF, tmSV, tmW1, tmW2);
}
```

```cpp
#include <cuda_runtime.h>
#include <cuda.h>
#include <cuda_bf16.h>
#include <stdint.h>

namespace {

constexpr int NT        = 512;
constexpr int NCWG      = 3;
constexpr int MAX_N     = 10240;
constexpr int MAX_CTA   = 144;
constexpr int MAX_NPC   = 80;
constexpr int MAX_ROUNDS = 38;
constexpr int REC_CAP   = MAX_ROUNDS * 128;
constexpr int SLOT_CAP  = 6144;
constexpr int MAX_STAGE = 4;
constexpr int STAGE_B   = 12288;

constexpr uint32_t D_MIN_BITS = 0x38D2;
constexpr uint32_t D_MAX_BITS = 0x409C;
constexpr int TAB_ROWS  = (int)(D_MAX_BITS - D_MIN_BITS) + 1;
constexpr int TAB_ZERO  = TAB_ROWS;
constexpr int TAB_BYTES = (TAB_ROWS + 1) * 32;

constexpr int SM_BINCNT = 0;
constexpr int SM_BINOFF = SM_BINCNT + MAX_CTA * 4;
constexpr int SM_NCNT   = SM_BINOFF + MAX_CTA * 4;
constexpr int SM_NINFO  = SM_NCNT + MAX_NPC * 4;
constexpr int SM_CTRL   = SM_NINFO + MAX_NPC * 4;
constexpr int SM_BARS   = SM_CTRL + 64;
constexpr int SM_WP     = 2048 + 128;
constexpr int SM_SID    = SM_WP + 6144;
constexpr int SM_META   = SM_SID + SLOT_CAP * 2;
constexpr int SM_TOTAL  = 232448;
constexpr int SM_HT     = (SM_TOTAL - NCWG * 8192) / 1024 * 1024;
constexpr int SM_RING4  = SM_HT - NCWG * 4 * STAGE_B;
constexpr int SM_RING3  = SM_HT - NCWG * 3 * STAGE_B;
constexpr int SLOT_CAP4 = (SM_RING4 - SM_META) / 8;
constexpr int SM_STAGE2 = SM_RING3 - 0;
constexpr int STAGE_CAP = (SM_TOTAL - SM_RING3) / 16;
constexpr int P1_POS    = 3072;
constexpr int P1_STAGE  = P1_POS + 61440;
constexpr int P1_SV     = (P1_STAGE + REC_CAP * 16 + 1023) / 1024 * 1024;
constexpr int P1_W1     = P1_SV + MAX_NPC * 512;
constexpr int P1_W2     = P1_W1 + 8192;
constexpr int P1_END    = P1_W2 + 24576;
static_assert(SM_BARS + (4 + 2 * NCWG * MAX_STAGE) * 8 <= SM_WP, "misc block");
static_assert(SM_BARS + 256 <= P1_POS, "misc block");
static_assert(P1_END <= SM_TOTAL, "phase 1 overlay");
static_assert(SM_META + SLOT_CAP * 8 <= SM_RING3, "CSR");
static_assert(SM_RING4 % 1024 == 0 && SM_RING3 % 1024 == 0 && SM_HT % 1024 == 0, "alignment");
static_assert(SM_BARS % 8 == 0 && SM_META % 8 == 0, "alignment");
static_assert(MAX_N * 6 <= 61440, "pos");
static_assert(SM_SID + MAX_NPC * 1024 <= SM_TOTAL, "slow path accumulators");

__device__ __align__(1024) uint4 g_F[MAX_N * 32];
__device__ uint4    g_rec[MAX_CTA * REC_CAP];
__device__ uint32_t g_offs[MAX_CTA * MAX_CTA];
__device__ uint4    g_table[(TAB_BYTES + 15) / 16];
__device__ unsigned g_bar;
#define STAMP(k)
#define ITS(k)

struct Params {
    const __nv_bfloat16* sv;
    const __nv_bfloat16* pos;
    const int*           src;
    const int*           dst;
    const __nv_bfloat16* freqs;
    const __nv_bfloat16* w1;
    const __nv_bfloat16* w2;
    const __nv_bfloat16* wr;
    __nv_bfloat16*       out;
    int N, E, ncta, npc;
    uint32_t npc_magic;
    int quads_per_cta;
};

__device__ __forceinline__ uint32_t smem_u32(const void* p) { return (uint32_t)__cvta_generic_to_shared(p); }
__device__ __forceinline__ float bf_lo(uint32_t v) { return __uint_as_float(v << 16); }
__device__ __forceinline__ float bf_hi(uint32_t v) { return __uint_as_float(v & 0xffff0000u); }
__device__ __forceinline__ float bf_u16(uint16_t v) { return __uint_as_float((uint32_t)v << 16); }
__device__ __forceinline__ uint32_t pack_bf(float lo, float hi) {
    uint32_t r;
    asm("cvt.rn.bf16x2.f32 %0, %1, %2;" : "=r"(r) : "f"(hi), "f"(lo));
    return r;
}
__device__ __forceinline__ float rbf(float x) { return bf_lo(pack_bf(x, 0.f)); }
__device__ __forceinline__ uint32_t hmul2(uint32_t a, uint32_t b) {
    uint32_t r;
    asm("mul.rn.bf16x2 %0, %1, %2;" : "=r"(r) : "r"(a), "r"(b));
    return r;
}
__device__ __forceinline__ uint32_t hsub2(uint32_t a, uint32_t b) {
    uint32_t r;
    asm("sub.rn.bf16x2 %0, %1, %2;" : "=r"(r) : "r"(a), "r"(b));
    return r;
}
__device__ __forceinline__ uint32_t lds32(uint32_t a) { uint32_t v; asm volatile("ld.shared.u32 %0, [%1];" : "=r"(v) : "r"(a)); return v; }
__device__ __forceinline__ uint32_t lds16(uint32_t a) { uint16_t v; asm volatile("ld.shared.u16 %0, [%1];" : "=h"(v) : "r"(a)); return v; }
__device__ __forceinline__ uint2 lds64(uint32_t a) { uint2 v; asm volatile("ld.shared.v2.u32 {%0,%1}, [%2];" : "=r"(v.x), "=r"(v.y) : "r"(a)); return v; }
__device__ __forceinline__ uint4 lds128(uint32_t a) { uint4 v; asm volatile("ld.shared.v4.u32 {%0,%1,%2,%3}, [%4];" : "=r"(v.x), "=r"(v.y), "=r"(v.z), "=r"(v.w) : "r"(a)); return v; }
__device__ __forceinline__ void sts32(uint32_t a, uint32_t v) { asm volatile("st.shared.u32 [%0], %1;" ::"r"(a), "r"(v) : "memory"); }
__device__ __forceinline__ void sts128(uint32_t a, uint4 v) { asm volatile("st.shared.v4.u32 [%0], {%1,%2,%3,%4};" ::"r"(a), "r"(v.x), "r"(v.y), "r"(v.z), "r"(v.w) : "memory"); }
__device__ __forceinline__ void mbar_init(uint32_t bar, int cnt) { asm volatile("mbarrier.init.shared::cta.b64 [%0], %1;" ::"r"(bar), "r"(cnt) : "memory"); }
__device__ __forceinline__ void mbar_expect_tx(uint32_t bar, uint32_t bytes) { asm volatile("mbarrier.arrive.expect_tx.shared::cta.b64 _, [%0], %1;" ::"r"(bar), "r"(bytes) : "memory"); }
__device__ __forceinline__ void mbar_arrive(uint32_t bar) { asm volatile("mbarrier.arrive.shared::cta.b64 _, [%0];" ::"r"(bar) : "memory"); }
__device__ __forceinline__ void mbar_wait(uint32_t bar, uint32_t parity) {
    uint32_t done;
    int spins = 0;
    do {
        asm volatile("{\n.reg .pred p;\nmbarrier.try_wait.parity.shared::cta.b64 p, [%1], %2;\nselp.u32 %0, 1, 0, p;\n}"
                     : "=r"(done) : "r"(bar), "r"(parity) : "memory");
    } while (!done && ++spins < (1 << 22));
}
__device__ __forceinline__ void bulk_g2s(uint32_t dst, const void* src, uint32_t bytes, uint32_t bar) {
    asm volatile("cp.async.bulk.shared::cluster.global.mbarrier::complete_tx::bytes [%0], [%1], %2, [%3];"
                 ::"r"(dst), "l"(src), "r"(bytes), "r"(bar) : "memory");
}
__device__ __forceinline__ void tma_load(uint32_t dst, const CUtensorMap* tm, int line, uint32_t bar) {
    asm volatile("cp.async.bulk.tensor.2d.shared::cluster.global.mbarrier::complete_tx::bytes [%0], [%1, {%3, %4}], [%2];"
                 ::"r"(dst), "l"(tm), "r"(bar), "r"(0), "r"(line) : "memory");
}
__device__ __forceinline__ void tma_store(const CUtensorMap* tm, int line, uint32_t src) {
    asm volatile("cp.async.bulk.tensor.2d.global.shared::cta.bulk_group [%0, {%2, %3}], [%1];"
                 ::"l"(tm), "r"(src), "r"(0), "r"(line) : "memory");
}
__device__ __forceinline__ void fence_async_smem() { asm volatile("fence.proxy.async.shared::cta;" ::: "memory"); }
__device__ __forceinline__ void named_barrier(int id) { asm volatile("bar.sync %0, 128;" ::"r"(id) : "memory"); }
__device__ __forceinline__ void ldsm4(uint32_t (&r)[4], uint32_t a) {
    asm volatile("ldmatrix.sync.aligned.m8n8.x4.shared.b16 {%0,%1,%2,%3}, [%4];" : "=r"(r[0]), "=r"(r[1]), "=r"(r[2]), "=r"(r[3]) : "r"(a) : "memory");
}
__device__ __forceinline__ void ldsm4t(uint32_t (&r)[4], uint32_t a) {
    asm volatile("ldmatrix.sync.aligned.m8n8.x4.trans.shared.b16 {%0,%1,%2,%3}, [%4];" : "=r"(r[0]), "=r"(r[1]), "=r"(r[2]), "=r"(r[3]) : "r"(a) : "memory");
}
__device__ __forceinline__ void stsm4(uint32_t a, uint32_t r0, uint32_t r1, uint32_t r2, uint32_t r3) {
    asm volatile("stmatrix.sync.aligned.m8n8.x4.shared.b16 [%0], {%1,%2,%3,%4};" ::"r"(a), "r"(r0), "r"(r1), "r"(r2), "r"(r3) : "memory");
}
__device__ __forceinline__ void mma16816(float (&c)[4], const uint32_t (&a)[4], uint32_t b0, uint32_t b1) {
    asm volatile("mma.sync.aligned.m16n8k16.row.col.f32.bf16.bf16.f32 {%0,%1,%2,%3}, {%4,%5,%6,%7}, {%8,%9}, {%0,%1,%2,%3};"
                 : "+f"(c[0]), "+f"(c[1]), "+f"(c[2]), "+f"(c[3])
                 : "r"(a[0]), "r"(a[1]), "r"(a[2]), "r"(a[3]), "r"(b0), "r"(b1));
}

__device__ __forceinline__ uint32_t desc_lo(uint32_t saddr) { return ((saddr & 0x3FFFF) >> 4) | (1u << 16); }
#define DESC_HI "0x40000040"
__device__ __forceinline__ void wg_fence() { asm volatile("wgmma.fence.sync.aligned;" ::: "memory"); }
__device__ __forceinline__ void wg_commit() { asm volatile("wgmma.commit_group.sync.aligned;" ::: "memory"); }
__device__ __forceinline__ void wg_wait0() { asm volatile("wgmma.wait_group.sync.aligned 0;" ::: "memory"); }

__device__ __forceinline__ void wgmma_n64_first(float (&d)[8], float (&e)[24], const uint32_t (&a)[4], uint32_t bdesc) {
    asm volatile("{\n.reg .b64 b;\nmov.b64 b, {%36, " DESC_HI "};\n"
                 "wgmma.mma_async.sync.aligned.m64n64k16.f32.bf16.bf16 {%0,%1,%2,%3,%4,%5,%6,%7,%8,%9,%10,%11,%12,%13,%14,%15,%16,%17,%18,%19,%20,%21,%22,%23,%24,%25,%26,%27,%28,%29,%30,%31}, {%32,%33,%34,%35}, b, 0, 1, 1, 1;\n}"
                 : "=f"(d[0]), "=f"(d[1]), "=f"(d[2]), "=f"(d[3]), "=f"(d[4]), "=f"(d[5]), "=f"(d[6]), "=f"(d[7]),
                   "=f"(e[0]), "=f"(e[1]), "=f"(e[2]), "=f"(e[3]), "=f"(e[4]), "=f"(e[5]), "=f"(e[6]), "=f"(e[7]), "=f"(e[8]), "=f"(e[9]), "=f"(e[10]), "=f"(e[11]), "=f"(e[12]), "=f"(e[13]), "=f"(e[14]), "=f"(e[15]), "=f"(e[16]), "=f"(e[17]), "=f"(e[18]), "=f"(e[19]), "=f"(e[20]), "=f"(e[21]), "=f"(e[22]), "=f"(e[23])
                 : "r"(a[0]), "r"(a[1]), "r"(a[2]), "r"(a[3]), "r"(bdesc));
}
__device__ __forceinline__ void wgmma_n64(float (&d)[8], float (&e)[24], const uint32_t (&a)[4], uint32_t bdesc) {
    asm volatile("{\n.reg .b64 b;\nmov.b64 b, {%36, " DESC_HI "};\n"
                 "wgmma.mma_async.sync.aligned.m64n64k16.f32.bf16.bf16 {%0,%1,%2,%3,%4,%5,%6,%7,%8,%9,%10,%11,%12,%13,%14,%15,%16,%17,%18,%19,%20,%21,%22,%23,%24,%25,%26,%27,%28,%29,%30,%31}, {%32,%33,%34,%35}, b, 1, 1, 1, 1;\n}"
                 : "+f"(d[0]), "+f"(d[1]), "+f"(d[2]), "+f"(d[3]), "+f"(d[4]), "+f"(d[5]), "+f"(d[6]), "+f"(d[7]),
                   "+f"(e[0]), "+f"(e[1]), "+f"(e[2]), "+f"(e[3]), "+f"(e[4]), "+f"(e[5]), "+f"(e[6]), "+f"(e[7]), "+f"(e[8]), "+f"(e[9]), "+f"(e[10]), "+f"(e[11]), "+f"(e[12]), "+f"(e[13]), "+f"(e[14]), "+f"(e[15]), "+f"(e[16]), "+f"(e[17]), "+f"(e[18]), "+f"(e[19]), "+f"(e[20]), "+f"(e[21]), "+f"(e[22]), "+f"(e[23])
                 : "r"(a[0]), "r"(a[1]), "r"(a[2]), "r"(a[3]), "r"(bdesc));
}
__device__ __forceinline__ void wgmma_n48_first(float (&e)[24], const uint32_t (&a)[4], uint32_t bdesc) {
    asm volatile("{\n.reg .b64 b;\nmov.b64 b, {%28, " DESC_HI "};\n"
                 "wgmma.mma_async.sync.aligned.m64n48k16.f32.bf16.bf16 {%0,%1,%2,%3,%4,%5,%6,%7,%8,%9,%10,%11,%12,%13,%14,%15,%16,%17,%18,%19,%20,%21,%22,%23}, {%24,%25,%26,%27}, b, 0, 1, 1, 1;\n}"
                 : "=f"(e[0]), "=f"(e[1]), "=f"(e[2]), "=f"(e[3]), "=f"(e[4]), "=f"(e[5]), "=f"(e[6]), "=f"(e[7]), "=f"(e[8]), "=f"(e[9]), "=f"(e[10]), "=f"(e[11]), "=f"(e[12]), "=f"(e[13]), "=f"(e[14]), "=f"(e[15]), "=f"(e[16]), "=f"(e[17]), "=f"(e[18]), "=f"(e[19]), "=f"(e[20]), "=f"(e[21]), "=f"(e[22]), "=f"(e[23])
                 : "r"(a[0]), "r"(a[1]), "r"(a[2]), "r"(a[3]), "r"(bdesc));
}
__device__ __forceinline__ void wgmma_n48(float (&e)[24], const uint32_t (&a)[4], uint32_t bdesc) {
    asm volatile("{\n.reg .b64 b;\nmov.b64 b, {%28, " DESC_HI "};\n"
                 "wgmma.mma_async.sync.aligned.m64n48k16.f32.bf16.bf16 {%0,%1,%2,%3,%4,%5,%6,%7,%8,%9,%10,%11,%12,%13,%14,%15,%16,%17,%18,%19,%20,%21,%22,%23}, {%24,%25,%26,%27}, b, 1, 1, 1, 1;\n}"
                 : "+f"(e[0]), "+f"(e[1]), "+f"(e[2]), "+f"(e[3]), "+f"(e[4]), "+f"(e[5]), "+f"(e[6]), "+f"(e[7]), "+f"(e[8]), "+f"(e[9]), "+f"(e[10]), "+f"(e[11]), "+f"(e[12]), "+f"(e[13]), "+f"(e[14]), "+f"(e[15]), "+f"(e[16]), "+f"(e[17]), "+f"(e[18]), "+f"(e[19]), "+f"(e[20]), "+f"(e[21]), "+f"(e[22]), "+f"(e[23])
                 : "r"(a[0]), "r"(a[1]), "r"(a[2]), "r"(a[3]), "r"(bdesc));
}
__device__ __forceinline__ void wgmma_n16_first(float (&d)[8], const uint32_t (&a)[4], uint32_t bdesc) {
    asm volatile("{\n.reg .b64 b;\nmov.b64 b, {%12, " DESC_HI "};\n"
                 "wgmma.mma_async.sync.aligned.m64n16k16.f32.bf16.bf16 {%0,%1,%2,%3,%4,%5,%6,%7}, {%8,%9,%10,%11}, b, 0, 1, 1, 1;\n}"
                 : "=f"(d[0]), "=f"(d[1]), "=f"(d[2]), "=f"(d[3]), "=f"(d[4]), "=f"(d[5]), "=f"(d[6]), "=f"(d[7])
                 : "r"(a[0]), "r"(a[1]), "r"(a[2]), "r"(a[3]), "r"(bdesc));
}
__device__ __forceinline__ void wgmma_n16(float (&d)[8], const uint32_t (&a)[4], uint32_t bdesc) {
    asm volatile("{\n.reg .b64 b;\nmov.b64 b, {%12, " DESC_HI "};\n"
                 "wgmma.mma_async.sync.aligned.m64n16k16.f32.bf16.bf16 {%0,%1,%2,%3,%4,%5,%6,%7}, {%8,%9,%10,%11}, b, 1, 1, 1, 1;\n}"
                 : "+f"(d[0]), "+f"(d[1]), "+f"(d[2]), "+f"(d[3]), "+f"(d[4]), "+f"(d[5]), "+f"(d[6]), "+f"(d[7])
                 : "r"(a[0]), "r"(a[1]), "r"(a[2]), "r"(a[3]), "r"(bdesc));
}

__device__ __forceinline__ uint32_t edge_dist(uint32_t sxy, uint32_t sz, uint32_t dxy, uint32_t dz, uint32_t& rxy, uint32_t& rz) {
    rxy = hsub2(sxy, dxy);
    rz  = hsub2(sz, dz);
    uint32_t qxy = hmul2(rxy, rxy), qz = hmul2(rz, rz);
    float ss = rbf((bf_lo(qxy) + bf_hi(qxy)) + bf_lo(qz));
    float s2 = rbf(ss + 1e-8f);
    float d;
    asm("sqrt.approx.ftz.f32 %0, %1;" : "=f"(d) : "f"(s2));
    return pack_bf(d, 0.f) & 0xffffu;
}

__device__ __forceinline__ void load_pos(uint32_t sm_pos, int i, uint32_t& xy, uint32_t& z) {
    uint32_t a  = (sm_pos + 6u * (uint32_t)i) & ~3u;
    uint32_t w0 = lds32(a), w1 = lds32(a + 4);
    uint32_t sh = (uint32_t)i << 4;
    xy = __funnelshift_r(w0, w1, sh);
    z  = __funnelshift_r(w1, w1, sh);
}

__device__ __noinline__ float radial_value(float d, float f) {
    float arg = rbf(d * f);
    float sn  = rbf(sinf(arg));
    float rb  = rbf(__fdiv_rn(sn, d));
    float c   = rbf(cosf(rbf(__fdiv_rn(rbf(d * 3.14159265358979323846f), 5.0f))));
    float fc  = rbf(0.5f * rbf(c + 1.0f));
    return rb * fc;
}

__global__ void __launch_bounds__(NT, 1)
painn_kernel(const Params p, const __grid_constant__ CUtensorMap tmF, const __grid_constant__ CUtensorMap tmSV,
             const __grid_constant__ CUtensorMap tmW1, const __grid_constant__ CUtensorMap tmW2) {
    extern __shared__ __align__(1024) uint8_t smem[];
    const uint32_t sb   = smem_u32(smem);
    const int tid  = threadIdx.x, lane = tid & 31, warp = __shfl_sync(0xffffffffu, tid >> 5, 0);
    const int cta  = blockIdx.x;
    const int g    = lane >> 2, t = lane & 3;
    int* binCnt = (int*)(smem + SM_BINCNT);
    int* binOff = (int*)(smem + SM_BINOFF);
    int* nCnt   = (int*)(smem + SM_NCNT);
    uint32_t* nInfo = (uint32_t*)(smem + SM_NINFO);
    volatile int* ctrl = (volatile int*)(smem + SM_CTRL);
    const uint32_t bar_pos = sb + SM_BARS, bar_mlp = bar_pos + 8, bar_rec = bar_pos + 16;
    const uint32_t bar_full = bar_pos + 32, bar_empty = bar_full + NCWG * MAX_STAGE * 8;

    const int node0  = cta * p.npc;
    const int nnodes = max(0, min(p.npc, p.N - node0));

    STAMP(0);
    if (tid == 0) {
        mbar_init(bar_pos, 1);
        mbar_init(bar_mlp, 1);
        mbar_init(bar_rec, 1);
        for (int i = 0; i < NCWG * MAX_STAGE; i++) { mbar_init(bar_full + 8 * i, 1); mbar_init(bar_empty + 8 * i, 4); }
        asm volatile("fence.mbarrier_init.release.cluster;" ::: "memory");
        uint32_t pos_bytes = (uint32_t)(p.N * 6 + 15) & ~15u;
        mbar_expect_tx(bar_pos, pos_bytes);
        bulk_g2s(sb + P1_POS, p.pos, pos_bytes, bar_pos);
        mbar_expect_tx(bar_mlp, 2u * 160u * 128u + 8192u + 24576u);
        tma_load(sb + P1_SV, &tmSV, node0 * 4, bar_mlp);
        tma_load(sb + P1_SV + 160 * 128, &tmSV, node0 * 4 + 160, bar_mlp);
        tma_load(sb + P1_W1, &tmW1, 0, bar_mlp);
        tma_load(sb + P1_W2, &tmW2, 0, bar_mlp);
    }
    const bool mlp_warp = warp >= 11;
    int4 s4[3], d4[3];
    const int q0 = cta * p.quads_per_cta;
    const int qend = min(q0 + p.quads_per_cta, p.E >> 2);
    if (!mlp_warp) {
#pragma unroll
        for (int k = 0; k < 3; k++) {
            int q = q0 + (warp + 11 * k) * 32 + lane;
            bool ok = q < qend;
            s4[k] = ok ? __ldg((const int4*)p.src + q) : make_int4(-1, -1, -1, -1);
            d4[k] = ok ? __ldg((const int4*)p.dst + q) : make_int4(0, 0, 0, 0);
        }
    } else {
        int q = q0 + (33 + warp - 11) * 32 + lane;
        if (q < qend && (lane & 7) == 0) {
            asm volatile("prefetch.global.L2 [%0];" ::"l"((const int4*)p.src + q));
            asm volatile("prefetch.global.L2 [%0];" ::"l"((const int4*)p.dst + q));
        }
    }
    if (tid < MAX_CTA) binCnt[tid] = 0;
    if (tid < MAX_NPC) nCnt[tid] = 0;
    if (tid < 16) ctrl[tid] = 0;
    if (tid >= 416 && tid < 416 + 48) {
        asm volatile("prefetch.global.L2 [%0];" ::"l"((const uint8_t*)p.wr + (tid - 416) * 128));
    }
    __syncthreads();

    if (mlp_warp) {
        const int rows_per = (TAB_ROWS + 1 + p.ncta - 1) / p.ncta;
        for (int i = tid - 11 * 32; i < rows_per * 8; i += 5 * 32) {
            int row = cta * rows_per + (i >> 3), kp = i & 7;
            if (row <= TAB_ROWS) {
                uint32_t val = 0;
                if (row < TAB_ROWS) {
                    float d = __uint_as_float((D_MIN_BITS + row) << 16);
                    uint32_t f2 = __ldg((const uint32_t*)p.freqs + kp);
                    val = pack_bf(radial_value(d, bf_lo(f2)), radial_value(d, bf_hi(f2)));
                }
                ((uint32_t*)g_table)[row * 8 + kp] = val;
            }
        }
        const int mt = warp - 11;
        if (mt * 16 < nnodes) {
            mbar_wait(bar_mlp, 0);
            float acc[8][4];
#pragma unroll
            for (int i = 0; i < 8; i++) { acc[i][0] = acc[i][1] = acc[i][2] = acc[i][3] = 0.f; }
            const int lrow = (lane & 7) + ((lane >> 3) & 1) * 8, lch = lane >> 4;
#pragma unroll
            for (int ks = 0; ks < 4; ks++) {
                uint32_t a[4];
                const int line = 4 * (mt * 16 + lrow);
                ldsm4(a, sb + P1_SV + line * 128 + (((2 * ks + lch) ^ (line & 7)) << 4));
                const int kk = 16 * ks + lrow;
#pragma unroll
                for (int nt = 0; nt < 8; nt += 2) {
                    uint32_t b[4];
                    ldsm4t(b, sb + P1_W1 + kk * 128 + (((nt + lch) ^ (kk & 7)) << 4));
                    mma16816(acc[nt], a, b[0], b[1]);
                    mma16816(acc[nt + 1], a, b[2], b[3]);
                }
            }
            uint32_t hp[8][2];
#pragma unroll
            for (int i = 0; i < 8; i++) {
                float h[4];
#pragma unroll
                for (int q = 0; q < 4; q++) {
                    float x = rbf(acc[i][q]);
                    h[q] = __fdividef(x, 1.0f + __expf(-x));
                    acc[i][q] = 0.f;
                }
                hp[i][0] = pack_bf(h[0], h[1]);
                hp[i][1] = pack_bf(h[2], h[3]);
            }
#pragma unroll
            for (int ks = 0; ks < 4; ks++) {
                uint32_t a[4] = {hp[2 * ks][0], hp[2 * ks][1], hp[2 * ks + 1][0], hp[2 * ks + 1][1]};
                const int line = 3 * (16 * ks + lrow) + 1;
#pragma unroll
                for (int nt = 0; nt < 8; nt += 2) {
                    uint32_t b[4];
                    ldsm4t(b, sb + P1_W2 + line * 128 + (((nt + lch) ^ (line & 7)) << 4));
                    mma16816(acc[nt], a, b[0], b[1]);
                    mma16816(acc[nt + 1], a, b[2], b[3]);
                }
            }
            uint32_t q[3][8][2];
#pragma unroll
            for (int rh = 0; rh < 2; rh++) {
                const int row = mt * 16 + g + 8 * rh;
#pragma unroll
                for (int i = 0; i < 8; i++) {
                    const uint32_t ph = pack_bf(acc[i][2 * rh], acc[i][2 * rh + 1]);
#pragma unroll
                    for (int a = 0; a < 3; a++) {
                        const int line = 4 * row + 1 + a;
                        q[a][i][rh] = hmul2(ph, lds32(sb + P1_SV + line * 128 + ((i ^ (line & 7)) << 4) + 4 * t));
                    }
                }
            }
            __syncwarp();
            {
                const int row = mt * 16 + (lane & 7) + ((lane >> 3) & 1) * 8;
#pragma unroll
                for (int c = 0; c < 4; c++) {
                    const int line = 4 * row + c;
                    const uint32_t lb = sb + P1_SV + line * 128;
#pragma unroll
                    for (int i = 0; i < 8; i += 2) {
                        const uint32_t a = lb + (((i + lch) ^ (line & 7)) << 4);
                        if (c == 0) stsm4(a, hp[i][0], hp[i][1], hp[i + 1][0], hp[i + 1][1]);
                        else        stsm4(a, q[c - 1][i][0], q[c - 1][i][1], q[c - 1][i + 1][0], q[c - 1][i + 1][1]);
                    }
                }
            }
            fence_async_smem();
            __syncwarp();
            if (lane < 16 && mt * 16 + lane < nnodes) tma_store(&tmF, (node0 + mt * 16 + lane) * 4, sb + P1_SV + (mt * 16 + lane) * 512);
            asm volatile("cp.async.bulk.commit_group;" ::: "memory");
        }
        const int q = q0 + (33 + warp - 11) * 32 + lane;
        const bool ok = q < qend;
        s4[0] = ok ? __ldg((const int4*)p.src + q) : make_int4(-1, -1, -1, -1);
        d4[0] = ok ? __ldg((const int4*)p.dst + q) : make_int4(0, 0, 0, 0);
        s4[1] = s4[2] = make_int4(-1, -1, -1, -1);
        d4[1] = d4[2] = make_int4(0, 0, 0, 0);
    }
    mbar_wait(bar_pos, 0);
    STAMP(1);

    uint32_t r0[12], r1[12], r2[12], rk[12];
#pragma unroll
    for (int k = 0; k < 3; k++) {
        const int ss[4] = {s4[k].x, s4[k].y, s4[k].z, s4[k].w};
        const int dd[4] = {d4[k].x, d4[k].y, d4[k].z, d4[k].w};
#pragma unroll
        for (int j = 0; j < 4; j++) rk[k * 4 + j] = 0xffffffffu;
        if (ss[0] >= 0) {
#pragma unroll
            for (int j = 0; j < 4; j++) {
                const int e = k * 4 + j;
                const int s = ss[j], d = dd[j];
                uint32_t sxy, sz, dxy, dz, rxy, rz;
                load_pos(sb + P1_POS, s, sxy, sz);
                load_pos(sb + P1_POS, d, dxy, dz);
                uint32_t db = edge_dist(sxy, sz, dxy, dz, rxy, rz);
                float inv;
                asm("rcp.approx.ftz.f32 %0, %1;" : "=f"(inv) : "f"(__uint_as_float(db << 16)));
                uint32_t bin = __umulhi((uint32_t)d, p.npc_magic);
                uint32_t dl  = (uint32_t)d - bin * (uint32_t)p.npc;
                r0[e] = (uint32_t)s | ((db - D_MIN_BITS) << 16);
                r1[e] = pack_bf(bf_lo(rxy) * inv, bf_hi(rxy) * inv);
                r2[e] = __byte_perm(pack_bf(bf_lo(rz) * inv, 0.f), dl, 0x5410);
                if (db <= D_MAX_BITS) rk[e] = (uint32_t)atomicAdd(&binCnt[bin], 1) | (bin << 16);
            }
        }
    }
    STAMP(2);
    __syncthreads();
    STAMP(3);
    if (warp == 0) {
        int c[5], s = 0;
#pragma unroll
        for (int i = 0; i < 5; i++) { int b = lane * 5 + i; c[i] = b < p.ncta ? binCnt[b] : 0; s += c[i]; }
        int x = s;
#pragma unroll
        for (int o = 1; o < 32; o <<= 1) { int y = __shfl_up_sync(0xffffffffu, x, o); if (lane >= o) x += y; }
        int off = x - s;
#pragma unroll
        for (int i = 0; i < 5; i++) {
            int b = lane * 5 + i;
            if (b < p.ncta) { binOff[b] = off; g_offs[cta * MAX_CTA + b] = (uint32_t)off | ((uint32_t)c[i] << 16); }
            off += c[i];
        }
        if (lane == 31) ctrl[8] = x;
    }
    __syncthreads();
#pragma unroll
    for (int e = 0; e < 12; e++) {
        if (rk[e] != 0xffffffffu) {
            int pos = binOff[rk[e] >> 16] + (int)(rk[e] & 0xffffu);
            sts128(sb + P1_STAGE + pos * 16, make_uint4(r0[e], r1[e], r2[e], 0u));
        }
    }
    fence_async_smem();
    __syncthreads();
    if (tid == 0) {
        const uint32_t bytes = (uint32_t)ctrl[8] * 16u;
        if (bytes) asm volatile("cp.async.bulk.global.shared::cta.bulk_group [%0], [%1], %2;"
                                ::"l"(g_rec + (size_t)cta * REC_CAP), "r"(sb + P1_STAGE), "r"(bytes) : "memory");
        asm volatile("cp.async.bulk.commit_group;" ::: "memory");
    }
    asm volatile("cp.async.bulk.wait_group 0;" ::: "memory");
    asm volatile("fence.proxy.async;" ::: "memory");

    __syncthreads();
    STAMP(4);
    unsigned bar_target = 0;
    if (tid == 0) {
        unsigned old;
        __threadfence();
        asm volatile("atom.add.release.gpu.global.u32 %0, [%1], 1;" : "=r"(old) : "l"(&g_bar) : "memory");
        bar_target = (old / (unsigned)p.ncta + 1u) * (unsigned)p.ncta;
    }
    if (tid == 0) {
        unsigned cur;
        int spins = 0;
        do {
            asm volatile("ld.acquire.gpu.global.u32 %0, [%1];" : "=r"(cur) : "l"(&g_bar) : "memory");
        } while ((int)(cur - bar_target) < 0 && ++spins < (1 << 24));
        asm volatile("fence.proxy.async;" ::: "memory");
    }
    __syncthreads();
    STAMP(5);

    if (warp == 0) {
        uint32_t v[5];
        int s = 0;
#pragma unroll
        for (int i = 0; i < 5; i++) {
            int b = lane * 5 + i;
            v[i] = b < p.ncta ? __ldcg(&g_offs[b * MAX_CTA + cta]) : 0u;
        }
#pragma unroll
        for (int i = 0; i < 5; i++) s += (int)(v[i] >> 16);
        int x = s;
#pragma unroll
        for (int o = 1; o < 32; o <<= 1) { int y = __shfl_up_sync(0xffffffffu, x, o); if (lane >= o) x += y; }
        const int total = __shfl_sync(0xffffffffu, x, 31);
        int off = x - s;
#pragma unroll
        for (int i = 0; i < 5; i++) {
            int b = lane * 5 + i;
            if (b < p.ncta) { binCnt[b] = (int)v[i]; binOff[b] = off; }
            off += (int)(v[i] >> 16);
        }
        if (lane == 0) {
            ctrl[8] = total;
            if (total > STAGE_CAP) ctrl[1] = 1;
            mbar_expect_tx(bar_rec, total > STAGE_CAP ? 0u : (uint32_t)total * 16u);
        }
    }
    __syncthreads();
    const int total = ctrl[8];
    if (ctrl[1] == 0) {
        const int b = (lane << 4) | warp;
        if (lane < 9 && b < p.ncta) {
            const uint32_t v = (uint32_t)binCnt[b], c = v >> 16;
            if (c) {
                asm volatile("fence.proxy.async;" ::: "memory");
                bulk_g2s(sb + SM_STAGE2 + (uint32_t)binOff[b] * 16u, g_rec + (size_t)b * REC_CAP + (v & 0xffffu), c * 16u, bar_rec);
            }
        }
    }
    mbar_wait(bar_rec, 0);
    if (ctrl[1] == 0) {
        for (int i = tid; i < total; i += NT) {
            uint32_t dl = lds32(sb + SM_STAGE2 + i * 16 + 8) >> 16;
            sts32(sb + SM_STAGE2 + i * 16 + 12, (uint32_t)atomicAdd(&nCnt[dl], 1));
        }
    }
    __syncthreads();
    if (warp == 0) {
        int c[3], s = 0;
#pragma unroll
        for (int i = 0; i < 3; i++) {
            int b = lane * 3 + i;
            c[i] = b < nnodes ? max(16, (nCnt[b] + 15) & ~15) : 0;
            s += c[i];
        }
        int x = s;
#pragma unroll
        for (int o = 1; o < 32; o <<= 1) { int y = __shfl_up_sync(0xffffffffu, x, o); if (lane >= o) x += y; }
        const int slots = __shfl_sync(0xffffffffu, x, 31);
        int off = x - s, below1 = 0, below2 = 0;
#pragma unroll
        for (int i = 0; i < 3; i++) {
            int b = lane * 3 + i;
            if (b < nnodes) {
                nInfo[b] = (uint32_t)off | ((uint32_t)c[i] << 16);
                const int centre3 = 3 * (2 * off + c[i]);
                below1 += centre3 < 2 * slots;
                below2 += centre3 < 4 * slots;
            }
            off += c[i];
        }
        below1 = __reduce_add_sync(0xffffffffu, below1);
        below2 = __reduce_add_sync(0xffffffffu, below2);
        if (lane == 0) {
            ctrl[2] = below1;
            ctrl[3] = below2;
            ctrl[4] = slots;
            if (slots > SLOT_CAP) ctrl[1] = 1;
        }
    }
    __syncthreads();
    if (ctrl[1] == 0) {
        uint16_t* sid = (uint16_t*)(smem + SM_SID);
        uint2* meta = (uint2*)(smem + SM_META);
        for (int i = tid; i < total; i += NT) {
            uint4 r = lds128(sb + SM_STAGE2 + i * 16);
            int pos = (int)(nInfo[r.z >> 16] & 0xffffu) + (int)r.w;
            sid[pos]  = (uint16_t)(r.x & 0xffffu);
            meta[pos] = make_uint2(((r.x >> 16) << 5) | (r.z << 16), r.y);
        }
        for (int i = tid; i < nnodes * 16; i += NT) {
            int nl = i >> 4, c = nCnt[nl];
            int j = (c & ~15) + (i & 15);
            if (j >= c && (j < 16 || (c & 15))) {
                int pos = (int)(nInfo[nl] & 0xffffu) + j;
                sid[pos]  = 0xffffu;
                meta[pos] = make_uint2((uint32_t)TAB_ZERO << 5, 0u);
            }
        }
    }
    __syncthreads();
    for (int i = SM_RING4 / 16 + tid; i < SM_HT / 16; i += NT)
        if (i * 16 >= SM_META + ctrl[4] * 8) sts128(sb + i * 16, make_uint4(0u, 0u, 0u, 0u));
    fence_async_smem();
    __syncthreads();
    STAMP(6);

    if (__shfl_sync(0xffffffffu, ctrl[1], 0) != 0) {
        float* acc = (float*)(smem + P1_POS);
        for (int i = tid; i < nnodes * 256; i += NT) acc[i] = 0.f;
        __syncthreads();
        const uint16_t* posu = (const uint16_t*)p.pos;
        const uint32_t* tabg = (const uint32_t*)g_table;
        const uint32_t* Fw = (const uint32_t*)g_F;
        for (int e0 = warp * 32; e0 < p.E; e0 += NT) {
            int e = e0 + lane;
            int s = 0, d = 0;
            uint32_t db = 0xffff, rxy = 0, rz = 0;
            bool act = false;
            if (e < p.E) {
                s = p.src[e]; d = p.dst[e];
                if (d >= node0 && d < node0 + nnodes) {
                    uint32_t sxy = posu[s * 3] | ((uint32_t)posu[s * 3 + 1] << 16), sz = posu[s * 3 + 2];
                    uint32_t dxy = posu[d * 3] | ((uint32_t)posu[d * 3 + 1] << 16), dz = posu[d * 3 + 2];
                    db  = edge_dist(sxy, sz, dxy, dz, rxy, rz);
                    act = db <= D_MAX_BITS;
                }
            }
            unsigned m = __ballot_sync(0xffffffffu, act);
            while (m) {
                int l = __ffs(m) - 1;
                m &= m - 1;
                int es = __shfl_sync(0xffffffffu, s, l), ed = __shfl_sync(0xffffffffu, d, l);
                uint32_t edb = __shfl_sync(0xffffffffu, db, l), exy = __shfl_sync(0xffffffffu, rxy, l), ez = __shfl_sync(0xffffffffu, rz, l);
                float inv = 1.0f / __uint_as_float(edb << 16);
                float rh[3] = {rbf(bf_lo(exy) * inv), rbf(bf_hi(exy) * inv), rbf(bf_lo(ez) * inv)};
                const uint32_t* fr = Fw + (size_t)es * 128 + lane;
                const uint32_t fh = __ldcg(fr);
                const uint32_t q[3] = {__ldcg(fr + 32), __ldcg(fr + 64), __ldcg(fr + 96)};
                float ps0 = 0.f, ps1 = 0.f, pr0 = 0.f, pr1 = 0.f;
                for (int j2 = 0; j2 < 32; j2++) {
                    uint32_t hj = __shfl_sync(0xffffffffu, fh, j2);
                    uint32_t a0 = *(const uint32_t*)(p.w2 + (2 * j2) * 192 + 2 * lane), a1 = *(const uint32_t*)(p.w2 + (2 * j2 + 1) * 192 + 2 * lane);
                    uint32_t b0 = *(const uint32_t*)(p.w2 + (2 * j2) * 192 + 128 + 2 * lane), b1 = *(const uint32_t*)(p.w2 + (2 * j2 + 1) * 192 + 128 + 2 * lane);
                    ps0 += bf_lo(hj) * bf_lo(a0) + bf_hi(hj) * bf_lo(a1);
                    ps1 += bf_lo(hj) * bf_hi(a0) + bf_hi(hj) * bf_hi(a1);
                    pr0 += bf_lo(hj) * bf_lo(b0) + bf_hi(hj) * bf_lo(b1);
                    pr1 += bf_lo(hj) * bf_hi(b0) + bf_hi(hj) * bf_hi(b1);
                }
                float ws0 = 0.f, ws1 = 0.f, wv0 = 0.f, wv1 = 0.f, wr0 = 0.f, wr1 = 0.f;
                for (int k2 = 0; k2 < 8; k2++) {
                    uint32_t rk2 = __ldcg(tabg + (edb - D_MIN_BITS) * 8 + k2);
#pragma unroll
                    for (int h = 0; h < 2; h++) {
                        float rv = h ? bf_hi(rk2) : bf_lo(rk2);
                        const __nv_bfloat16* wrow = p.wr + (2 * k2 + h) * 192 + 2 * lane;
                        uint32_t a = *(const uint32_t*)wrow, b = *(const uint32_t*)(wrow + 64), c = *(const uint32_t*)(wrow + 128);
                        ws0 += rv * bf_lo(a); ws1 += rv * bf_hi(a);
                        wv0 += rv * bf_lo(b); wv1 += rv * bf_hi(b);
                        wr0 += rv * bf_lo(c); wr1 += rv * bf_hi(c);
                    }
                }
                float* a = acc + (ed - node0) * 256 + 2 * lane;
                atomicAdd(a, ps0 * ws0); atomicAdd(a + 1, ps1 * ws1);
#pragma unroll
                for (int c = 0; c < 3; c++) {
                    atomicAdd(a + 64 * (c + 1), wv0 * bf_lo(q[c]) + pr0 * wr0 * rh[c]);
                    atomicAdd(a + 64 * (c + 1) + 1, wv1 * bf_hi(q[c]) + pr1 * wr1 * rh[c]);
                }
            }
        }
        __syncthreads();
        for (int i = tid; i < nnodes * 128; i += NT) {
            uint32_t r = *(const uint32_t*)(p.sv + (size_t)node0 * 256 + 2 * i);
            *(uint32_t*)(p.out + (size_t)node0 * 256 + 2 * i) = pack_bf(bf_lo(r) + acc[2 * i], bf_hi(r) + acc[2 * i + 1]);
        }
        return;
    }

    const int slots = ctrl[4];
    const int nstage = slots <= SLOT_CAP4 ? 4 : 3;
    const uint32_t ring = sb + (nstage == 4 ? SM_RING4 : SM_RING3);
    if (warp >= 4 * NCWG) {
        asm volatile("setmaxnreg.dec.sync.aligned.u32 56;");
        const int wg = warp - 4 * NCWG;
        if (wg < NCWG) {
            const int nb = wg == 0 ? 0 : ctrl[1 + wg], ne = wg == NCWG - 1 ? nnodes : ctrl[2 + wg];
            const int g0 = (nb < nnodes ? (int)(nInfo[nb] & 0xffffu) : slots) >> 4;
            const int g1 = (ne < nnodes ? (int)(nInfo[ne] & 0xffffu) : slots) >> 4;
            const int e = lane >> 1, half = lane & 1;
            const uint32_t coef_off = e * 128 + ((half ^ (e & 7)) << 4);
            const uint8_t* tab = (const uint8_t*)g_table + half * 16;
            int stage = 0, phase = 1, cur_gi = 0;
            struct Pre { uint2 m; uint4 tv; uint4 ia, ib; };
            auto prefetch = [&](Pre& q, int gi) {
                q.m  = lds64(sb + SM_META + (gi * 16 + e) * 8);
                q.ia = lds128(sb + SM_SID + gi * 32);
                q.ib = lds128(sb + SM_SID + gi * 32 + 16);
                q.tv = __ldg((const uint4*)(tab + (q.m.x & 0xffffu)));
            };
            auto produce = [&](const Pre& q) {
                const uint32_t st = ring + (wg * nstage + stage) * STAGE_B;
                const uint32_t fb = bar_full + (wg * MAX_STAGE + stage) * 8;
                const uint32_t id2[8] = {q.ia.x, q.ia.y, q.ia.z, q.ia.w, q.ib.x, q.ib.y, q.ib.z, q.ib.w};
                const int nv = __popc(__ballot_sync(0xffffffffu, (q.m.x & 0xffffu) != (uint32_t)(TAB_ZERO << 5))) >> 1;
                mbar_wait(bar_empty + (wg * MAX_STAGE + stage) * 8, phase);
                uint32_t leader;
                asm volatile("{\n.reg .pred p;\nelect.sync _|p, 0xffffffff;\nselp.u32 %0, 1, 0, p;\n}" : "=r"(leader));
                if (leader) {
                    if (nv == 16) {
#pragma unroll
                        for (int i = 0; i < 8; i++) {
                            tma_load(st + 2048 + (2 * i) * 640, &tmF, (int)(id2[i] & 0xffffu) * 4, fb);
                            tma_load(st + 2048 + (2 * i + 1) * 640, &tmF, (int)(id2[i] >> 16) * 4, fb);
                        }
                    } else {
                        for (int i = 0; i < nv; i++)
                            tma_load(st + 2048 + i * 640, &tmF, (int)lds16(sb + SM_SID + (cur_gi * 16 + i) * 2) * 4, fb);
                    }
                }
                __syncwarp();
                const uint32_t mx = __byte_perm(q.m.y, 0, 0x1010), my = __byte_perm(q.m.y, 0, 0x3232), mz = __byte_perm(q.m.x, 0, 0x3232);
                const uint32_t a = st + coef_off;
                sts128(a, q.tv);
                sts128(a ^ 0x20, make_uint4(hmul2(q.tv.x, mx), hmul2(q.tv.y, mx), hmul2(q.tv.z, mx), hmul2(q.tv.w, mx)));
                sts128(a ^ 0x40, make_uint4(hmul2(q.tv.x, my), hmul2(q.tv.y, my), hmul2(q.tv.z, my), hmul2(q.tv.w, my)));
                sts128(a ^ 0x60, make_uint4(hmul2(q.tv.x, mz), hmul2(q.tv.y, mz), hmul2(q.tv.z, mz), hmul2(q.tv.w, mz)));
                fence_async_smem();
                __syncwarp();
                if (lane == 0) mbar_expect_tx(fb, (uint32_t)nv * 512u);
                if (++stage == nstage) { stage = 0; phase ^= 1; }
            };
            Pre qa, qb;
            int gi = g0;
            if (gi < g1) prefetch(qa, gi);
            while (gi < g1) {
                if (gi + 1 < g1) prefetch(qb, gi + 1);
                cur_gi = gi;
                produce(qa);
                if (++gi >= g1) break;
                if (gi + 1 < g1) prefetch(qa, gi + 1);
                cur_gi = gi;
                produce(qb);
                ++gi;
            }
        }
    } else {
        asm volatile("setmaxnreg.inc.sync.aligned.u32 152;");
        const int wg = warp >> 2, w = warp & 3;
        const int n_begin = wg == 0 ? 0 : ctrl[1 + wg], n_end = wg == NCWG - 1 ? nnodes : ctrl[2 + wg];
        uint32_t wA[2][4][4];
        {
            const uint16_t* w2 = (const uint16_t*)p.w2 + 16 * w + g;
#pragma unroll
            for (int m = 0; m < 2; m++) {
#pragma unroll
                for (int ks = 0; ks < 4; ks++) {
#pragma unroll
                    for (int i = 0; i < 4; i++) {
                        const uint16_t* q = w2 + (16 * ks + 2 * t + 8 * (i >> 1)) * 192 + m * 128 + 8 * (i & 1);
                        wA[m][ks][i] = (uint32_t)__ldg(q) | ((uint32_t)__ldg(q + 192) << 16);
                    }
                }
            }
            if (wg == 0) {
                const uint16_t* wr = (const uint16_t*)p.wr + 16 * w + g;
#pragma unroll
                for (int ty = 0; ty < 3; ty++) {
                    uint32_t wp[4];
#pragma unroll
                    for (int i = 0; i < 4; i++) {
                        const uint16_t* q = wr + (8 * (i >> 1) + 2 * t) * 192 + ty * 64 + 8 * (i & 1);
                        wp[i] = (uint32_t)__ldg(q) | ((uint32_t)__ldg(q + 192) << 16);
                    }
                    sts128(sb + SM_WP + (ty * 128 + (tid & 127)) * 16, make_uint4(wp[0], wp[1], wp[2], wp[3]));
                }
            }
            asm volatile("bar.sync 4, 384;" ::: "memory");
        }
        uint32_t wp[3][4];
#pragma unroll
        for (int ty = 0; ty < 3; ty++) {
            const uint4 q = lds128(sb + SM_WP + (ty * 128 + (tid & 127)) * 16);
            wp[ty][0] = q.x; wp[ty][1] = q.y; wp[ty][2] = q.z; wp[ty][3] = q.w;
        }
        uint32_t aoff[4];
        {
            const int e = (lane & 7) + 8 * (lane >> 4), ch = 2 * w + ((lane >> 3) & 1);
#pragma unroll
            for (int b = 0; b < 4; b++) aoff[b] = 2048 + e * 640 + b * 128 + ((ch ^ ((5 * e + b) & 7)) << 4);
        }
        const uint32_t ht = sb + SM_HT + wg * 8192;
        const uint32_t stsm_a = ht + (16 * w + (lane & 15)) * 128 + (((lane >> 4) ^ (lane & 7)) << 4);
        const uint32_t dht = desc_lo(ht);
        const uint32_t out_lane = (uint32_t)node0 * 512u + t * 128 + (16 * w + (g & 1) * 8 + (g & 6)) * 2;
        const uint32_t ring_wg = ring + wg * nstage * STAGE_B;
        const uint32_t full_wg = bar_full + wg * MAX_STAGE * 8, empty_wg = bar_empty + wg * MAX_STAGE * 8;
        float ys[8], yv[24], dQ[3][8];
        int left;
        {
            const int s0 = n_begin < nnodes ? (int)(nInfo[n_begin] & 0xffffu) : slots;
            const int s1 = n_end < nnodes ? (int)(nInfo[n_end] & 0xffffu) : slots;
            left = __reduce_max_sync(0xffffffffu, (s1 - s0) >> 4);
        }
        uint32_t A0[4][4];
        int cstage = 0, cphase = 0;
        int nl = n_begin, gi = 0, G = 0;
        uint32_t resid = 0;
        auto node_begin = [&]() {
            G = __reduce_max_sync(0xffffffffu, (int)(nInfo[nl] >> 20));
            resid = __ldg((const uint32_t*)((const uint8_t*)p.sv + (out_lane + (uint32_t)nl * 512u)));
            gi = 0;
        };
        auto epilogue = [&]() {
            ITS(5);
            named_barrier(1 + wg);
            ITS(6);
            uint32_t sa = stsm_a;
            asm volatile("" : "+r"(sa));
            stsm4(sa, pack_bf(ys[0], ys[1]), pack_bf(ys[2], ys[3]), pack_bf(ys[4], ys[5]), pack_bf(ys[6], ys[7]));
#pragma unroll
            for (int i = 0; i < 6; i += 2) {
                stsm4(sa ^ ((i + 2) << 4),
                      pack_bf(yv[4 * i], yv[4 * i + 1]), pack_bf(yv[4 * i + 2], yv[4 * i + 3]),
                      pack_bf(yv[4 * i + 4], yv[4 * i + 5]), pack_bf(yv[4 * i + 6], yv[4 * i + 7]));
            }
            ITS(7);
            fence_async_smem();
            ITS(8);
            named_barrier(1 + wg);
            ITS(9);
            float zs[8], zv[24];
            wg_fence();
            wgmma_n16_first(zs, wA[0][0], dht);
            wgmma_n48_first(zv, wA[1][0], dht + 2);
#pragma unroll
            for (int ks = 1; ks < 4; ks++) {
                wgmma_n16(zs, wA[0][ks], dht + ks * 128);
                wgmma_n48(zv, wA[1][ks], dht + ks * 128 + 2);
            }
            wg_commit();
#pragma unroll
            for (int i = 0; i < 12; i++) asm volatile("" : "+r"(wp[i >> 2][i & 3]));
            float pr[4][2];
#pragma unroll
            for (int a = 0; a < 3; a++) {
                const float* q = dQ[a];
                pr[a + 1][0] = bf_lo(wp[1][0]) * q[0] + bf_hi(wp[1][0]) * q[1] + bf_lo(wp[1][2]) * q[4] + bf_hi(wp[1][2]) * q[5];
                pr[a + 1][1] = bf_lo(wp[1][1]) * q[2] + bf_hi(wp[1][1]) * q[3] + bf_lo(wp[1][3]) * q[6] + bf_hi(wp[1][3]) * q[7];
            }
            ITS(10);
            wg_wait0();
            ITS(11);
            pr[0][0] = bf_lo(wp[0][0]) * zs[0] + bf_hi(wp[0][0]) * zs[1] + bf_lo(wp[0][2]) * zs[4] + bf_hi(wp[0][2]) * zs[5];
            pr[0][1] = bf_lo(wp[0][1]) * zs[2] + bf_hi(wp[0][1]) * zs[3] + bf_lo(wp[0][3]) * zs[6] + bf_hi(wp[0][3]) * zs[7];
#pragma unroll
            for (int a = 0; a < 3; a++) {
                const float* y = zv + 8 * a;
                pr[a + 1][0] += bf_lo(wp[2][0]) * y[0] + bf_hi(wp[2][0]) * y[1] + bf_lo(wp[2][2]) * y[4] + bf_hi(wp[2][2]) * y[5];
                pr[a + 1][1] += bf_lo(wp[2][1]) * y[2] + bf_hi(wp[2][1]) * y[3] + bf_lo(wp[2][3]) * y[6] + bf_hi(wp[2][3]) * y[7];
            }
            const bool hi2 = t & 2, hi1 = t & 1, odd = g & 1;
            float ka0 = hi2 ? pr[2][0] : pr[0][0], ka1 = hi2 ? pr[2][1] : pr[0][1];
            float kb0 = hi2 ? pr[3][0] : pr[1][0], kb1 = hi2 ? pr[3][1] : pr[1][1];
            float sa0 = hi2 ? pr[0][0] : pr[2][0], sa1 = hi2 ? pr[0][1] : pr[2][1];
            float sb0 = hi2 ? pr[1][0] : pr[3][0], sb1 = hi2 ? pr[1][1] : pr[3][1];
            ka0 += __shfl_xor_sync(0xffffffffu, sa0, 2); ka1 += __shfl_xor_sync(0xffffffffu, sa1, 2);
            kb0 += __shfl_xor_sync(0xffffffffu, sb0, 2); kb1 += __shfl_xor_sync(0xffffffffu, sb1, 2);
            float k0 = hi1 ? kb0 : ka0, k1 = hi1 ? kb1 : ka1;
            float s0 = hi1 ? ka0 : kb0, s1 = hi1 ? ka1 : kb1;
            k0 += __shfl_xor_sync(0xffffffffu, s0, 1);
            k1 += __shfl_xor_sync(0xffffffffu, s1, 1);
            const float other = __shfl_xor_sync(0xffffffffu, odd ? k0 : k1, 4);
            const float lo = odd ? other : k0, hi = odd ? k1 : other;
            *(uint32_t*)((uint8_t*)p.out + (out_lane + (uint32_t)nl * 512u)) = pack_bf(bf_lo(resid) + lo, bf_hi(resid) + hi);
            ITS(12);
        };
        if (left > 0) node_begin();
        while (left > 0) {
            ITS(0);
            ITS(1);
            const uint32_t st = ring_wg + cstage * STAGE_B;
            mbar_wait(full_wg + cstage * 8, cphase);
            ITS(2);
#pragma unroll
            for (int b = 0; b < 4; b++) ldsm4t(A0[b], st + aoff[b]);
            const uint32_t bd = desc_lo(st);
            wg_fence();
            if (gi == 0) {
                wgmma_n64_first(ys, yv, A0[0], bd);
                wgmma_n16_first(dQ[0], A0[1], bd);
                wgmma_n16_first(dQ[1], A0[2], bd);
                wgmma_n16_first(dQ[2], A0[3], bd);
            } else {
                wgmma_n64(ys, yv, A0[0], bd);
                wgmma_n16(dQ[0], A0[1], bd);
                wgmma_n16(dQ[1], A0[2], bd);
                wgmma_n16(dQ[2], A0[3], bd);
            }
            wg_commit();
            ITS(3);
            wg_wait0();
            ITS(4);
            if (lane == 0) mbar_arrive(empty_wg + cstage * 8);
            if (++cstage == nstage) { cstage = 0; cphase ^= 1; }
            --left;
            if (++gi == G) {
                epilogue();
                if (++nl < n_end) node_begin();
            }
            ITS(13);
        }
    }
    STAMP(8);
}

typedef CUresult (*EncodeFn)(CUtensorMap*, CUtensorMapDataType, cuuint32_t, void*, const cuuint64_t*, const cuuint64_t*,
                             const cuuint32_t*, const cuuint32_t*, CUtensorMapInterleave, CUtensorMapSwizzle,
                             CUtensorMapL2promotion, CUtensorMapFloatOOBfill);

void make_map(EncodeFn enc, CUtensorMap* tm, const void* base, uint64_t lines, uint32_t box) {
    cuuint64_t gd[2] = {64, lines};
    cuuint64_t gs[1] = {128};
    cuuint32_t bd[2] = {64, box};
    cuuint32_t es[2] = {1, 1};
    enc(tm, CU_TENSOR_MAP_DATA_TYPE_BFLOAT16, 2, const_cast<void*>(base), gd, gs, bd, es, CU_TENSOR_MAP_INTERLEAVE_NONE,
        CU_TENSOR_MAP_SWIZZLE_128B, CU_TENSOR_MAP_L2_PROMOTION_L2_128B, CU_TENSOR_MAP_FLOAT_OOB_FILL_NONE);
}

}

extern "C" void kernel_launch(void* const* d_in, const int* in_sizes, int n_in, void* d_out, int out_size) {
    (void)n_in; (void)out_size;
    static int n_sm = 0;
    static EncodeFn enc = nullptr;
    static void* f_ptr = nullptr;
    if (n_sm == 0) {
        int dev = 0;
        cudaGetDevice(&dev);
        cudaDeviceGetAttribute(&n_sm, cudaDevAttrMultiProcessorCount, dev);
        cudaFuncSetAttribute(painn_kernel, cudaFuncAttributeMaxDynamicSharedMemorySize, SM_TOTAL);
        void* fn = nullptr;
        cudaDriverEntryPointQueryResult qr;
        cudaGetDriverEntryPoint("cuTensorMapEncodeTiled", &fn, cudaEnableDefault, &qr);
        enc = (EncodeFn)fn;
        cudaGetSymbolAddress(&f_ptr, g_F);
    }
    Params p;
    p.sv    = (const __nv_bfloat16*)d_in[0];
    p.pos   = (const __nv_bfloat16*)d_in[1];
    p.src   = (const int*)d_in[2];
    p.dst   = (const int*)d_in[3];
    p.freqs = (const __nv_bfloat16*)d_in[4];
    p.w1    = (const __nv_bfloat16*)d_in[5];
    p.w2    = (const __nv_bfloat16*)d_in[6];
    p.wr    = (const __nv_bfloat16*)d_in[7];
    p.out   = (__nv_bfloat16*)d_out;
    p.N = in_sizes[1] / 3;
    p.E = in_sizes[2];
    p.ncta = n_sm < MAX_CTA ? n_sm : MAX_CTA;
    p.npc = (p.N + p.ncta - 1) / p.ncta;
    p.npc_magic = (uint32_t)(0x100000000ull / (uint32_t)p.npc) + 1u;
    p.quads_per_cta = ((p.E >> 2) + p.ncta - 1) / p.ncta;
    if (!enc || p.N > MAX_N || p.npc > MAX_NPC || (p.E & 3) || p.quads_per_cta > MAX_ROUNDS * 32) return;

    CUtensorMap tmF, tmSV, tmW1, tmW2;
    make_map(enc, &tmF, f_ptr, (uint64_t)p.N * 4, 4);
    make_map(enc, &tmSV, p.sv, (uint64_t)p.N * 4, 160);
    make_map(enc, &tmW1, p.w1, 64, 64);
    make_map(enc, &tmW2, p.w2, 192, 192);

    cudaLaunchConfig_t cfg = {};
    cfg.gridDim = dim3(p.ncta);
    cfg.blockDim = dim3(NT);
    cfg.dynamicSmemBytes = SM_TOTAL;
    cfg.stream = cudaStreamPerThread;
    cudaLaunchAttribute attr[1];
    attr[0].id = cudaLaunchAttributeCooperative;
    attr[0].val.cooperative = 1;
    cfg.attrs = attr;
    cfg.numAttrs = 1;
    cudaLaunchKernelEx(&cfg, painn_kernel, p, tmF, tmSV, tmW1, tmW2);
}
```

```cpp
#include <cuda_runtime.h>
#include <cuda.h>
#include <cuda_bf16.h>
#include <stdint.h>

namespace {

constexpr int NT        = 512;
constexpr int NCWG      = 2;
constexpr int MAX_N     = 10240;
constexpr int MAX_CTA   = 144;
constexpr int MAX_NPC   = 80;
constexpr int MAX_ROUNDS = 38;
constexpr int REC_CAP   = MAX_ROUNDS * 128;
constexpr int SLOT_CAP  = 6144;
constexpr int MAX_STAGE = 6;
constexpr int STAGE_B   = 12288;

constexpr uint32_t D_MIN_BITS = 0x38D2;
constexpr uint32_t D_MAX_BITS = 0x409C;
constexpr int TAB_ROWS  = (int)(D_MAX_BITS - D_MIN_BITS) + 1;
constexpr int TAB_ZERO  = TAB_ROWS;
constexpr int TAB_BYTES = (TAB_ROWS + 1) * 32;

constexpr int SM_BINCNT = 0;
constexpr int SM_BINOFF = SM_BINCNT + MAX_CTA * 4;
constexpr int SM_NCNT   = SM_BINOFF + MAX_CTA * 4;
constexpr int SM_NINFO  = SM_NCNT + MAX_NPC * 4;
constexpr int SM_CTRL   = SM_NINFO + MAX_NPC * 4;
constexpr int SM_BARS   = SM_CTRL + 64;
constexpr int SM_SID    = 2048 + 128;
constexpr int SM_META   = SM_SID + SLOT_CAP * 2;
constexpr int SM_TOTAL  = 232448;
constexpr int SM_HT     = (SM_TOTAL - NCWG * 8192) / 1024 * 1024;
constexpr int SM_RING4  = SM_HT - NCWG * 6 * STAGE_B;
constexpr int SM_RING3  = SM_HT - NCWG * 5 * STAGE_B;
constexpr int SLOT_CAP4 = (SM_RING4 - SM_META) / 8;
constexpr int SM_STAGE2 = SM_RING3 - 0;
constexpr int STAGE_CAP = (SM_TOTAL - SM_RING3) / 16;
constexpr int P1_POS    = 3072;
constexpr int P1_STAGE  = P1_POS + 61440;
constexpr int P1_SV     = (P1_STAGE + REC_CAP * 16 + 1023) / 1024 * 1024;
constexpr int P1_W1     = P1_SV + MAX_NPC * 512;
constexpr int P1_W2     = P1_W1 + 8192;
constexpr int P1_END    = P1_W2 + 24576;
static_assert(SM_BARS + (4 + 2 * NCWG * MAX_STAGE) * 8 <= SM_SID, "misc block");
static_assert(SM_BARS + 256 <= P1_POS, "misc block");
static_assert(P1_END <= SM_TOTAL, "phase 1 overlay");
static_assert(SM_META + SLOT_CAP * 8 <= SM_RING3, "CSR");
static_assert(SM_RING4 % 1024 == 0 && SM_RING3 % 1024 == 0 && SM_HT % 1024 == 0, "alignment");
static_assert(SM_BARS % 8 == 0 && SM_META % 8 == 0, "alignment");
static_assert(MAX_N * 6 <= 61440, "pos");
static_assert(SM_SID + MAX_NPC * 1024 <= SM_TOTAL, "slow path accumulators");

__device__ __align__(1024) uint4 g_F[MAX_N * 32];
__device__ uint4    g_rec[MAX_CTA * REC_CAP];
__device__ uint32_t g_offs[MAX_CTA * MAX_CTA];
__device__ uint4    g_table[(TAB_BYTES + 15) / 16];
__device__ unsigned g_bar;
#define STAMP(k)
#define ITS(k)

struct Params {
    const __nv_bfloat16* sv;
    const __nv_bfloat16* pos;
    const int*           src;
    const int*           dst;
    const __nv_bfloat16* freqs;
    const __nv_bfloat16* w1;
    const __nv_bfloat16* w2;
    const __nv_bfloat16* wr;
    __nv_bfloat16*       out;
    int N, E, ncta, npc;
    uint32_t npc_magic;
    int quads_per_cta;
};

__device__ __forceinline__ uint32_t smem_u32(const void* p) { return (uint32_t)__cvta_generic_to_shared(p); }
__device__ __forceinline__ float bf_lo(uint32_t v) { return __uint_as_float(v << 16); }
__device__ __forceinline__ float bf_hi(uint32_t v) { return __uint_as_float(v & 0xffff0000u); }
__device__ __forceinline__ float bf_u16(uint16_t v) { return __uint_as_float((uint32_t)v << 16); }
__device__ __forceinline__ uint32_t pack_bf(float lo, float hi) {
    uint32_t r;
    asm("cvt.rn.bf16x2.f32 %0, %1, %2;" : "=r"(r) : "f"(hi), "f"(lo));
    return r;
}
__device__ __forceinline__ float rbf(float x) { return bf_lo(pack_bf(x, 0.f)); }
__device__ __forceinline__ uint32_t hmul2(uint32_t a, uint32_t b) {
    uint32_t r;
    asm("mul.rn.bf16x2 %0, %1, %2;" : "=r"(r) : "r"(a), "r"(b));
    return r;
}
__device__ __forceinline__ uint32_t hsub2(uint32_t a, uint32_t b) {
    uint32_t r;
    asm("sub.rn.bf16x2 %0, %1, %2;" : "=r"(r) : "r"(a), "r"(b));
    return r;
}
__device__ __forceinline__ uint32_t lds32(uint32_t a) { uint32_t v; asm volatile("ld.shared.u32 %0, [%1];" : "=r"(v) : "r"(a)); return v; }
__device__ __forceinline__ uint32_t lds16(uint32_t a) { uint16_t v; asm volatile("ld.shared.u16 %0, [%1];" : "=h"(v) : "r"(a)); return v; }
__device__ __forceinline__ uint2 lds64(uint32_t a) { uint2 v; asm volatile("ld.shared.v2.u32 {%0,%1}, [%2];" : "=r"(v.x), "=r"(v.y) : "r"(a)); return v; }
__device__ __forceinline__ uint4 lds128(uint32_t a) { uint4 v; asm volatile("ld.shared.v4.u32 {%0,%1,%2,%3}, [%4];" : "=r"(v.x), "=r"(v.y), "=r"(v.z), "=r"(v.w) : "r"(a)); return v; }
__device__ __forceinline__ void sts32(uint32_t a, uint32_t v) { asm volatile("st.shared.u32 [%0], %1;" ::"r"(a), "r"(v) : "memory"); }
__device__ __forceinline__ void sts128(uint32_t a, uint4 v) { asm volatile("st.shared.v4.u32 [%0], {%1,%2,%3,%4};" ::"r"(a), "r"(v.x), "r"(v.y), "r"(v.z), "r"(v.w) : "memory"); }
__device__ __forceinline__ void mbar_init(uint32_t bar, int cnt) { asm volatile("mbarrier.init.shared::cta.b64 [%0], %1;" ::"r"(bar), "r"(cnt) : "memory"); }
__device__ __forceinline__ void mbar_expect_tx(uint32_t bar, uint32_t bytes) { asm volatile("mbarrier.arrive.expect_tx.shared::cta.b64 _, [%0], %1;" ::"r"(bar), "r"(bytes) : "memory"); }
__device__ __forceinline__ void mbar_arrive(uint32_t bar) { asm volatile("mbarrier.arrive.shared::cta.b64 _, [%0];" ::"r"(bar) : "memory"); }
__device__ __forceinline__ void mbar_wait(uint32_t bar, uint32_t parity) {
    uint32_t done;
    int spins = 0;
    do {
        asm volatile("{\n.reg .pred p;\nmbarrier.try_wait.parity.shared::cta.b64 p, [%1], %2;\nselp.u32 %0, 1, 0, p;\n}"
                     : "=r"(done) : "r"(bar), "r"(parity) : "memory");
    } while (!done && ++spins < (1 << 22));
}
__device__ __forceinline__ void bulk_g2s(uint32_t dst, const void* src, uint32_t bytes, uint32_t bar) {
    asm volatile("cp.async.bulk.shared::cluster.global.mbarrier::complete_tx::bytes [%0], [%1], %2, [%3];"
                 ::"r"(dst), "l"(src), "r"(bytes), "r"(bar) : "memory");
}
__device__ __forceinline__ void tma_load(uint32_t dst, const CUtensorMap* tm, int line, uint32_t bar) {
    asm volatile("cp.async.bulk.tensor.2d.shared::cluster.global.mbarrier::complete_tx::bytes [%0], [%1, {%3, %4}], [%2];"
                 ::"r"(dst), "l"(tm), "r"(bar), "r"(0), "r"(line) : "memory");
}
__device__ __forceinline__ void tma_store(const CUtensorMap* tm, int line, uint32_t src) {
    asm volatile("cp.async.bulk.tensor.2d.global.shared::cta.bulk_group [%0, {%2, %3}], [%1];"
                 ::"l"(tm), "r"(src), "r"(0), "r"(line) : "memory");
}
__device__ __forceinline__ void fence_async_smem() { asm volatile("fence.proxy.async.shared::cta;" ::: "memory"); }
__device__ __forceinline__ void named_barrier(int id) { asm volatile("bar.sync %0, 128;" ::"r"(id) : "memory"); }
__device__ __forceinline__ void ldsm4(uint32_t (&r)[4], uint32_t a) {
    asm volatile("ldmatrix.sync.aligned.m8n8.x4.shared.b16 {%0,%1,%2,%3}, [%4];" : "=r"(r[0]), "=r"(r[1]), "=r"(r[2]), "=r"(r[3]) : "r"(a) : "memory");
}
__device__ __forceinline__ void ldsm4t(uint32_t (&r)[4], uint32_t a) {
    asm volatile("ldmatrix.sync.aligned.m8n8.x4.trans.shared.b16 {%0,%1,%2,%3}, [%4];" : "=r"(r[0]), "=r"(r[1]), "=r"(r[2]), "=r"(r[3]) : "r"(a) : "memory");
}
__device__ __forceinline__ void stsm4(uint32_t a, uint32_t r0, uint32_t r1, uint32_t r2, uint32_t r3) {
    asm volatile("stmatrix.sync.aligned.m8n8.x4.shared.b16 [%0], {%1,%2,%3,%4};" ::"r"(a), "r"(r0), "r"(r1), "r"(r2), "r"(r3) : "memory");
}
__device__ __forceinline__ void mma16816(float (&c)[4], const uint32_t (&a)[4], uint32_t b0, uint32_t b1) {
    asm volatile("mma.sync.aligned.m16n8k16.row.col.f32.bf16.bf16.f32 {%0,%1,%2,%3}, {%4,%5,%6,%7}, {%8,%9}, {%0,%1,%2,%3};"
                 : "+f"(c[0]), "+f"(c[1]), "+f"(c[2]), "+f"(c[3])
                 : "r"(a[0]), "r"(a[1]), "r"(a[2]), "r"(a[3]), "r"(b0), "r"(b1));
}

__device__ __forceinline__ uint32_t desc_lo(uint32_t saddr) { return ((saddr & 0x3FFFF) >> 4) | (1u << 16); }
#define DESC_HI "0x40000040"
__device__ __forceinline__ void wg_fence() { asm volatile("wgmma.fence.sync.aligned;" ::: "memory"); }
__device__ __forceinline__ void wg_commit() { asm volatile("wgmma.commit_group.sync.aligned;" ::: "memory"); }
__device__ __forceinline__ void wg_wait0() { asm volatile("wgmma.wait_group.sync.aligned 0;" ::: "memory"); }
__device__ __forceinline__ void wg_wait1() { asm volatile("wgmma.wait_group.sync.aligned 1;" ::: "memory"); }

__device__ __forceinline__ void wgmma_n64_first(float (&d)[8], float (&e)[24], const uint32_t (&a)[4], uint32_t bdesc) {
    asm volatile("{\n.reg .b64 b;\nmov.b64 b, {%36, " DESC_HI "};\n"
                 "wgmma.mma_async.sync.aligned.m64n64k16.f32.bf16.bf16 {%0,%1,%2,%3,%4,%5,%6,%7,%8,%9,%10,%11,%12,%13,%14,%15,%16,%17,%18,%19,%20,%21,%22,%23,%24,%25,%26,%27,%28,%29,%30,%31}, {%32,%33,%34,%35}, b, 0, 1, 1, 1;\n}"
                 : "=f"(d[0]), "=f"(d[1]), "=f"(d[2]), "=f"(d[3]), "=f"(d[4]), "=f"(d[5]), "=f"(d[6]), "=f"(d[7]),
                   "=f"(e[0]), "=f"(e[1]), "=f"(e[2]), "=f"(e[3]), "=f"(e[4]), "=f"(e[5]), "=f"(e[6]), "=f"(e[7]), "=f"(e[8]), "=f"(e[9]), "=f"(e[10]), "=f"(e[11]), "=f"(e[12]), "=f"(e[13]), "=f"(e[14]), "=f"(e[15]), "=f"(e[16]), "=f"(e[17]), "=f"(e[18]), "=f"(e[19]), "=f"(e[20]), "=f"(e[21]), "=f"(e[22]), "=f"(e[23])
                 : "r"(a[0]), "r"(a[1]), "r"(a[2]), "r"(a[3]), "r"(bdesc));
}
__device__ __forceinline__ void wgmma_n64(float (&d)[8], float (&e)[24], const uint32_t (&a)[4], uint32_t bdesc) {
    asm volatile("{\n.reg .b64 b;\nmov.b64 b, {%36, " DESC_HI "};\n"
                 "wgmma.mma_async.sync.aligned.m64n64k16.f32.bf16.bf16 {%0,%1,%2,%3,%4,%5,%6,%7,%8,%9,%10,%11,%12,%13,%14,%15,%16,%17,%18,%19,%20,%21,%22,%23,%24,%25,%26,%27,%28,%29,%30,%31}, {%32,%33,%34,%35}, b, 1, 1, 1, 1;\n}"
                 : "+f"(d[0]), "+f"(d[1]), "+f"(d[2]), "+f"(d[3]), "+f"(d[4]), "+f"(d[5]), "+f"(d[6]), "+f"(d[7]),
                   "+f"(e[0]), "+f"(e[1]), "+f"(e[2]), "+f"(e[3]), "+f"(e[4]), "+f"(e[5]), "+f"(e[6]), "+f"(e[7]), "+f"(e[8]), "+f"(e[9]), "+f"(e[10]), "+f"(e[11]), "+f"(e[12]), "+f"(e[13]), "+f"(e[14]), "+f"(e[15]), "+f"(e[16]), "+f"(e[17]), "+f"(e[18]), "+f"(e[19]), "+f"(e[20]), "+f"(e[21]), "+f"(e[22]), "+f"(e[23])
                 : "r"(a[0]), "r"(a[1]), "r"(a[2]), "r"(a[3]), "r"(bdesc));
}
__device__ __forceinline__ void wgmma_n48_first(float (&e)[24], const uint32_t (&a)[4], uint32_t bdesc) {
    asm volatile("{\n.reg .b64 b;\nmov.b64 b, {%28, " DESC_HI "};\n"
                 "wgmma.mma_async.sync.aligned.m64n48k16.f32.bf16.bf16 {%0,%1,%2,%3,%4,%5,%6,%7,%8,%9,%10,%11,%12,%13,%14,%15,%16,%17,%18,%19,%20,%21,%22,%23}, {%24,%25,%26,%27}, b, 0, 1, 1, 1;\n}"
                 : "=f"(e[0]), "=f"(e[1]), "=f"(e[2]), "=f"(e[3]), "=f"(e[4]), "=f"(e[5]), "=f"(e[6]), "=f"(e[7]), "=f"(e[8]), "=f"(e[9]), "=f"(e[10]), "=f"(e[11]), "=f"(e[12]), "=f"(e[13]), "=f"(e[14]), "=f"(e[15]), "=f"(e[16]), "=f"(e[17]), "=f"(e[18]), "=f"(e[19]), "=f"(e[20]), "=f"(e[21]), "=f"(e[22]), "=f"(e[23])
                 : "r"(a[0]), "r"(a[1]), "r"(a[2]), "r"(a[3]), "r"(bdesc));
}
__device__ __forceinline__ void wgmma_n48(float (&e)[24], const uint32_t (&a)[4], uint32_t bdesc) {
    asm volatile("{\n.reg .b64 b;\nmov.b64 b, {%28, " DESC_HI "};\n"
                 "wgmma.mma_async.sync.aligned.m64n48k16.f32.bf16.bf16 {%0,%1,%2,%3,%4,%5,%6,%7,%8,%9,%10,%11,%12,%13,%14,%15,%16,%17,%18,%19,%20,%21,%22,%23}, {%24,%25,%26,%27}, b, 1, 1, 1, 1;\n}"
                 : "+f"(e[0]), "+f"(e[1]), "+f"(e[2]), "+f"(e[3]), "+f"(e[4]), "+f"(e[5]), "+f"(e[6]), "+f"(e[7]), "+f"(e[8]), "+f"(e[9]), "+f"(e[10]), "+f"(e[11]), "+f"(e[12]), "+f"(e[13]), "+f"(e[14]), "+f"(e[15]), "+f"(e[16]), "+f"(e[17]), "+f"(e[18]), "+f"(e[19]), "+f"(e[20]), "+f"(e[21]), "+f"(e[22]), "+f"(e[23])
                 : "r"(a[0]), "r"(a[1]), "r"(a[2]), "r"(a[3]), "r"(bdesc));
}
__device__ __forceinline__ void wgmma_n16_first(float (&d)[8], const uint32_t (&a)[4], uint32_t bdesc) {
    asm volatile("{\n.reg .b64 b;\nmov.b64 b, {%12, " DESC_HI "};\n"
                 "wgmma.mma_async.sync.aligned.m64n16k16.f32.bf16.bf16 {%0,%1,%2,%3,%4,%5,%6,%7}, {%8,%9,%10,%11}, b, 0, 1, 1, 1;\n}"
                 : "=f"(d[0]), "=f"(d[1]), "=f"(d[2]), "=f"(d[3]), "=f"(d[4]), "=f"(d[5]), "=f"(d[6]), "=f"(d[7])
                 : "r"(a[0]), "r"(a[1]), "r"(a[2]), "r"(a[3]), "r"(bdesc));
}
__device__ __forceinline__ void wgmma_n16(float (&d)[8], const uint32_t (&a)[4], uint32_t bdesc) {
    asm volatile("{\n.reg .b64 b;\nmov.b64 b, {%12, " DESC_HI "};\n"
                 "wgmma.mma_async.sync.aligned.m64n16k16.f32.bf16.bf16 {%0,%1,%2,%3,%4,%5,%6,%7}, {%8,%9,%10,%11}, b, 1, 1, 1, 1;\n}"
                 : "+f"(d[0]), "+f"(d[1]), "+f"(d[2]), "+f"(d[3]), "+f"(d[4]), "+f"(d[5]), "+f"(d[6]), "+f"(d[7])
                 : "r"(a[0]), "r"(a[1]), "r"(a[2]), "r"(a[3]), "r"(bdesc));
}

__device__ __forceinline__ uint32_t edge_dist(uint32_t sxy, uint32_t sz, uint32_t dxy, uint32_t dz, uint32_t& rxy, uint32_t& rz) {
    rxy = hsub2(sxy, dxy);
    rz  = hsub2(sz, dz);
    uint32_t qxy = hmul2(rxy, rxy), qz = hmul2(rz, rz);
    float ss = rbf((bf_lo(qxy) + bf_hi(qxy)) + bf_lo(qz));
    float s2 = rbf(ss + 1e-8f);
    float d;
    asm("sqrt.approx.ftz.f32 %0, %1;" : "=f"(d) : "f"(s2));
    return pack_bf(d, 0.f) & 0xffffu;
}

__device__ __forceinline__ void load_pos(uint32_t sm_pos, int i, uint32_t& xy, uint32_t& z) {
    uint32_t a  = (sm_pos + 6u * (uint32_t)i) & ~3u;
    uint32_t w0 = lds32(a), w1 = lds32(a + 4);
    uint32_t sh = (uint32_t)i << 4;
    xy = __funnelshift_r(w0, w1, sh);
    z  = __funnelshift_r(w1, w1, sh);
}

__device__ __noinline__ float radial_value(float d, float f) {
    float arg = rbf(d * f);
    float sn  = rbf(sinf(arg));
    float rb  = rbf(__fdiv_rn(sn, d));
    float c   = rbf(cosf(rbf(__fdiv_rn(rbf(d * 3.14159265358979323846f), 5.0f))));
    float fc  = rbf(0.5f * rbf(c + 1.0f));
    return rb * fc;
}

__global__ void __launch_bounds__(NT, 1)
painn_kernel(const Params p, const __grid_constant__ CUtensorMap tmF, const __grid_constant__ CUtensorMap tmSV,
             const __grid_constant__ CUtensorMap tmW1, const __grid_constant__ CUtensorMap tmW2) {
    extern __shared__ __align__(1024) uint8_t smem[];
    const uint32_t sb   = smem_u32(smem);
    const int tid  = threadIdx.x, lane = tid & 31, warp = __shfl_sync(0xffffffffu, tid >> 5, 0);
    const int cta  = blockIdx.x;
    const int g    = lane >> 2, t = lane & 3;
    int* binCnt = (int*)(smem + SM_BINCNT);
    int* binOff = (int*)(smem + SM_BINOFF);
    int* nCnt   = (int*)(smem + SM_NCNT);
    uint32_t* nInfo = (uint32_t*)(smem + SM_NINFO);
    volatile int* ctrl = (volatile int*)(smem + SM_CTRL);
    const uint32_t bar_pos = sb + SM_BARS, bar_mlp = bar_pos + 8, bar_rec = bar_pos + 16;
    const uint32_t bar_full = bar_pos + 32, bar_empty = bar_full + NCWG * MAX_STAGE * 8;

    const int node0  = cta * p.npc;
    const int nnodes = max(0, min(p.npc, p.N - node0));

    STAMP(0);
    if (tid == 0) {
        mbar_init(bar_pos, 1);
        mbar_init(bar_mlp, 1);
        mbar_init(bar_rec, 1);
        for (int i = 0; i < NCWG * MAX_STAGE; i++) { mbar_init(bar_full + 8 * i, 1); mbar_init(bar_empty + 8 * i, 4); }
        asm volatile("fence.mbarrier_init.release.cluster;" ::: "memory");
        uint32_t pos_bytes = (uint32_t)(p.N * 6 + 15) & ~15u;
        mbar_expect_tx(bar_pos, pos_bytes);
        bulk_g2s(sb + P1_POS, p.pos, pos_bytes, bar_pos);
        mbar_expect_tx(bar_mlp, 2u * 160u * 128u + 8192u + 24576u);
        tma_load(sb + P1_SV, &tmSV, node0 * 4, bar_mlp);
        tma_load(sb + P1_SV + 160 * 128, &tmSV, node0 * 4 + 160, bar_mlp);
        tma_load(sb + P1_W1, &tmW1, 0, bar_mlp);
        tma_load(sb + P1_W2, &tmW2, 0, bar_mlp);
    }
    const bool mlp_warp = warp >= 11;
    int4 s4[3], d4[3];
    const int q0 = cta * p.quads_per_cta;
    const int qend = min(q0 + p.quads_per_cta, p.E >> 2);
    if (!mlp_warp) {
#pragma unroll
        for (int k = 0; k < 3; k++) {
            int q = q0 + (warp + 11 * k) * 32 + lane;
            bool ok = q < qend;
            s4[k] = ok ? __ldg((const int4*)p.src + q) : make_int4(-1, -1, -1, -1);
            d4[k] = ok ? __ldg((const int4*)p.dst + q) : make_int4(0, 0, 0, 0);
        }
    } else {
        int q = q0 + (33 + warp - 11) * 32 + lane;
        if (q < qend && (lane & 7) == 0) {
            asm volatile("prefetch.global.L2 [%0];" ::"l"((const int4*)p.src + q));
            asm volatile("prefetch.global.L2 [%0];" ::"l"((const int4*)p.dst + q));
        }
    }
    if (tid < MAX_CTA) binCnt[tid] = 0;
    if (tid < MAX_NPC) nCnt[tid] = 0;
    if (tid < 16) ctrl[tid] = 0;
    if (tid >= 416 && tid < 416 + 48) {
        asm volatile("prefetch.global.L2 [%0];" ::"l"((const uint8_t*)p.wr + (tid - 416) * 128));
    }
    __syncthreads();

    if (mlp_warp) {
        const int rows_per = (TAB_ROWS + 1 + p.ncta - 1) / p.ncta;
        for (int i = tid - 11 * 32; i < rows_per * 8; i += 5 * 32) {
            int row = cta * rows_per + (i >> 3), kp = i & 7;
            if (row <= TAB_ROWS) {
                uint32_t val = 0;
                if (row < TAB_ROWS) {
                    float d = __uint_as_float((D_MIN_BITS + row) << 16);
                    uint32_t f2 = __ldg((const uint32_t*)p.freqs + kp);
                    val = pack_bf(radial_value(d, bf_lo(f2)), radial_value(d, bf_hi(f2)));
                }
                ((uint32_t*)g_table)[row * 8 + kp] = val;
            }
        }
        const int mt = warp - 11;
        if (mt * 16 < nnodes) {
            mbar_wait(bar_mlp, 0);
            float acc[8][4];
#pragma unroll
            for (int i = 0; i < 8; i++) { acc[i][0] = acc[i][1] = acc[i][2] = acc[i][3] = 0.f; }
            const int lrow = (lane & 7) + ((lane >> 3) & 1) * 8, lch = lane >> 4;
#pragma unroll
            for (int ks = 0; ks < 4; ks++) {
                uint32_t a[4];
                const int line = 4 * (mt * 16 + lrow);
                ldsm4(a, sb + P1_SV + line * 128 + (((2 * ks + lch) ^ (line & 7)) << 4));
                const int kk = 16 * ks + lrow;
#pragma unroll
                for (int nt = 0; nt < 8; nt += 2) {
                    uint32_t b[4];
                    ldsm4t(b, sb + P1_W1 + kk * 128 + (((nt + lch) ^ (kk & 7)) << 4));
                    mma16816(acc[nt], a, b[0], b[1]);
                    mma16816(acc[nt + 1], a, b[2], b[3]);
                }
            }
            uint32_t hp[8][2];
#pragma unroll
            for (int i = 0; i < 8; i++) {
                float h[4];
#pragma unroll
                for (int q = 0; q < 4; q++) {
                    float x = rbf(acc[i][q]);
                    h[q] = __fdividef(x, 1.0f + __expf(-x));
                    acc[i][q] = 0.f;
                }
                hp[i][0] = pack_bf(h[0], h[1]);
                hp[i][1] = pack_bf(h[2], h[3]);
            }
#pragma unroll
            for (int ks = 0; ks < 4; ks++) {
                uint32_t a[4] = {hp[2 * ks][0], hp[2 * ks][1], hp[2 * ks + 1][0], hp[2 * ks + 1][1]};
                const int line = 3 * (16 * ks + lrow) + 1;
#pragma unroll
                for (int nt = 0; nt < 8; nt += 2) {
                    uint32_t b[4];
                    ldsm4t(b, sb + P1_W2 + line * 128 + (((nt + lch) ^ (line & 7)) << 4));
                    mma16816(acc[nt], a, b[0], b[1]);
                    mma16816(acc[nt + 1], a, b[2], b[3]);
                }
            }
            uint32_t q[3][8][2];
#pragma unroll
            for (int rh = 0; rh < 2; rh++) {
                const int row = mt * 16 + g + 8 * rh;
#pragma unroll
                for (int i = 0; i < 8; i++) {
                    const uint32_t ph = pack_bf(acc[i][2 * rh], acc[i][2 * rh + 1]);
#pragma unroll
                    for (int a = 0; a < 3; a++) {
                        const int line = 4 * row + 1 + a;
                        q[a][i][rh] = hmul2(ph, lds32(sb + P1_SV + line * 128 + ((i ^ (line & 7)) << 4) + 4 * t));
                    }
                }
            }
            __syncwarp();
            {
                const int row = mt * 16 + (lane & 7) + ((lane >> 3) & 1) * 8;
#pragma unroll
                for (int c = 0; c < 4; c++) {
                    const int line = 4 * row + c;
                    const uint32_t lb = sb + P1_SV + line * 128;
#pragma unroll
                    for (int i = 0; i < 8; i += 2) {
                        const uint32_t a = lb + (((i + lch) ^ (line & 7)) << 4);
                        if (c == 0) stsm4(a, hp[i][0], hp[i][1], hp[i + 1][0], hp[i + 1][1]);
                        else        stsm4(a, q[c - 1][i][0], q[c - 1][i][1], q[c - 1][i + 1][0], q[c - 1][i + 1][1]);
                    }
                }
            }
            fence_async_smem();
            __syncwarp();
            if (lane < 16 && mt * 16 + lane < nnodes) tma_store(&tmF, (node0 + mt * 16 + lane) * 4, sb + P1_SV + (mt * 16 + lane) * 512);
            asm volatile("cp.async.bulk.commit_group;" ::: "memory");
        }
        const int q = q0 + (33 + warp - 11) * 32 + lane;
        const bool ok = q < qend;
        s4[0] = ok ? __ldg((const int4*)p.src + q) : make_int4(-1, -1, -1, -1);
        d4[0] = ok ? __ldg((const int4*)p.dst + q) : make_int4(0, 0, 0, 0);
        s4[1] = s4[2] = make_int4(-1, -1, -1, -1);
        d4[1] = d4[2] = make_int4(0, 0, 0, 0);
    }
    mbar_wait(bar_pos, 0);
    STAMP(1);

    uint32_t r0[12], r1[12], r2[12], rk[12];
#pragma unroll
    for (int k = 0; k < 3; k++) {
        const int ss[4] = {s4[k].x, s4[k].y, s4[k].z, s4[k].w};
        const int dd[4] = {d4[k].x, d4[k].y, d4[k].z, d4[k].w};
#pragma unroll
        for (int j = 0; j < 4; j++) rk[k * 4 + j] = 0xffffffffu;
        if (ss[0] >= 0) {
#pragma unroll
            for (int j = 0; j < 4; j++) {
                const int e = k * 4 + j;
                const int s = ss[j], d = dd[j];
                uint32_t sxy, sz, dxy, dz, rxy, rz;
                load_pos(sb + P1_POS, s, sxy, sz);
                load_pos(sb + P1_POS, d, dxy, dz);
                uint32_t db = edge_dist(sxy, sz, dxy, dz, rxy, rz);
                float inv;
                asm("rcp.approx.ftz.f32 %0, %1;" : "=f"(inv) : "f"(__uint_as_float(db << 16)));
                uint32_t bin = __umulhi((uint32_t)d, p.npc_magic);
                uint32_t dl  = (uint32_t)d - bin * (uint32_t)p.npc;
                r0[e] = (uint32_t)s | ((db - D_MIN_BITS) << 16);
                r1[e] = pack_bf(bf_lo(rxy) * inv, bf_hi(rxy) * inv);
                r2[e] = __byte_perm(pack_bf(bf_lo(rz) * inv, 0.f), dl, 0x5410);
                if (db <= D_MAX_BITS) rk[e] = (uint32_t)atomicAdd(&binCnt[bin], 1) | (bin << 16);
            }
        }
    }
    STAMP(2);
    __syncthreads();
    STAMP(3);
    if (warp == 0) {
        int c[5], s = 0;
#pragma unroll
        for (int i = 0; i < 5; i++) { int b = lane * 5 + i; c[i] = b < p.ncta ? binCnt[b] : 0; s += c[i]; }
        int x = s;
#pragma unroll
        for (int o = 1; o < 32; o <<= 1) { int y = __shfl_up_sync(0xffffffffu, x, o); if (lane >= o) x += y; }
        int off = x - s;
#pragma unroll
        for (int i = 0; i < 5; i++) {
            int b = lane * 5 + i;
            if (b < p.ncta) { binOff[b] = off; g_offs[cta * MAX_CTA + b] = (uint32_t)off | ((uint32_t)c[i] << 16); }
            off += c[i];
        }
        if (lane == 31) ctrl[8] = x;
    }
    __syncthreads();
#pragma unroll
    for (int e = 0; e < 12; e++) {
        if (rk[e] != 0xffffffffu) {
            int pos = binOff[rk[e] >> 16] + (int)(rk[e] & 0xffffu);
            sts128(sb + P1_STAGE + pos * 16, make_uint4(r0[e], r1[e], r2[e], 0u));
        }
    }
    fence_async_smem();
    __syncthreads();
    if (tid == 0) {
        const uint32_t bytes = (uint32_t)ctrl[8] * 16u;
        if (bytes) asm volatile("cp.async.bulk.global.shared::cta.bulk_group [%0], [%1], %2;"
                                ::"l"(g_rec + (size_t)cta * REC_CAP), "r"(sb + P1_STAGE), "r"(bytes) : "memory");
        asm volatile("cp.async.bulk.commit_group;" ::: "memory");
    }
    asm volatile("cp.async.bulk.wait_group 0;" ::: "memory");
    asm volatile("fence.proxy.async;" ::: "memory");

    __syncthreads();
    STAMP(4);
    unsigned bar_target = 0;
    if (tid == 0) {
        unsigned old;
        __threadfence();
        asm volatile("atom.add.release.gpu.global.u32 %0, [%1], 1;" : "=r"(old) : "l"(&g_bar) : "memory");
        bar_target = (old / (unsigned)p.ncta + 1u) * (unsigned)p.ncta;
    }
    if (tid == 0) {
        unsigned cur;
        int spins = 0;
        do {
            asm volatile("ld.acquire.gpu.global.u32 %0, [%1];" : "=r"(cur) : "l"(&g_bar) : "memory");
        } while ((int)(cur - bar_target) < 0 && ++spins < (1 << 24));
        asm volatile("fence.proxy.async;" ::: "memory");
    }
    __syncthreads();
    STAMP(5);

    if (warp == 0) {
        uint32_t v[5];
        int s = 0;
#pragma unroll
        for (int i = 0; i < 5; i++) {
            int b = lane * 5 + i;
            v[i] = b < p.ncta ? __ldcg(&g_offs[b * MAX_CTA + cta]) : 0u;
        }
#pragma unroll
        for (int i = 0; i < 5; i++) s += (int)(v[i] >> 16);
        int x = s;
#pragma unroll
        for (int o = 1; o < 32; o <<= 1) { int y = __shfl_up_sync(0xffffffffu, x, o); if (lane >= o) x += y; }
        const int total = __shfl_sync(0xffffffffu, x, 31);
        int off = x - s;
#pragma unroll
        for (int i = 0; i < 5; i++) {
            int b = lane * 5 + i;
            if (b < p.ncta) { binCnt[b] = (int)v[i]; binOff[b] = off; }
            off += (int)(v[i] >> 16);
        }
        if (lane == 0) {
            ctrl[8] = total;
            if (total > STAGE_CAP) ctrl[1] = 1;
            mbar_expect_tx(bar_rec, total > STAGE_CAP ? 0u : (uint32_t)total * 16u);
        }
    }
    __syncthreads();
    const int total = ctrl[8];
    if (ctrl[1] == 0) {
        const int b = (lane << 4) | warp;
        if (lane < 9 && b < p.ncta) {
            const uint32_t v = (uint32_t)binCnt[b], c = v >> 16;
            if (c) {
                asm volatile("fence.proxy.async;" ::: "memory");
                bulk_g2s(sb + SM_STAGE2 + (uint32_t)binOff[b] * 16u, g_rec + (size_t)b * REC_CAP + (v & 0xffffu), c * 16u, bar_rec);
            }
        }
    }
    mbar_wait(bar_rec, 0);
    if (ctrl[1] == 0) {
        for (int i = tid; i < total; i += NT) {
            uint32_t dl = lds32(sb + SM_STAGE2 + i * 16 + 8) >> 16;
            sts32(sb + SM_STAGE2 + i * 16 + 12, (uint32_t)atomicAdd(&nCnt[dl], 1));
        }
    }
    __syncthreads();
    if (warp == 0) {
        int c[3], s = 0;
#pragma unroll
        for (int i = 0; i < 3; i++) {
            int b = lane * 3 + i;
            c[i] = b < nnodes ? max(16, (nCnt[b] + 15) & ~15) : 0;
            s += c[i];
        }
        int x = s;
#pragma unroll
        for (int o = 1; o < 32; o <<= 1) { int y = __shfl_up_sync(0xffffffffu, x, o); if (lane >= o) x += y; }
        const int slots = __shfl_sync(0xffffffffu, x, 31);
        int off = x - s, below = 0;
#pragma unroll
        for (int i = 0; i < 3; i++) {
            int b = lane * 3 + i;
            if (b < nnodes) {
                nInfo[b] = (uint32_t)off | ((uint32_t)c[i] << 16);
                below += (2 * off + c[i] < slots);
            }
            off += c[i];
        }
        below = __reduce_add_sync(0xffffffffu, below);
        if (lane == 0) {
            ctrl[2] = below;
            ctrl[4] = slots;
            if (slots > SLOT_CAP) ctrl[1] = 1;
        }
    }
    __syncthreads();
    if (ctrl[1] == 0) {
        uint16_t* sid = (uint16_t*)(smem + SM_SID);
        uint2* meta = (uint2*)(smem + SM_META);
        for (int i = tid; i < total; i += NT) {
            uint4 r = lds128(sb + SM_STAGE2 + i * 16);
            int pos = (int)(nInfo[r.z >> 16] & 0xffffu) + (int)r.w;
            sid[pos]  = (uint16_t)(r.x & 0xffffu);
            meta[pos] = make_uint2(((r.x >> 16) << 5) | (r.z << 16), r.y);
        }
        for (int i = tid; i < nnodes * 16; i += NT) {
            int nl = i >> 4, c = nCnt[nl];
            int j = (c & ~15) + (i & 15);
            if (j >= c && (j < 16 || (c & 15))) {
                int pos = (int)(nInfo[nl] & 0xffffu) + j;
                sid[pos]  = 0xffffu;
                meta[pos] = make_uint2((uint32_t)TAB_ZERO << 5, 0u);
            }
        }
    }
    __syncthreads();
    for (int i = SM_RING4 / 16 + tid; i < SM_HT / 16; i += NT)
        if (i * 16 >= SM_META + ctrl[4] * 8) sts128(sb + i * 16, make_uint4(0u, 0u, 0u, 0u));
    fence_async_smem();
    __syncthreads();
    STAMP(6);

    if (__shfl_sync(0xffffffffu, ctrl[1], 0) != 0) {
        float* acc = (float*)(smem + P1_POS);
        for (int i = tid; i < nnodes * 256; i += NT) acc[i] = 0.f;
        __syncthreads();
        const uint16_t* posu = (const uint16_t*)p.pos;
        const uint32_t* tabg = (const uint32_t*)g_table;
        const uint32_t* Fw = (const uint32_t*)g_F;
        for (int e0 = warp * 32; e0 < p.E; e0 += NT) {
            int e = e0 + lane;
            int s = 0, d = 0;
            uint32_t db = 0xffff, rxy = 0, rz = 0;
            bool act = false;
            if (e < p.E) {
                s = p.src[e]; d = p.dst[e];
                if (d >= node0 && d < node0 + nnodes) {
                    uint32_t sxy = posu[s * 3] | ((uint32_t)posu[s * 3 + 1] << 16), sz = posu[s * 3 + 2];
                    uint32_t dxy = posu[d * 3] | ((uint32_t)posu[d * 3 + 1] << 16), dz = posu[d * 3 + 2];
                    db  = edge_dist(sxy, sz, dxy, dz, rxy, rz);
                    act = db <= D_MAX_BITS;
                }
            }
            unsigned m = __ballot_sync(0xffffffffu, act);
            while (m) {
                int l = __ffs(m) - 1;
                m &= m - 1;
                int es = __shfl_sync(0xffffffffu, s, l), ed = __shfl_sync(0xffffffffu, d, l);
                uint32_t edb = __shfl_sync(0xffffffffu, db, l), exy = __shfl_sync(0xffffffffu, rxy, l), ez = __shfl_sync(0xffffffffu, rz, l);
                float inv = 1.0f / __uint_as_float(edb << 16);
                float rh[3] = {rbf(bf_lo(exy) * inv), rbf(bf_hi(exy) * inv), rbf(bf_lo(ez) * inv)};
                const uint32_t* fr = Fw + (size_t)es * 128 + lane;
                const uint32_t fh = __ldcg(fr);
                const uint32_t q[3] = {__ldcg(fr + 32), __ldcg(fr + 64), __ldcg(fr + 96)};
                float ps0 = 0.f, ps1 = 0.f, pr0 = 0.f, pr1 = 0.f;
                for (int j2 = 0; j2 < 32; j2++) {
                    uint32_t hj = __shfl_sync(0xffffffffu, fh, j2);
                    uint32_t a0 = *(const uint32_t*)(p.w2 + (2 * j2) * 192 + 2 * lane), a1 = *(const uint32_t*)(p.w2 + (2 * j2 + 1) * 192 + 2 * lane);
                    uint32_t b0 = *(const uint32_t*)(p.w2 + (2 * j2) * 192 + 128 + 2 * lane), b1 = *(const uint32_t*)(p.w2 + (2 * j2 + 1) * 192 + 128 + 2 * lane);
                    ps0 += bf_lo(hj) * bf_lo(a0) + bf_hi(hj) * bf_lo(a1);
                    ps1 += bf_lo(hj) * bf_hi(a0) + bf_hi(hj) * bf_hi(a1);
                    pr0 += bf_lo(hj) * bf_lo(b0) + bf_hi(hj) * bf_lo(b1);
                    pr1 += bf_lo(hj) * bf_hi(b0) + bf_hi(hj) * bf_hi(b1);
                }
                float ws0 = 0.f, ws1 = 0.f, wv0 = 0.f, wv1 = 0.f, wr0 = 0.f, wr1 = 0.f;
                for (int k2 = 0; k2 < 8; k2++) {
                    uint32_t rk2 = __ldcg(tabg + (edb - D_MIN_BITS) * 8 + k2);
#pragma unroll
                    for (int h = 0; h < 2; h++) {
                        float rv = h ? bf_hi(rk2) : bf_lo(rk2);
                        const __nv_bfloat16* wrow = p.wr + (2 * k2 + h) * 192 + 2 * lane;
                        uint32_t a = *(const uint32_t*)wrow, b = *(const uint32_t*)(wrow + 64), c = *(const uint32_t*)(wrow + 128);
                        ws0 += rv * bf_lo(a); ws1 += rv * bf_hi(a);
                        wv0 += rv * bf_lo(b); wv1 += rv * bf_hi(b);
                        wr0 += rv * bf_lo(c); wr1 += rv * bf_hi(c);
                    }
                }
                float* a = acc + (ed - node0) * 256 + 2 * lane;
                atomicAdd(a, ps0 * ws0); atomicAdd(a + 1, ps1 * ws1);
#pragma unroll
                for (int c = 0; c < 3; c++) {
                    atomicAdd(a + 64 * (c + 1), wv0 * bf_lo(q[c]) + pr0 * wr0 * rh[c]);
                    atomicAdd(a + 64 * (c + 1) + 1, wv1 * bf_hi(q[c]) + pr1 * wr1 * rh[c]);
                }
            }
        }
        __syncthreads();
        for (int i = tid; i < nnodes * 128; i += NT) {
            uint32_t r = *(const uint32_t*)(p.sv + (size_t)node0 * 256 + 2 * i);
            *(uint32_t*)(p.out + (size_t)node0 * 256 + 2 * i) = pack_bf(bf_lo(r) + acc[2 * i], bf_hi(r) + acc[2 * i + 1]);
        }
        return;
    }

    const int slots = __reduce_max_sync(0xffffffffu, ctrl[4]);
    const int split = __reduce_max_sync(0xffffffffu, ctrl[2]);
    const int nstage = slots <= SLOT_CAP4 ? 6 : 5;
    const uint32_t ring = sb + (nstage == 6 ? SM_RING4 : SM_RING3);
    const int mid = __reduce_max_sync(0xffffffffu, split < nnodes ? (int)(nInfo[split] & 0xffffu) : slots) >> 4;
    if (warp >= 4 * NCWG) {
        asm volatile("setmaxnreg.dec.sync.aligned.u32 48;");
        const int wg = (warp - 4 * NCWG) >> 2, r = warp & 3;
        const int g0 = wg == 0 ? 0 : mid, g1 = wg == 0 ? mid : slots >> 4;
        const int e = lane >> 1, half = lane & 1;
        const uint32_t coef_off = e * 128 + ((half ^ (e & 7)) << 4);
        const int vrot = (e & 3) ^ ((e >> 1) & 3);
        const uint8_t* tab = (const uint8_t*)g_table + half * 16;
        int stage = r, phase = 1;
        for (int gi = g0 + r; gi < g1; gi += 4) {
            const uint32_t st = ring + (wg * nstage + stage) * STAGE_B;
            const uint32_t fb = bar_full + (wg * MAX_STAGE + stage) * 8;
            const uint2 m = lds64(sb + SM_META + (gi * 16 + e) * 8);
            const uint4 ia = lds128(sb + SM_SID + gi * 32), ib = lds128(sb + SM_SID + gi * 32 + 16);
            const uint4 tv = __ldg((const uint4*)(tab + (m.x & 0xffffu)));
            const uint32_t id2[8] = {ia.x, ia.y, ia.z, ia.w, ib.x, ib.y, ib.z, ib.w};
            const int nv = __popc(__ballot_sync(0xffffffffu, (m.x & 0xffffu) != (uint32_t)(TAB_ZERO << 5))) >> 1;
            mbar_wait(bar_empty + (wg * MAX_STAGE + stage) * 8, phase);
            uint32_t leader;
            asm volatile("{\n.reg .pred p;\nelect.sync _|p, 0xffffffff;\nselp.u32 %0, 1, 0, p;\n}" : "=r"(leader));
            if (leader) {
                if (nv == 16) {
#pragma unroll
                    for (int i = 0; i < 8; i++) {
                        tma_load(st + 2048 + (2 * i) * 640, &tmF, (int)(id2[i] & 0xffffu) * 4, fb);
                        tma_load(st + 2048 + (2 * i + 1) * 640, &tmF, (int)(id2[i] >> 16) * 4, fb);
                    }
                } else {
                    for (int i = 0; i < nv; i++)
                        tma_load(st + 2048 + i * 640, &tmF, (int)lds16(sb + SM_SID + (gi * 16 + i) * 2) * 4, fb);
                }
            }
            __syncwarp();
            const uint32_t mul[4] = {0x3f803f80u, __byte_perm(m.y, 0, 0x1010), __byte_perm(m.y, 0, 0x3232), __byte_perm(m.x, 0, 0x3232)};
            const uint32_t a = st + coef_off;
#pragma unroll
            for (int j = 0; j < 4; j++) {
                const int v = j ^ vrot;
                const uint32_t lo = (v & 1) ? mul[1] : mul[0], hi = (v & 1) ? mul[3] : mul[2];
                const uint32_t mm = (v & 2) ? hi : lo;
                sts128(a ^ (v << 5), make_uint4(hmul2(tv.x, mm), hmul2(tv.y, mm), hmul2(tv.z, mm), hmul2(tv.w, mm)));
            }
            fence_async_smem();
            __syncwarp();
            if (lane == 0) mbar_expect_tx(fb, (uint32_t)nv * 512u);
            stage += 4;
            if (stage >= nstage) { stage -= nstage; phase ^= 1; }
        }
    } else {
        asm volatile("setmaxnreg.inc.sync.aligned.u32 208;");
        const int wg = warp >> 2, w = warp & 3;
        const int n_end = wg == 0 ? split : nnodes;
        uint32_t wA[2][4][4];
        uint32_t wp[3][4];
        {
            const uint16_t* w2 = (const uint16_t*)p.w2 + 16 * w + g;
#pragma unroll
            for (int m = 0; m < 2; m++) {
#pragma unroll
                for (int ks = 0; ks < 4; ks++) {
#pragma unroll
                    for (int i = 0; i < 4; i++) {
                        const uint16_t* q = w2 + (16 * ks + 2 * t + 8 * (i >> 1)) * 192 + m * 128 + 8 * (i & 1);
                        wA[m][ks][i] = (uint32_t)__ldg(q) | ((uint32_t)__ldg(q + 192) << 16);
                    }
                }
            }
            const uint16_t* wr = (const uint16_t*)p.wr + 16 * w + g;
#pragma unroll
            for (int ty = 0; ty < 3; ty++) {
#pragma unroll
                for (int i = 0; i < 4; i++) {
                    const uint16_t* q = wr + (8 * (i >> 1) + 2 * t) * 192 + ty * 64 + 8 * (i & 1);
                    wp[ty][i] = (uint32_t)__ldg(q) | ((uint32_t)__ldg(q + 192) << 16);
                }
            }
        }
        uint32_t aoff[4];
        {
            const int e = (lane & 7) + 8 * (lane >> 4), ch = 2 * w + ((lane >> 3) & 1);
#pragma unroll
            for (int b = 0; b < 4; b++) aoff[b] = 2048 + e * 640 + b * 128 + ((ch ^ ((5 * e + b) & 7)) << 4);
        }
        const uint32_t ht = sb + SM_HT + wg * 8192;
        const uint32_t stsm_a = ht + (16 * w + (lane & 15)) * 128 + (((lane >> 4) ^ (lane & 7)) << 4);
        const uint32_t dht = desc_lo(ht);
        const uint32_t out_lane = (uint32_t)node0 * 512u + t * 128 + (16 * w + (g & 1) * 8 + (g & 6)) * 2;
        const uint32_t ring_wg = ring + wg * nstage * STAGE_B;
        const uint32_t full_wg = bar_full + wg * MAX_STAGE * 8, empty_wg = bar_empty + wg * MAX_STAGE * 8;

        float ys[8], yv[24], dQ[3][8];
        float zs[8], zv[24], pv[3][2];
        uint32_t A0[4][4], A1[4][4];
        int left = wg == 0 ? mid : (slots >> 4) - mid;
        int fstage = 0, fphase = 0;
        int cstage = 0;
        int nl = wg == 0 ? 0 : split, gi = 0, G = 0, pend = -1;
        uint32_t resid = 0, resid_p = 0, resid_q = 0;

        auto fetch = [&](uint32_t (&A)[4][4]) {
            const uint32_t st = ring_wg + fstage * STAGE_B;
            mbar_wait(full_wg + fstage * 8, fphase);
#pragma unroll
            for (int b = 0; b < 4; b++) ldsm4t(A[b], st + aoff[b]);
            if (++fstage == nstage) { fstage = 0; fphase ^= 1; }
        };
        auto node_begin = [&]() {
            G = __reduce_max_sync(0xffffffffu, (int)(nInfo[nl] >> 20));
            resid = __ldg((const uint32_t*)((const uint8_t*)p.sv + (out_lane + (uint32_t)nl * 512u)));
            gi = 0;
        };
        float pr[4][2];
        int pend2 = -1;
        auto weigh = [&]() {
#pragma unroll
            for (int i = 0; i < 12; i++) asm volatile("" : "+r"(wp[i >> 2][i & 3]));
            pr[0][0] = bf_lo(wp[0][0]) * zs[0] + bf_hi(wp[0][0]) * zs[1] + bf_lo(wp[0][2]) * zs[4] + bf_hi(wp[0][2]) * zs[5];
            pr[0][1] = bf_lo(wp[0][1]) * zs[2] + bf_hi(wp[0][1]) * zs[3] + bf_lo(wp[0][3]) * zs[6] + bf_hi(wp[0][3]) * zs[7];
#pragma unroll
            for (int a = 0; a < 3; a++) {
                const float* y = zv + 8 * a;
                pr[a + 1][0] = pv[a][0] + bf_lo(wp[2][0]) * y[0] + bf_hi(wp[2][0]) * y[1] + bf_lo(wp[2][2]) * y[4] + bf_hi(wp[2][2]) * y[5];
                pr[a + 1][1] = pv[a][1] + bf_lo(wp[2][1]) * y[2] + bf_hi(wp[2][1]) * y[3] + bf_lo(wp[2][3]) * y[6] + bf_hi(wp[2][3]) * y[7];
            }
            pend2 = pend;
            resid_q = resid_p;
            pend = -1;
        };
        auto finish = [&]() {
            const bool hi2 = t & 2, hi1 = t & 1, odd = g & 1;
            float ka0 = hi2 ? pr[2][0] : pr[0][0], ka1 = hi2 ? pr[2][1] : pr[0][1];
            float kb0 = hi2 ? pr[3][0] : pr[1][0], kb1 = hi2 ? pr[3][1] : pr[1][1];
            float sa0 = hi2 ? pr[0][0] : pr[2][0], sa1 = hi2 ? pr[0][1] : pr[2][1];
            float sb0 = hi2 ? pr[1][0] : pr[3][0], sb1 = hi2 ? pr[1][1] : pr[3][1];
            ka0 += __shfl_xor_sync(0xffffffffu, sa0, 2); ka1 += __shfl_xor_sync(0xffffffffu, sa1, 2);
            kb0 += __shfl_xor_sync(0xffffffffu, sb0, 2); kb1 += __shfl_xor_sync(0xffffffffu, sb1, 2);
            float k0 = hi1 ? kb0 : ka0, k1 = hi1 ? kb1 : ka1;
            float s0 = hi1 ? ka0 : kb0, s1 = hi1 ? ka1 : kb1;
            k0 += __shfl_xor_sync(0xffffffffu, s0, 1);
            k1 += __shfl_xor_sync(0xffffffffu, s1, 1);
            const float other = __shfl_xor_sync(0xffffffffu, odd ? k0 : k1, 4);
            const float lo = odd ? other : k0, hi = odd ? k1 : other;
            *(uint32_t*)((uint8_t*)p.out + (out_lane + (uint32_t)pend2 * 512u)) = pack_bf(bf_lo(resid_q) + lo, bf_hi(resid_q) + hi);
            pend2 = -1;
        };
        auto step = [&](uint32_t (&Ac)[4][4], uint32_t (&An)[4][4]) {
            const uint32_t bd = desc_lo(ring_wg + cstage * STAGE_B);
            wg_fence();
            if (gi == 0) {
                wgmma_n64_first(ys, yv, Ac[0], bd);
                wgmma_n16_first(dQ[0], Ac[1], bd);
                wgmma_n16_first(dQ[1], Ac[2], bd);
                wgmma_n16_first(dQ[2], Ac[3], bd);
                wg_commit();
            } else {
                wgmma_n64(ys, yv, Ac[0], bd);
                wgmma_n16(dQ[0], Ac[1], bd);
                wgmma_n16(dQ[1], Ac[2], bd);
                wgmma_n16(dQ[2], Ac[3], bd);
                wg_commit();
            }
            if (pend2 >= 0) finish();
            if (--left > 0) fetch(An);
            wg_wait0();
            if (lane == 0) mbar_arrive(empty_wg + cstage * 8);
            if (++cstage == nstage) cstage = 0;
            if (pend >= 0) weigh();
            if (++gi == G) {
                named_barrier(1 + wg);
                uint32_t sa = stsm_a;
                asm volatile("" : "+r"(sa));
                stsm4(sa, pack_bf(ys[0], ys[1]), pack_bf(ys[2], ys[3]), pack_bf(ys[4], ys[5]), pack_bf(ys[6], ys[7]));
#pragma unroll
                for (int i = 0; i < 6; i += 2) {
                    stsm4(sa ^ ((i + 2) << 4),
                          pack_bf(yv[4 * i], yv[4 * i + 1]), pack_bf(yv[4 * i + 2], yv[4 * i + 3]),
                          pack_bf(yv[4 * i + 4], yv[4 * i + 5]), pack_bf(yv[4 * i + 6], yv[4 * i + 7]));
                }
                fence_async_smem();
#pragma unroll
                for (int i = 0; i < 4; i++) asm volatile("" : "+r"(wp[1][i]));
#pragma unroll
                for (int a = 0; a < 3; a++) {
                    const float* q = dQ[a];
                    pv[a][0] = bf_lo(wp[1][0]) * q[0] + bf_hi(wp[1][0]) * q[1] + bf_lo(wp[1][2]) * q[4] + bf_hi(wp[1][2]) * q[5];
                    pv[a][1] = bf_lo(wp[1][1]) * q[2] + bf_hi(wp[1][1]) * q[3] + bf_lo(wp[1][3]) * q[6] + bf_hi(wp[1][3]) * q[7];
                }
                named_barrier(1 + wg);
                wg_fence();
                wgmma_n16_first(zs, wA[0][0], dht);
                wgmma_n48_first(zv, wA[1][0], dht + 2);
#pragma unroll
                for (int ks = 1; ks < 4; ks++) {
                    wgmma_n16(zs, wA[0][ks], dht + ks * 128);
                    wgmma_n48(zv, wA[1][ks], dht + ks * 128 + 2);
                }
                wg_commit();
                pend = nl;
                resid_p = resid;
                if (++nl < n_end) node_begin();
            }
        };
        if (left > 0) {
            node_begin();
            fetch(A0);
            while (true) {
                step(A0, A1);
                if (left <= 0) break;
                step(A1, A0);
                if (left <= 0) break;
            }
            if (pend2 >= 0) finish();
            wg_wait0();
            weigh();
            finish();
        }
    }
    STAMP(8);
}

typedef CUresult (*EncodeFn)(CUtensorMap*, CUtensorMapDataType, cuuint32_t, void*, const cuuint64_t*, const cuuint64_t*,
                             const cuuint32_t*, const cuuint32_t*, CUtensorMapInterleave, CUtensorMapSwizzle,
                             CUtensorMapL2promotion, CUtensorMapFloatOOBfill);

void make_map(EncodeFn enc, CUtensorMap* tm, const void* base, uint64_t lines, uint32_t box) {
    cuuint64_t gd[2] = {64, lines};
    cuuint64_t gs[1] = {128};
    cuuint32_t bd[2] = {64, box};
    cuuint32_t es[2] = {1, 1};
    enc(tm, CU_TENSOR_MAP_DATA_TYPE_BFLOAT16, 2, const_cast<void*>(base), gd, gs, bd, es, CU_TENSOR_MAP_INTERLEAVE_NONE,
        CU_TENSOR_MAP_SWIZZLE_128B, CU_TENSOR_MAP_L2_PROMOTION_L2_128B, CU_TENSOR_MAP_FLOAT_OOB_FILL_NONE);
}

}

extern "C" void kernel_launch(void* const* d_in, const int* in_sizes, int n_in, void* d_out, int out_size) {
    (void)n_in; (void)out_size;
    static int n_sm = 0;
    static EncodeFn enc = nullptr;
    static void* f_ptr = nullptr;
    if (n_sm == 0) {
        int dev = 0;
        cudaGetDevice(&dev);
        cudaDeviceGetAttribute(&n_sm, cudaDevAttrMultiProcessorCount, dev);
        cudaFuncSetAttribute(painn_kernel, cudaFuncAttributeMaxDynamicSharedMemorySize, SM_TOTAL);
        void* fn = nullptr;
        cudaDriverEntryPointQueryResult qr;
        cudaGetDriverEntryPoint("cuTensorMapEncodeTiled", &fn, cudaEnableDefault, &qr);
        enc = (EncodeFn)fn;
        cudaGetSymbolAddress(&f_ptr, g_F);
    }
    Params p;
    p.sv    = (const __nv_bfloat16*)d_in[0];
    p.pos   = (const __nv_bfloat16*)d_in[1];
    p.src   = (const int*)d_in[2];
    p.dst   = (const int*)d_in[3];
    p.freqs = (const __nv_bfloat16*)d_in[4];
    p.w1    = (const __nv_bfloat16*)d_in[5];
    p.w2    = (const __nv_bfloat16*)d_in[6];
    p.wr    = (const __nv_bfloat16*)d_in[7];
    p.out   = (__nv_bfloat16*)d_out;
    p.N = in_sizes[1] / 3;
    p.E = in_sizes[2];
    p.ncta = n_sm < MAX_CTA ? n_sm : MAX_CTA;
    p.npc = (p.N + p.ncta - 1) / p.ncta;
    p.npc_magic = (uint32_t)(0x100000000ull / (uint32_t)p.npc) + 1u;
    p.quads_per_cta = ((p.E >> 2) + p.ncta - 1) / p.ncta;
    if (!enc || p.N > MAX_N || p.npc > MAX_NPC || (p.E & 3) || p.quads_per_cta > MAX_ROUNDS * 32) return;

    CUtensorMap tmF, tmSV, tmW1, tmW2;
    make_map(enc, &tmF, f_ptr, (uint64_t)p.N * 4, 4);
    make_map(enc, &tmSV, p.sv, (uint64_t)p.N * 4, 160);
    make_map(enc, &tmW1, p.w1, 64, 64);
    make_map(enc, &tmW2, p.w2, 192, 192);

    cudaLaunchConfig_t cfg = {};
    cfg.gridDim = dim3(p.ncta);
    cfg.blockDim = dim3(NT);
    cfg.dynamicSmemBytes = SM_TOTAL;
    cfg.stream = cudaStreamPerThread;
    cudaLaunchAttribute attr[1];
    attr[0].id = cudaLaunchAttributeCooperative;
    attr[0].val.cooperative = 1;
    cfg.attrs = attr;
    cfg.numAttrs = 1;
    cudaLaunchKernelEx(&cfg, painn_kernel, p, tmF, tmSV, tmW1, tmW2);
}
```

```cpp
#include <cuda_runtime.h>
#include <cuda.h>
#include <cuda_bf16.h>
#include <stdint.h>

namespace {

constexpr int NT        = 512;
constexpr int NCWG      = 2;
constexpr int MAX_N     = 10240;
constexpr int MAX_CTA   = 144;
constexpr int MAX_NPC   = 80;
constexpr int MAX_ROUNDS = 38;
constexpr int REC_CAP   = MAX_ROUNDS * 128;
constexpr int SLOT_CAP  = 6144;
constexpr int MAX_STAGE = 6;
constexpr int STAGE_B   = 12288;

constexpr uint32_t D_MIN_BITS = 0x38D2;
constexpr uint32_t D_MAX_BITS = 0x409C;
constexpr int TAB_ROWS  = (int)(D_MAX_BITS - D_MIN_BITS) + 1;
constexpr int TAB_ZERO  = TAB_ROWS;
constexpr int TAB_BYTES = (TAB_ROWS + 1) * 32;

constexpr int SM_BINCNT = 0;
constexpr int SM_BINOFF = SM_BINCNT + MAX_CTA * 4;
constexpr int SM_NCNT   = SM_BINOFF + MAX_CTA * 4;
constexpr int SM_NINFO  = SM_NCNT + MAX_NPC * 4;
constexpr int SM_CTRL   = SM_NINFO + MAX_NPC * 4;
constexpr int SM_BARS   = SM_CTRL + 64;
constexpr int SM_SID    = 2048 + 128;
constexpr int SM_META   = SM_SID + SLOT_CAP * 2;
constexpr int SM_TOTAL  = 232448;
constexpr int SM_HT     = (SM_TOTAL - NCWG * 8192) / 1024 * 1024;
constexpr int SM_RING4  = SM_HT - NCWG * 6 * STAGE_B;
constexpr int SM_RING3  = SM_HT - NCWG * 5 * STAGE_B;
constexpr int SLOT_CAP4 = (SM_RING4 - SM_META) / 8;
constexpr int SM_STAGE2 = SM_RING3 - 0;
constexpr int STAGE_CAP = (SM_HT - SM_RING3) / 16;
constexpr int P1_POS    = 3072;
constexpr int P1_STAGE  = P1_POS + 61440;
constexpr int P1_SV     = (P1_STAGE + REC_CAP * 16 + 1023) / 1024 * 1024;
constexpr int P1_W1     = P1_SV + MAX_NPC * 512;
constexpr int P1_W2     = P1_W1 + 8192;
constexpr int P1_END    = P1_W2 + 24576;
static_assert(SM_BARS + (4 + 2 * NCWG * MAX_STAGE) * 8 <= SM_SID, "misc block");
static_assert(SM_BARS + 256 <= P1_POS, "misc block");
static_assert(P1_END <= SM_TOTAL, "phase 1 overlay");
static_assert(SM_META + SLOT_CAP * 8 <= SM_RING3, "CSR");
static_assert(SM_RING4 % 1024 == 0 && SM_RING3 % 1024 == 0 && SM_HT % 1024 == 0, "alignment");
static_assert(SM_BARS % 8 == 0 && SM_META % 8 == 0, "alignment");
static_assert(MAX_N * 6 <= 61440, "pos");
static_assert(SM_SID + MAX_NPC * 1024 <= SM_TOTAL, "slow path accumulators");

__device__ __align__(1024) uint4 g_F[MAX_N * 32];
__device__ uint4    g_rec[MAX_CTA * REC_CAP];
__device__ uint32_t g_offs[MAX_CTA * MAX_CTA];
__device__ uint4    g_table[(TAB_BYTES + 15) / 16];
__device__ unsigned g_bar[2];
#define STAMP(k)
#define STAMPT(k, T)
#define ITS(k)

struct Params {
    const __nv_bfloat16* sv;
    const __nv_bfloat16* pos;
    const int*           src;
    const int*           dst;
    const __nv_bfloat16* freqs;
    const __nv_bfloat16* w1;
    const __nv_bfloat16* w2;
    const __nv_bfloat16* wr;
    __nv_bfloat16*       out;
    int N, E, ncta, npc;
    uint32_t npc_magic;
    int quads_per_cta;
};

__device__ __forceinline__ uint32_t smem_u32(const void* p) { return (uint32_t)__cvta_generic_to_shared(p); }
__device__ __forceinline__ float bf_lo(uint32_t v) { return __uint_as_float(v << 16); }
__device__ __forceinline__ float bf_hi(uint32_t v) { return __uint_as_float(v & 0xffff0000u); }
__device__ __forceinline__ float bf_u16(uint16_t v) { return __uint_as_float((uint32_t)v << 16); }
__device__ __forceinline__ uint32_t pack_bf(float lo, float hi) {
    uint32_t r;
    asm("cvt.rn.bf16x2.f32 %0, %1, %2;" : "=r"(r) : "f"(hi), "f"(lo));
    return r;
}
__device__ __forceinline__ float rbf(float x) { return bf_lo(pack_bf(x, 0.f)); }
__device__ __forceinline__ uint32_t hmul2(uint32_t a, uint32_t b) {
    uint32_t r;
    asm("mul.rn.bf16x2 %0, %1, %2;" : "=r"(r) : "r"(a), "r"(b));
    return r;
}
__device__ __forceinline__ uint32_t hsub2(uint32_t a, uint32_t b) {
    uint32_t r;
    asm("sub.rn.bf16x2 %0, %1, %2;" : "=r"(r) : "r"(a), "r"(b));
    return r;
}
__device__ __forceinline__ uint32_t lds32(uint32_t a) { uint32_t v; asm volatile("ld.shared.u32 %0, [%1];" : "=r"(v) : "r"(a)); return v; }
__device__ __forceinline__ uint32_t lds16(uint32_t a) { uint16_t v; asm volatile("ld.shared.u16 %0, [%1];" : "=h"(v) : "r"(a)); return v; }
__device__ __forceinline__ uint2 lds64(uint32_t a) { uint2 v; asm volatile("ld.shared.v2.u32 {%0,%1}, [%2];" : "=r"(v.x), "=r"(v.y) : "r"(a)); return v; }
__device__ __forceinline__ uint4 lds128(uint32_t a) { uint4 v; asm volatile("ld.shared.v4.u32 {%0,%1,%2,%3}, [%4];" : "=r"(v.x), "=r"(v.y), "=r"(v.z), "=r"(v.w) : "r"(a)); return v; }
__device__ __forceinline__ void sts32(uint32_t a, uint32_t v) { asm volatile("st.shared.u32 [%0], %1;" ::"r"(a), "r"(v) : "memory"); }
__device__ __forceinline__ void sts128(uint32_t a, uint4 v) { asm volatile("st.shared.v4.u32 [%0], {%1,%2,%3,%4};" ::"r"(a), "r"(v.x), "r"(v.y), "r"(v.z), "r"(v.w) : "memory"); }
__device__ __forceinline__ void mbar_init(uint32_t bar, int cnt) { asm volatile("mbarrier.init.shared::cta.b64 [%0], %1;" ::"r"(bar), "r"(cnt) : "memory"); }
__device__ __forceinline__ void mbar_expect_tx(uint32_t bar, uint32_t bytes) { asm volatile("mbarrier.arrive.expect_tx.shared::cta.b64 _, [%0], %1;" ::"r"(bar), "r"(bytes) : "memory"); }
__device__ __forceinline__ void mbar_arrive(uint32_t bar) { asm volatile("mbarrier.arrive.shared::cta.b64 _, [%0];" ::"r"(bar) : "memory"); }
__device__ __forceinline__ void mbar_wait(uint32_t bar, uint32_t parity) {
    asm volatile("{\n.reg .pred p;\n.reg .u32 c;\n"
                 "mbarrier.try_wait.parity.shared::cta.b64 p, [%0], %1;\n"
                 "@p bra DONE_%=;\n"
                 "mov.u32 c, 0;\n"
                 "LOOP_%=:\n"
                 "mbarrier.try_wait.parity.shared::cta.b64 p, [%0], %1;\n"
                 "@p bra DONE_%=;\n"
                 "add.u32 c, c, 1;\n"
                 "setp.lt.u32 p, c, 4194304;\n"
                 "@p bra LOOP_%=;\n"
                 "DONE_%=:\n}"
                 ::"r"(bar), "r"(parity) : "memory");
}
__device__ __forceinline__ void mbar_arrive_elected(uint32_t bar) {
    asm volatile("{\n.reg .pred p;\nelect.sync _|p, 0xffffffff;\n@p mbarrier.arrive.shared::cta.b64 _, [%0];\n}" ::"r"(bar) : "memory");
}
__device__ __forceinline__ void bulk_g2s(uint32_t dst, const void* src, uint32_t bytes, uint32_t bar) {
    asm volatile("cp.async.bulk.shared::cluster.global.mbarrier::complete_tx::bytes [%0], [%1], %2, [%3];"
                 ::"r"(dst), "l"(src), "r"(bytes), "r"(bar) : "memory");
}
__device__ __forceinline__ void tma_load(uint32_t dst, const CUtensorMap* tm, int line, uint32_t bar) {
    asm volatile("cp.async.bulk.tensor.2d.shared::cluster.global.mbarrier::complete_tx::bytes [%0], [%1, {%3, %4}], [%2];"
                 ::"r"(dst), "l"(tm), "r"(bar), "r"(0), "r"(line) : "memory");
}
__device__ __forceinline__ void tma_store(const CUtensorMap* tm, int line, uint32_t src) {
    asm volatile("cp.async.bulk.tensor.2d.global.shared::cta.bulk_group [%0, {%2, %3}], [%1];"
                 ::"l"(tm), "r"(src), "r"(0), "r"(line) : "memory");
}
__device__ __forceinline__ void fence_async_smem() { asm volatile("fence.proxy.async.shared::cta;" ::: "memory"); }
__device__ __forceinline__ void named_barrier(int id) { asm volatile("bar.sync %0, 128;" ::"r"(id) : "memory"); }
__device__ __forceinline__ void ldsm4(uint32_t (&r)[4], uint32_t a) {
    asm volatile("ldmatrix.sync.aligned.m8n8.x4.shared.b16 {%0,%1,%2,%3}, [%4];" : "=r"(r[0]), "=r"(r[1]), "=r"(r[2]), "=r"(r[3]) : "r"(a) : "memory");
}
__device__ __forceinline__ void ldsm4t(uint32_t (&r)[4], uint32_t a) {
    asm volatile("ldmatrix.sync.aligned.m8n8.x4.trans.shared.b16 {%0,%1,%2,%3}, [%4];" : "=r"(r[0]), "=r"(r[1]), "=r"(r[2]), "=r"(r[3]) : "r"(a) : "memory");
}
__device__ __forceinline__ void stsm4(uint32_t a, uint32_t r0, uint32_t r1, uint32_t r2, uint32_t r3) {
    asm volatile("stmatrix.sync.aligned.m8n8.x4.shared.b16 [%0], {%1,%2,%3,%4};" ::"r"(a), "r"(r0), "r"(r1), "r"(r2), "r"(r3) : "memory");
}
__device__ __forceinline__ void mma16816(float (&c)[4], const uint32_t (&a)[4], uint32_t b0, uint32_t b1) {
    asm volatile("mma.sync.aligned.m16n8k16.row.col.f32.bf16.bf16.f32 {%0,%1,%2,%3}, {%4,%5,%6,%7}, {%8,%9}, {%0,%1,%2,%3};"
                 : "+f"(c[0]), "+f"(c[1]), "+f"(c[2]), "+f"(c[3])
                 : "r"(a[0]), "r"(a[1]), "r"(a[2]), "r"(a[3]), "r"(b0), "r"(b1));
}

__device__ __forceinline__ uint32_t desc_lo(uint32_t saddr) { return ((saddr & 0x3FFFF) >> 4) | (1u << 16); }
#define DESC_HI "0x40000040"
__device__ __forceinline__ void wg_fence() { asm volatile("wgmma.fence.sync.aligned;" ::: "memory"); }
__device__ __forceinline__ void wg_commit() { asm volatile("wgmma.commit_group.sync.aligned;" ::: "memory"); }
__device__ __forceinline__ void wg_wait0() { asm volatile("wgmma.wait_group.sync.aligned 0;" ::: "memory"); }
__device__ __forceinline__ void wg_wait1() { asm volatile("wgmma.wait_group.sync.aligned 1;" ::: "memory"); }

__device__ __forceinline__ void wgmma_n64_first(float (&d)[8], float (&e)[24], const uint32_t (&a)[4], uint32_t bdesc) {
    asm volatile("{\n.reg .b64 b;\nmov.b64 b, {%36, " DESC_HI "};\n"
                 "wgmma.mma_async.sync.aligned.m64n64k16.f32.bf16.bf16 {%0,%1,%2,%3,%4,%5,%6,%7,%8,%9,%10,%11,%12,%13,%14,%15,%16,%17,%18,%19,%20,%21,%22,%23,%24,%25,%26,%27,%28,%29,%30,%31}, {%32,%33,%34,%35}, b, 0, 1, 1, 1;\n}"
                 : "=f"(d[0]), "=f"(d[1]), "=f"(d[2]), "=f"(d[3]), "=f"(d[4]), "=f"(d[5]), "=f"(d[6]), "=f"(d[7]),
                   "=f"(e[0]), "=f"(e[1]), "=f"(e[2]), "=f"(e[3]), "=f"(e[4]), "=f"(e[5]), "=f"(e[6]), "=f"(e[7]), "=f"(e[8]), "=f"(e[9]), "=f"(e[10]), "=f"(e[11]), "=f"(e[12]), "=f"(e[13]), "=f"(e[14]), "=f"(e[15]), "=f"(e[16]), "=f"(e[17]), "=f"(e[18]), "=f"(e[19]), "=f"(e[20]), "=f"(e[21]), "=f"(e[22]), "=f"(e[23])
                 : "r"(a[0]), "r"(a[1]), "r"(a[2]), "r"(a[3]), "r"(bdesc));
}
__device__ __forceinline__ void wgmma_n64(float (&d)[8], float (&e)[24], const uint32_t (&a)[4], uint32_t bdesc) {
    asm volatile("{\n.reg .b64 b;\nmov.b64 b, {%36, " DESC_HI "};\n"
                 "wgmma.mma_async.sync.aligned.m64n64k16.f32.bf16.bf16 {%0,%1,%2,%3,%4,%5,%6,%7,%8,%9,%10,%11,%12,%13,%14,%15,%16,%17,%18,%19,%20,%21,%22,%23,%24,%25,%26,%27,%28,%29,%30,%31}, {%32,%33,%34,%35}, b, 1, 1, 1, 1;\n}"
                 : "+f"(d[0]), "+f"(d[1]), "+f"(d[2]), "+f"(d[3]), "+f"(d[4]), "+f"(d[5]), "+f"(d[6]), "+f"(d[7]),
                   "+f"(e[0]), "+f"(e[1]), "+f"(e[2]), "+f"(e[3]), "+f"(e[4]), "+f"(e[5]), "+f"(e[6]), "+f"(e[7]), "+f"(e[8]), "+f"(e[9]), "+f"(e[10]), "+f"(e[11]), "+f"(e[12]), "+f"(e[13]), "+f"(e[14]), "+f"(e[15]), "+f"(e[16]), "+f"(e[17]), "+f"(e[18]), "+f"(e[19]), "+f"(e[20]), "+f"(e[21]), "+f"(e[22]), "+f"(e[23])
                 : "r"(a[0]), "r"(a[1]), "r"(a[2]), "r"(a[3]), "r"(bdesc));
}
__device__ __forceinline__ void wgmma_n48_first(float (&e)[24], const uint32_t (&a)[4], uint32_t bdesc) {
    asm volatile("{\n.reg .b64 b;\nmov.b64 b, {%28, " DESC_HI "};\n"
                 "wgmma.mma_async.sync.aligned.m64n48k16.f32.bf16.bf16 {%0,%1,%2,%3,%4,%5,%6,%7,%8,%9,%10,%11,%12,%13,%14,%15,%16,%17,%18,%19,%20,%21,%22,%23}, {%24,%25,%26,%27}, b, 0, 1, 1, 1;\n}"
                 : "=f"(e[0]), "=f"(e[1]), "=f"(e[2]), "=f"(e[3]), "=f"(e[4]), "=f"(e[5]), "=f"(e[6]), "=f"(e[7]), "=f"(e[8]), "=f"(e[9]), "=f"(e[10]), "=f"(e[11]), "=f"(e[12]), "=f"(e[13]), "=f"(e[14]), "=f"(e[15]), "=f"(e[16]), "=f"(e[17]), "=f"(e[18]), "=f"(e[19]), "=f"(e[20]), "=f"(e[21]), "=f"(e[22]), "=f"(e[23])
                 : "r"(a[0]), "r"(a[1]), "r"(a[2]), "r"(a[3]), "r"(bdesc));
}
__device__ __forceinline__ void wgmma_n48(float (&e)[24], const uint32_t (&a)[4], uint32_t bdesc) {
    asm volatile("{\n.reg .b64 b;\nmov.b64 b, {%28, " DESC_HI "};\n"
                 "wgmma.mma_async.sync.aligned.m64n48k16.f32.bf16.bf16 {%0,%1,%2,%3,%4,%5,%6,%7,%8,%9,%10,%11,%12,%13,%14,%15,%16,%17,%18,%19,%20,%21,%22,%23}, {%24,%25,%26,%27}, b, 1, 1, 1, 1;\n}"
                 : "+f"(e[0]), "+f"(e[1]), "+f"(e[2]), "+f"(e[3]), "+f"(e[4]), "+f"(e[5]), "+f"(e[6]), "+f"(e[7]), "+f"(e[8]), "+f"(e[9]), "+f"(e[10]), "+f"(e[11]), "+f"(e[12]), "+f"(e[13]), "+f"(e[14]), "+f"(e[15]), "+f"(e[16]), "+f"(e[17]), "+f"(e[18]), "+f"(e[19]), "+f"(e[20]), "+f"(e[21]), "+f"(e[22]), "+f"(e[23])
                 : "r"(a[0]), "r"(a[1]), "r"(a[2]), "r"(a[3]), "r"(bdesc));
}
__device__ __forceinline__ void wgmma_n16_first(float (&d)[8], const uint32_t (&a)[4], uint32_t bdesc) {
    asm volatile("{\n.reg .b64 b;\nmov.b64 b, {%12, " DESC_HI "};\n"
                 "wgmma.mma_async.sync.aligned.m64n16k16.f32.bf16.bf16 {%0,%1,%2,%3,%4,%5,%6,%7}, {%8,%9,%10,%11}, b, 0, 1, 1, 1;\n}"
                 : "=f"(d[0]), "=f"(d[1]), "=f"(d[2]), "=f"(d[3]), "=f"(d[4]), "=f"(d[5]), "=f"(d[6]), "=f"(d[7])
                 : "r"(a[0]), "r"(a[1]), "r"(a[2]), "r"(a[3]), "r"(bdesc));
}
__device__ __forceinline__ void wgmma_n16(float (&d)[8], const uint32_t (&a)[4], uint32_t bdesc) {
    asm volatile("{\n.reg .b64 b;\nmov.b64 b, {%12, " DESC_HI "};\n"
                 "wgmma.mma_async.sync.aligned.m64n16k16.f32.bf16.bf16 {%0,%1,%2,%3,%4,%5,%6,%7}, {%8,%9,%10,%11}, b, 1, 1, 1, 1;\n}"
                 : "+f"(d[0]), "+f"(d[1]), "+f"(d[2]), "+f"(d[3]), "+f"(d[4]), "+f"(d[5]), "+f"(d[6]), "+f"(d[7])
                 : "r"(a[0]), "r"(a[1]), "r"(a[2]), "r"(a[3]), "r"(bdesc));
}

__device__ __forceinline__ void wgmma_n64_p(float (&d)[8], float (&e)[24], const uint32_t (&a)[4], uint32_t bdesc, int acc) {
    asm volatile("{\n.reg .pred p;\n.reg .b64 b;\nsetp.ne.b32 p, %37, 0;\nmov.b64 b, {%36, " DESC_HI "};\n"
                 "wgmma.mma_async.sync.aligned.m64n64k16.f32.bf16.bf16 {%0,%1,%2,%3,%4,%5,%6,%7,%8,%9,%10,%11,%12,%13,%14,%15,%16,%17,%18,%19,%20,%21,%22,%23,%24,%25,%26,%27,%28,%29,%30,%31}, {%32,%33,%34,%35}, b, p, 1, 1, 1;\n}"
                 : "+f"(d[0]), "+f"(d[1]), "+f"(d[2]), "+f"(d[3]), "+f"(d[4]), "+f"(d[5]), "+f"(d[6]), "+f"(d[7]),
                   "+f"(e[0]), "+f"(e[1]), "+f"(e[2]), "+f"(e[3]), "+f"(e[4]), "+f"(e[5]), "+f"(e[6]), "+f"(e[7]), "+f"(e[8]), "+f"(e[9]), "+f"(e[10]), "+f"(e[11]), "+f"(e[12]), "+f"(e[13]), "+f"(e[14]), "+f"(e[15]), "+f"(e[16]), "+f"(e[17]), "+f"(e[18]), "+f"(e[19]), "+f"(e[20]), "+f"(e[21]), "+f"(e[22]), "+f"(e[23])
                 : "r"(a[0]), "r"(a[1]), "r"(a[2]), "r"(a[3]), "r"(bdesc), "r"(acc));
}
__device__ __forceinline__ void wgmma_n16_p(float (&d)[8], const uint32_t (&a)[4], uint32_t bdesc, int acc) {
    asm volatile("{\n.reg .pred p;\n.reg .b64 b;\nsetp.ne.b32 p, %13, 0;\nmov.b64 b, {%12, " DESC_HI "};\n"
                 "wgmma.mma_async.sync.aligned.m64n16k16.f32.bf16.bf16 {%0,%1,%2,%3,%4,%5,%6,%7}, {%8,%9,%10,%11}, b, p, 1, 1, 1;\n}"
                 : "+f"(d[0]), "+f"(d[1]), "+f"(d[2]), "+f"(d[3]), "+f"(d[4]), "+f"(d[5]), "+f"(d[6]), "+f"(d[7])
                 : "r"(a[0]), "r"(a[1]), "r"(a[2]), "r"(a[3]), "r"(bdesc), "r"(acc));
}

__device__ __forceinline__ uint32_t edge_dist(uint32_t sxy, uint32_t sz, uint32_t dxy, uint32_t dz, uint32_t& rxy, uint32_t& rz) {
    rxy = hsub2(sxy, dxy);
    rz  = hsub2(sz, dz);
    uint32_t qxy = hmul2(rxy, rxy), qz = hmul2(rz, rz);
    float ss = rbf((bf_lo(qxy) + bf_hi(qxy)) + bf_lo(qz));
    float s2 = rbf(ss + 1e-8f);
    float d;
    asm("sqrt.approx.ftz.f32 %0, %1;" : "=f"(d) : "f"(s2));
    return pack_bf(d, 0.f) & 0xffffu;
}

__device__ __forceinline__ void load_pos(uint32_t sm_pos, int i, uint32_t& xy, uint32_t& z) {
    uint32_t a  = (sm_pos + 6u * (uint32_t)i) & ~3u;
    uint32_t w0 = lds32(a), w1 = lds32(a + 4);
    uint32_t sh = (uint32_t)i << 4;
    xy = __funnelshift_r(w0, w1, sh);
    z  = __funnelshift_r(w1, w1, sh);
}

__device__ __noinline__ float radial_value(float d, float f) {
    float arg = rbf(d * f);
    float sn  = rbf(sinf(arg));
    float rb  = rbf(__fdiv_rn(sn, d));
    float c   = rbf(cosf(rbf(__fdiv_rn(rbf(d * 3.14159265358979323846f), 5.0f))));
    float fc  = rbf(0.5f * rbf(c + 1.0f));
    return rb * fc;
}

__global__ void __launch_bounds__(NT, 1)
painn_kernel(const Params p, const __grid_constant__ CUtensorMap tmF, const __grid_constant__ CUtensorMap tmSV,
             const __grid_constant__ CUtensorMap tmW1, const __grid_constant__ CUtensorMap tmW2) {
    extern __shared__ __align__(1024) uint8_t smem[];
    const uint32_t sb   = smem_u32(smem);
    const int tid  = threadIdx.x, lane = tid & 31, warp = __shfl_sync(0xffffffffu, tid >> 5, 0);
    const int cta  = blockIdx.x;
    const int g    = lane >> 2, t = lane & 3;
    int* binCnt = (int*)(smem + SM_BINCNT);
    int* binOff = (int*)(smem + SM_BINOFF);
    int* nCnt   = (int*)(smem + SM_NCNT);
    uint32_t* nInfo = (uint32_t*)(smem + SM_NINFO);
    volatile int* ctrl = (volatile int*)(smem + SM_CTRL);
    const uint32_t bar_pos = sb + SM_BARS, bar_mlp = bar_pos + 8, bar_rec = bar_pos + 16;
    const uint32_t bar_full = bar_pos + 32, bar_empty = bar_full + NCWG * MAX_STAGE * 8;

    const int node0  = cta * p.npc;
    const int nnodes = max(0, min(p.npc, p.N - node0));

    STAMP(0);
    if (tid == 0) {
        mbar_init(bar_pos, 1);
        mbar_init(bar_mlp, 1);
        mbar_init(bar_rec, 1);
        for (int i = 0; i < NCWG * MAX_STAGE; i++) { mbar_init(bar_full + 8 * i, 1); mbar_init(bar_empty + 8 * i, 4); }
        asm volatile("fence.mbarrier_init.release.cluster;" ::: "memory");
        uint32_t pos_bytes = (uint32_t)(p.N * 6 + 15) & ~15u;
        mbar_expect_tx(bar_pos, pos_bytes);
        bulk_g2s(sb + P1_POS, p.pos, pos_bytes, bar_pos);
        mbar_expect_tx(bar_mlp, 2u * 160u * 128u + 8192u + 24576u);
        tma_load(sb + P1_SV, &tmSV, node0 * 4, bar_mlp);
        tma_load(sb + P1_SV + 160 * 128, &tmSV, node0 * 4 + 160, bar_mlp);
        tma_load(sb + P1_W1, &tmW1, 0, bar_mlp);
        tma_load(sb + P1_W2, &tmW2, 0, bar_mlp);
    }
    const bool mlp_warp = warp >= 11;
    int4 s4[3], d4[3];
    const int q0 = cta * p.quads_per_cta;
    const int qend = min(q0 + p.quads_per_cta, p.E >> 2);
    if (!mlp_warp) {
#pragma unroll
        for (int k = 0; k < 3; k++) {
            int q = q0 + (warp + 11 * k) * 32 + lane;
            bool ok = q < qend;
            s4[k] = ok ? __ldg((const int4*)p.src + q) : make_int4(-1, -1, -1, -1);
            d4[k] = ok ? __ldg((const int4*)p.dst + q) : make_int4(0, 0, 0, 0);
        }
    } else {
        int q = q0 + (33 + warp - 11) * 32 + lane;
        if (q < qend && (lane & 7) == 0) {
            asm volatile("prefetch.global.L2 [%0];" ::"l"((const int4*)p.src + q));
            asm volatile("prefetch.global.L2 [%0];" ::"l"((const int4*)p.dst + q));
        }
    }
    if (tid < MAX_CTA) binCnt[tid] = 0;
    if (tid < MAX_NPC) nCnt[tid] = 0;
    if (tid < 16) ctrl[tid] = 0;
    if (tid >= 416 && tid < 416 + 48) {
        asm volatile("prefetch.global.L2 [%0];" ::"l"((const uint8_t*)p.wr + (tid - 416) * 128));
    }
    for (int i = P1_STAGE / 16 + tid; i < P1_SV / 16; i += NT) sts128(sb + i * 16, make_uint4(0u, 0u, 0u, 0u));
    __syncthreads();

    if (warp < 5) {
        const int rows_per = (TAB_ROWS + 1 + p.ncta - 1) / p.ncta;
        for (int i = tid; i < rows_per * 8; i += 5 * 32) {
            int row = cta * rows_per + (i >> 3), kp = i & 7;
            if (row <= TAB_ROWS) {
                uint32_t val = 0;
                if (row < TAB_ROWS) {
                    float d = __uint_as_float((D_MIN_BITS + row) << 16);
                    uint32_t f2 = __ldg((const uint32_t*)p.freqs + kp);
                    val = pack_bf(radial_value(d, bf_lo(f2)), radial_value(d, bf_hi(f2)));
                }
                ((uint32_t*)g_table)[row * 8 + kp] = val;
            }
        }
    }
    if (mlp_warp) {
        const int mt = warp - 11;
        if (mt * 16 < nnodes) {
            mbar_wait(bar_mlp, 0);
            STAMPT(10, 11 * 32);
            float acc[8][4];
#pragma unroll
            for (int i = 0; i < 8; i++) { acc[i][0] = acc[i][1] = acc[i][2] = acc[i][3] = 0.f; }
            const int lrow = (lane & 7) + ((lane >> 3) & 1) * 8, lch = lane >> 4;
#pragma unroll
            for (int ks = 0; ks < 4; ks++) {
                uint32_t a[4];
                const int line = 4 * (mt * 16 + lrow);
                ldsm4(a, sb + P1_SV + line * 128 + (((2 * ks + lch) ^ (line & 7)) << 4));
                const int kk = 16 * ks + lrow;
#pragma unroll
                for (int nt = 0; nt < 8; nt += 2) {
                    uint32_t b[4];
                    ldsm4t(b, sb + P1_W1 + kk * 128 + (((nt + lch) ^ (kk & 7)) << 4));
                    mma16816(acc[nt], a, b[0], b[1]);
                    mma16816(acc[nt + 1], a, b[2], b[3]);
                }
            }
            uint32_t hp[8][2];
#pragma unroll
            for (int i = 0; i < 8; i++) {
                float h[4];
#pragma unroll
                for (int q = 0; q < 4; q++) {
                    float x = rbf(acc[i][q]);
                    h[q] = __fdividef(x, 1.0f + __expf(-x));
                    acc[i][q] = 0.f;
                }
                hp[i][0] = pack_bf(h[0], h[1]);
                hp[i][1] = pack_bf(h[2], h[3]);
            }
#pragma unroll
            for (int ks = 0; ks < 4; ks++) {
                uint32_t a[4] = {hp[2 * ks][0], hp[2 * ks][1], hp[2 * ks + 1][0], hp[2 * ks + 1][1]};
                const int line = 3 * (16 * ks + lrow) + 1;
#pragma unroll
                for (int nt = 0; nt < 8; nt += 2) {
                    uint32_t b[4];
                    ldsm4t(b, sb + P1_W2 + line * 128 + (((nt + lch) ^ (line & 7)) << 4));
                    mma16816(acc[nt], a, b[0], b[1]);
                    mma16816(acc[nt + 1], a, b[2], b[3]);
                }
            }
            uint32_t q[3][8][2];
#pragma unroll
            for (int rh = 0; rh < 2; rh++) {
                const int row = mt * 16 + g + 8 * rh;
#pragma unroll
                for (int i = 0; i < 8; i++) {
                    const uint32_t ph = pack_bf(acc[i][2 * rh], acc[i][2 * rh + 1]);
#pragma unroll
                    for (int a = 0; a < 3; a++) {
                        const int line = 4 * row + 1 + a;
                        q[a][i][rh] = hmul2(ph, lds32(sb + P1_SV + line * 128 + ((i ^ (line & 7)) << 4) + 4 * t));
                    }
                }
            }
            __syncwarp();
            {
                const int row = mt * 16 + (lane & 7) + ((lane >> 3) & 1) * 8;
#pragma unroll
                for (int c = 0; c < 4; c++) {
                    const int line = 4 * row + c;
                    const uint32_t lb = sb + P1_SV + line * 128;
#pragma unroll
                    for (int i = 0; i < 8; i += 2) {
                        const uint32_t a = lb + (((i + lch) ^ (line & 7)) << 4);
                        if (c == 0) stsm4(a, hp[i][0], hp[i][1], hp[i + 1][0], hp[i + 1][1]);
                        else        stsm4(a, q[c - 1][i][0], q[c - 1][i][1], q[c - 1][i + 1][0], q[c - 1][i + 1][1]);
                    }
                }
            }
            fence_async_smem();
            __syncwarp();
            if (lane < 16 && mt * 16 + lane < nnodes) tma_store(&tmF, (node0 + mt * 16 + lane) * 4, sb + P1_SV + (mt * 16 + lane) * 512);
            asm volatile("cp.async.bulk.commit_group;" ::: "memory");
        }
        STAMPT(11, 11 * 32);
        const int q = q0 + (33 + warp - 11) * 32 + lane;
        const bool ok = q < qend;
        s4[0] = ok ? __ldg((const int4*)p.src + q) : make_int4(-1, -1, -1, -1);
        d4[0] = ok ? __ldg((const int4*)p.dst + q) : make_int4(0, 0, 0, 0);
        s4[1] = s4[2] = make_int4(-1, -1, -1, -1);
        d4[1] = d4[2] = make_int4(0, 0, 0, 0);
    }
    mbar_wait(bar_pos, 0);
    STAMP(1);

    uint32_t r0[12], r1[12], r2[12], rk[12];
#pragma unroll
    for (int k = 0; k < 3; k++) {
        const int ss[4] = {s4[k].x, s4[k].y, s4[k].z, s4[k].w};
        const int dd[4] = {d4[k].x, d4[k].y, d4[k].z, d4[k].w};
#pragma unroll
        for (int j = 0; j < 4; j++) rk[k * 4 + j] = 0xffffffffu;
        if (ss[0] >= 0) {
#pragma unroll
            for (int j = 0; j < 4; j++) {
                const int e = k * 4 + j;
                const int s = ss[j], d = dd[j];
                uint32_t sxy, sz, dxy, dz, rxy, rz;
                load_pos(sb + P1_POS, s, sxy, sz);
                load_pos(sb + P1_POS, d, dxy, dz);
                uint32_t db = edge_dist(sxy, sz, dxy, dz, rxy, rz);
                float inv;
                asm("rcp.approx.ftz.f32 %0, %1;" : "=f"(inv) : "f"(__uint_as_float(db << 16)));
                uint32_t bin = __umulhi((uint32_t)d, p.npc_magic);
                uint32_t dl  = (uint32_t)d - bin * (uint32_t)p.npc;
                r0[e] = (uint32_t)s | ((db - D_MIN_BITS) << 16);
                r1[e] = pack_bf(bf_lo(rxy) * inv, bf_hi(rxy) * inv);
                r2[e] = __byte_perm(pack_bf(bf_lo(rz) * inv, 0.f), dl, 0x5410);
                if (db <= D_MAX_BITS) rk[e] = (uint32_t)atomicAdd(&binCnt[bin], 1) | (bin << 16);
            }
        }
    }
    STAMP(2);
    STAMPT(12, 11 * 32);
    __syncthreads();
    STAMP(3);
    if (warp == 0) {
        int c[5], s = 0;
#pragma unroll
        for (int i = 0; i < 5; i++) { int b = lane * 5 + i; c[i] = b < p.ncta ? binCnt[b] : 0; s += c[i]; }
        int x = s;
#pragma unroll
        for (int o = 1; o < 32; o <<= 1) { int y = __shfl_up_sync(0xffffffffu, x, o); if (lane >= o) x += y; }
        int off = x - s;
#pragma unroll
        for (int i = 0; i < 5; i++) {
            int b = lane * 5 + i;
            if (b < p.ncta) { binOff[b] = off; g_offs[cta * MAX_CTA + b] = (uint32_t)off | ((uint32_t)c[i] << 16); }
            off += c[i];
        }
        if (lane == 31) ctrl[8] = x;
    }
    __syncthreads();
    unsigned bar_target = 0;
    if (tid == 0) {
        unsigned old;
        asm volatile("atom.add.release.gpu.global.u32 %0, [%1], 1;" : "=r"(old) : "l"(&g_bar[0]) : "memory");
        bar_target = (old / (unsigned)p.ncta + 1u) * (unsigned)p.ncta;
    }
#pragma unroll
    for (int e = 0; e < 12; e++) {
        if (rk[e] != 0xffffffffu) {
            int pos = binOff[rk[e] >> 16] + (int)(rk[e] & 0xffffu);
            sts128(sb + P1_STAGE + pos * 16, make_uint4(r0[e], r1[e], r2[e], 0u));
        }
    }
    fence_async_smem();
    __syncthreads();
    if (tid == 0) {
        const uint32_t bytes = (uint32_t)ctrl[8] * 16u;
        if (bytes) asm volatile("cp.async.bulk.global.shared::cta.bulk_group [%0], [%1], %2;"
                                ::"l"(g_rec + (size_t)cta * REC_CAP), "r"(sb + P1_STAGE), "r"(bytes) : "memory");
        asm volatile("cp.async.bulk.commit_group;" ::: "memory");
    }
    asm volatile("cp.async.bulk.wait_group 0;" ::: "memory");
    asm volatile("fence.proxy.async;" ::: "memory");

    __syncthreads();
    STAMP(4);
    if (tid == 0) asm volatile("red.add.release.gpu.global.u32 [%0], 1;" ::"l"(&g_bar[1]) : "memory");
    uint32_t wp[3][4];
    if (warp < 4) {
        const uint16_t* w2 = (const uint16_t*)p.w2 + 16 * warp + g;
#pragma unroll
        for (int mk = 0; mk < 8; mk++) {
            uint32_t f[4];
#pragma unroll
            for (int i = 0; i < 4; i++) {
                const uint16_t* q = w2 + (16 * (mk & 3) + 2 * t + 8 * (i >> 1)) * 192 + (mk >> 2) * 128 + 8 * (i & 1);
                f[i] = (uint32_t)__ldg(q) | ((uint32_t)__ldg(q + 192) << 16);
            }
            sts128(sb + SM_HT + (mk * 128 + tid) * 16, make_uint4(f[0], f[1], f[2], f[3]));
        }
    }
    if (warp < 4 * NCWG) {
        const uint16_t* wr = (const uint16_t*)p.wr + 16 * (warp & 3) + g;
#pragma unroll
        for (int ty = 0; ty < 3; ty++) {
#pragma unroll
            for (int i = 0; i < 4; i++) {
                const uint16_t* q = wr + (8 * (i >> 1) + 2 * t) * 192 + ty * 64 + 8 * (i & 1);
                wp[ty][i] = (uint32_t)__ldg(q) | ((uint32_t)__ldg(q + 192) << 16);
            }
        }
    }
    if (tid == 0) ctrl[10] = (int)bar_target;
    __syncthreads();
    if (warp == 15) {
        const unsigned target = (unsigned)ctrl[10];
        if (lane == 0) {
            unsigned cur;
            int spins = 0;
            do {
                asm volatile("ld.acquire.gpu.global.u32 %0, [%1];" : "=r"(cur) : "l"(&g_bar[0]) : "memory");
            } while ((int)(cur - target) < 0 && ++spins < (1 << 24));
        }
        __syncwarp();
        uint32_t v[5];
        int s = 0;
#pragma unroll
        for (int i = 0; i < 5; i++) {
            int b = lane * 5 + i;
            v[i] = b < p.ncta ? __ldcg(&g_offs[b * MAX_CTA + cta]) : 0u;
        }
#pragma unroll
        for (int i = 0; i < 5; i++) s += (int)(v[i] >> 16);
        int x = s;
#pragma unroll
        for (int o = 1; o < 32; o <<= 1) { int y = __shfl_up_sync(0xffffffffu, x, o); if (lane >= o) x += y; }
        const int tot = __shfl_sync(0xffffffffu, x, 31);
        int off = x - s;
#pragma unroll
        for (int i = 0; i < 5; i++) {
            int b = lane * 5 + i;
            if (b < p.ncta) { binCnt[b] = (int)v[i]; binOff[b] = off; }
            off += (int)(v[i] >> 16);
        }
        if (lane == 0) {
            ctrl[8] = tot;
            if (tot > STAGE_CAP) ctrl[1] = 1;
            mbar_expect_tx(bar_rec, tot > STAGE_CAP ? 0u : (uint32_t)tot * 16u);
        }
    }
    if (tid == 0) {
        unsigned cur;
        int spins = 0;
        do {
            asm volatile("ld.acquire.gpu.global.u32 %0, [%1];" : "=r"(cur) : "l"(&g_bar[1]) : "memory");
        } while ((int)(cur - bar_target) < 0 && ++spins < (1 << 24));
    }
    __syncthreads();
    STAMP(5);

    const int total = ctrl[8];
    if (ctrl[1] == 0) {
        const int b = (lane << 4) | warp;
        if (lane < 9 && b < p.ncta) {
            const uint32_t v = (uint32_t)binCnt[b], c = v >> 16;
            if (c) {
                asm volatile("fence.proxy.async;" ::: "memory");
                bulk_g2s(sb + SM_STAGE2 + (uint32_t)binOff[b] * 16u, g_rec + (size_t)b * REC_CAP + (v & 0xffffu), c * 16u, bar_rec);
            }
        }
    }
    mbar_wait(bar_rec, 0);
    if (ctrl[1] == 0) {
        for (int i = tid; i < total; i += NT) {
            uint32_t dl = lds32(sb + SM_STAGE2 + i * 16 + 8) >> 16;
            sts32(sb + SM_STAGE2 + i * 16 + 12, (uint32_t)atomicAdd(&nCnt[dl], 1));
        }
    }
    __syncthreads();
    if (warp == 0) {
        int c[3], s = 0;
#pragma unroll
        for (int i = 0; i < 3; i++) {
            int b = lane * 3 + i;
            c[i] = b < nnodes ? max(16, (nCnt[b] + 15) & ~15) : 0;
            s += c[i];
        }
        int x = s;
#pragma unroll
        for (int o = 1; o < 32; o <<= 1) { int y = __shfl_up_sync(0xffffffffu, x, o); if (lane >= o) x += y; }
        const int slots = __shfl_sync(0xffffffffu, x, 31);
        int off = x - s, below = 0;
#pragma unroll
        for (int i = 0; i < 3; i++) {
            int b = lane * 3 + i;
            if (b < nnodes) {
                nInfo[b] = (uint32_t)off | ((uint32_t)c[i] << 16);
                below += (2 * off + c[i] < slots);
            }
            off += c[i];
        }
        below = __reduce_add_sync(0xffffffffu, below);
        if (lane == 0) {
            ctrl[2] = below;
            ctrl[4] = slots;
            if (slots > SLOT_CAP) ctrl[1] = 1;
        }
    }
    __syncthreads();
    if (ctrl[1] == 0) {
        uint16_t* sid = (uint16_t*)(smem + SM_SID);
        uint2* meta = (uint2*)(smem + SM_META);
        for (int i = tid; i < total; i += NT) {
            uint4 r = lds128(sb + SM_STAGE2 + i * 16);
            int pos = (int)(nInfo[r.z >> 16] & 0xffffu) + (int)r.w;
            sid[pos]  = (uint16_t)(r.x & 0xffffu);
            meta[pos] = make_uint2(((r.x >> 16) << 5) | (r.z << 16), r.y);
        }
        for (int i = tid; i < nnodes * 16; i += NT) {
            int nl = i >> 4, c = nCnt[nl];
            int j = (c & ~15) + (i & 15);
            if (j >= c && (j < 16 || (c & 15))) {
                int pos = (int)(nInfo[nl] & 0xffffu) + j;
                sid[pos]  = 0xffffu;
                meta[pos] = make_uint2((uint32_t)TAB_ZERO << 5, 0u);
            }
        }
    }
    fence_async_smem();
    __syncthreads();
    STAMP(6);

    if (__shfl_sync(0xffffffffu, ctrl[1], 0) != 0) {
        float* acc = (float*)(smem + P1_POS);
        for (int i = tid; i < nnodes * 256; i += NT) acc[i] = 0.f;
        __syncthreads();
        const uint16_t* posu = (const uint16_t*)p.pos;
        const uint32_t* tabg = (const uint32_t*)g_table;
        const uint32_t* Fw = (const uint32_t*)g_F;
        for (int e0 = warp * 32; e0 < p.E; e0 += NT) {
            int e = e0 + lane;
            int s = 0, d = 0;
            uint32_t db = 0xffff, rxy = 0, rz = 0;
            bool act = false;
            if (e < p.E) {
                s = p.src[e]; d = p.dst[e];
                if (d >= node0 && d < node0 + nnodes) {
                    uint32_t sxy = posu[s * 3] | ((uint32_t)posu[s * 3 + 1] << 16), sz = posu[s * 3 + 2];
                    uint32_t dxy = posu[d * 3] | ((uint32_t)posu[d * 3 + 1] << 16), dz = posu[d * 3 + 2];
                    db  = edge_dist(sxy, sz, dxy, dz, rxy, rz);
                    act = db <= D_MAX_BITS;
                }
            }
            unsigned m = __ballot_sync(0xffffffffu, act);
            while (m) {
                int l = __ffs(m) - 1;
                m &= m - 1;
                int es = __shfl_sync(0xffffffffu, s, l), ed = __shfl_sync(0xffffffffu, d, l);
                uint32_t edb = __shfl_sync(0xffffffffu, db, l), exy = __shfl_sync(0xffffffffu, rxy, l), ez = __shfl_sync(0xffffffffu, rz, l);
                float inv = 1.0f / __uint_as_float(edb << 16);
                float rh[3] = {rbf(bf_lo(exy) * inv), rbf(bf_hi(exy) * inv), rbf(bf_lo(ez) * inv)};
                const uint32_t* fr = Fw + (size_t)es * 128 + lane;
                const uint32_t fh = __ldcg(fr);
                const uint32_t q[3] = {__ldcg(fr + 32), __ldcg(fr + 64), __ldcg(fr + 96)};
                float ps0 = 0.f, ps1 = 0.f, pr0 = 0.f, pr1 = 0.f;
                for (int j2 = 0; j2 < 32; j2++) {
                    uint32_t hj = __shfl_sync(0xffffffffu, fh, j2);
                    uint32_t a0 = *(const uint32_t*)(p.w2 + (2 * j2) * 192 + 2 * lane), a1 = *(const uint32_t*)(p.w2 + (2 * j2 + 1) * 192 + 2 * lane);
                    uint32_t b0 = *(const uint32_t*)(p.w2 + (2 * j2) * 192 + 128 + 2 * lane), b1 = *(const uint32_t*)(p.w2 + (2 * j2 + 1) * 192 + 128 + 2 * lane);
                    ps0 += bf_lo(hj) * bf_lo(a0) + bf_hi(hj) * bf_lo(a1);
                    ps1 += bf_lo(hj) * bf_hi(a0) + bf_hi(hj) * bf_hi(a1);
                    pr0 += bf_lo(hj) * bf_lo(b0) + bf_hi(hj) * bf_lo(b1);
                    pr1 += bf_lo(hj) * bf_hi(b0) + bf_hi(hj) * bf_hi(b1);
                }
                float ws0 = 0.f, ws1 = 0.f, wv0 = 0.f, wv1 = 0.f, wr0 = 0.f, wr1 = 0.f;
                for (int k2 = 0; k2 < 8; k2++) {
                    uint32_t rk2 = __ldcg(tabg + (edb - D_MIN_BITS) * 8 + k2);
#pragma unroll
                    for (int h = 0; h < 2; h++) {
                        float rv = h ? bf_hi(rk2) : bf_lo(rk2);
                        const __nv_bfloat16* wrow = p.wr + (2 * k2 + h) * 192 + 2 * lane;
                        uint32_t a = *(const uint32_t*)wrow, b = *(const uint32_t*)(wrow + 64), c = *(const uint32_t*)(wrow + 128);
                        ws0 += rv * bf_lo(a); ws1 += rv * bf_hi(a);
                        wv0 += rv * bf_lo(b); wv1 += rv * bf_hi(b);
                        wr0 += rv * bf_lo(c); wr1 += rv * bf_hi(c);
                    }
                }
                float* a = acc + (ed - node0) * 256 + 2 * lane;
                atomicAdd(a, ps0 * ws0); atomicAdd(a + 1, ps1 * ws1);
#pragma unroll
                for (int c = 0; c < 3; c++) {
                    atomicAdd(a + 64 * (c + 1), wv0 * bf_lo(q[c]) + pr0 * wr0 * rh[c]);
                    atomicAdd(a + 64 * (c + 1) + 1, wv1 * bf_hi(q[c]) + pr1 * wr1 * rh[c]);
                }
            }
        }
        __syncthreads();
        for (int i = tid; i < nnodes * 128; i += NT) {
            uint32_t r = *(const uint32_t*)(p.sv + (size_t)node0 * 256 + 2 * i);
            *(uint32_t*)(p.out + (size_t)node0 * 256 + 2 * i) = pack_bf(bf_lo(r) + acc[2 * i], bf_hi(r) + acc[2 * i + 1]);
        }
        return;
    }

    const int slots = __reduce_max_sync(0xffffffffu, ctrl[4]);
    const int split = __reduce_max_sync(0xffffffffu, ctrl[2]);
    const int nstage = slots <= SLOT_CAP4 ? 6 : 5;
    const uint32_t ring = sb + (nstage == 6 ? SM_RING4 : SM_RING3);
    const int mid = __reduce_max_sync(0xffffffffu, split < nnodes ? (int)(nInfo[split] & 0xffffu) : slots) >> 4;
    if (warp >= 4 * NCWG) {
        asm volatile("setmaxnreg.dec.sync.aligned.u32 48;");
        const int wg = (warp - 4 * NCWG) >> 2, r = warp & 3;
        const int g0 = wg == 0 ? 0 : mid, g1 = wg == 0 ? mid : slots >> 4;
        const int e = lane >> 1, half = lane & 1;
        const uint32_t coef_off = e * 128 + ((half ^ (e & 7)) << 4);
        const int vrot = (e & 3) ^ ((e >> 1) & 3);
        const uint8_t* tab = (const uint8_t*)g_table + half * 16;
        int stage = r, phase = 1;
        for (int gi = g0 + r; gi < g1; gi += 4) {
            const uint32_t st = ring + (wg * nstage + stage) * STAGE_B;
            const uint32_t fb = bar_full + (wg * MAX_STAGE + stage) * 8;
            const uint2 m = lds64(sb + SM_META + (gi * 16 + e) * 8);
            const uint4 ia = lds128(sb + SM_SID + gi * 32), ib = lds128(sb + SM_SID + gi * 32 + 16);
            const uint4 tv = __ldg((const uint4*)(tab + (m.x & 0xffffu)));
            const uint32_t id2[8] = {ia.x, ia.y, ia.z, ia.w, ib.x, ib.y, ib.z, ib.w};
            const int nv = __popc(__ballot_sync(0xffffffffu, (m.x & 0xffffu) != (uint32_t)(TAB_ZERO << 5))) >> 1;
            mbar_wait(bar_empty + (wg * MAX_STAGE + stage) * 8, phase);
            uint32_t leader;
            asm volatile("{\n.reg .pred p;\nelect.sync _|p, 0xffffffff;\nselp.u32 %0, 1, 0, p;\n}" : "=r"(leader));
            if (leader) {
                if (nv == 16) {
#pragma unroll
                    for (int i = 0; i < 8; i++) {
                        tma_load(st + 2048 + (2 * i) * 640, &tmF, (int)(id2[i] & 0xffffu) * 4, fb);
                        tma_load(st + 2048 + (2 * i + 1) * 640, &tmF, (int)(id2[i] >> 16) * 4, fb);
                    }
                } else {
                    for (int i = 0; i < nv; i++)
                        tma_load(st + 2048 + i * 640, &tmF, (int)lds16(sb + SM_SID + (gi * 16 + i) * 2) * 4, fb);
                }
            }
            __syncwarp();
            const uint32_t mul[4] = {0x3f803f80u, __byte_perm(m.y, 0, 0x1010), __byte_perm(m.y, 0, 0x3232), __byte_perm(m.x, 0, 0x3232)};
            const uint32_t a = st + coef_off;
#pragma unroll
            for (int j = 0; j < 4; j++) {
                const int v = j ^ vrot;
                const uint32_t lo = (v & 1) ? mul[1] : mul[0], hi = (v & 1) ? mul[3] : mul[2];
                const uint32_t mm = (v & 2) ? hi : lo;
                sts128(a ^ (v << 5), make_uint4(hmul2(tv.x, mm), hmul2(tv.y, mm), hmul2(tv.z, mm), hmul2(tv.w, mm)));
            }
            fence_async_smem();
            __syncwarp();
            if (lane == 0) mbar_expect_tx(fb, (uint32_t)nv * 512u);
            stage += 4;
            if (stage >= nstage) { stage -= nstage; phase ^= 1; }
        }
    } else {
        asm volatile("setmaxnreg.inc.sync.aligned.u32 208;");
        const int wg = warp >> 2, w = warp & 3;
        const int n_end = wg == 0 ? split : nnodes;
        uint32_t wA[2][4][4];
#pragma unroll
        for (int mk = 0; mk < 8; mk++) {
            const uint4 q = lds128(sb + SM_HT + (mk * 128 + (tid & 127)) * 16);
            wA[mk >> 2][mk & 3][0] = q.x; wA[mk >> 2][mk & 3][1] = q.y; wA[mk >> 2][mk & 3][2] = q.z; wA[mk >> 2][mk & 3][3] = q.w;
        }
        asm volatile("bar.sync 3, 256;" ::: "memory");
        uint32_t aoff[4];
        {
            const int e = (lane & 7) + 8 * (lane >> 4), ch = 2 * w + ((lane >> 3) & 1);
#pragma unroll
            for (int b = 0; b < 4; b++) aoff[b] = 2048 + e * 640 + b * 128 + ((ch ^ ((5 * e + b) & 7)) << 4);
        }
        const uint32_t ht = sb + SM_HT + wg * 8192;
        const uint32_t stsm_a = ht + (16 * w + (lane & 15)) * 128 + (((lane >> 4) ^ (lane & 7)) << 4);
        const uint32_t dht = desc_lo(ht);
        const uint32_t out_lane = (uint32_t)node0 * 512u + t * 128 + (16 * w + (g & 1) * 8 + (g & 6)) * 2;
        const uint32_t ring_wg = ring + wg * nstage * STAGE_B;
        const uint32_t full_wg = bar_full + wg * MAX_STAGE * 8;

        float ys[8], yv[24], dQ[3][8];
        float zs[8], zv[24], pv[3][2];
        uint32_t A0[4][4], A1[4][4];
#pragma unroll
        for (int i = 0; i < 24; i++) yv[i] = 0.f;
#pragma unroll
        for (int i = 0; i < 8; i++) { ys[i] = 0.f; dQ[0][i] = 0.f; dQ[1][i] = 0.f; dQ[2][i] = 0.f; }
        int left = wg == 0 ? mid : (slots >> 4) - mid;
        int fstage = 0;
        uint32_t fphase = 0, fst = ring_wg, fbar = full_wg;
        int nl = wg == 0 ? 0 : split, gi = 0, G = 0, pend = -1;
        uint32_t rs0 = 0, rs1 = 0;
        int npar = 0, ppar = 0, qpar = 0;

        auto fetch = [&](uint32_t (&A)[4][4], uint32_t& bd, uint32_t& eb) {
            mbar_wait(fbar, fphase);
#pragma unroll
            for (int b = 0; b < 4; b++) ldsm4t(A[b], fst + aoff[b]);
            bd = desc_lo(fst);
            eb = fbar + NCWG * MAX_STAGE * 8;
            fst += STAGE_B; fbar += 8;
            if (++fstage == nstage) { fstage = 0; fphase ^= 1; fst = ring_wg; fbar = full_wg; }
        };
        auto node_begin = [&]() {
            G = __reduce_max_sync(0xffffffffu, (int)(nInfo[nl] >> 20));
            gi = 0;
        };
        float pr[4][2];
        int pend2 = -1;
        auto weigh = [&]() {
#pragma unroll
            for (int i = 0; i < 12; i++) asm volatile("" : "+r"(wp[i >> 2][i & 3]));
            pr[0][0] = bf_lo(wp[0][0]) * zs[0] + bf_hi(wp[0][0]) * zs[1] + bf_lo(wp[0][2]) * zs[4] + bf_hi(wp[0][2]) * zs[5];
            pr[0][1] = bf_lo(wp[0][1]) * zs[2] + bf_hi(wp[0][1]) * zs[3] + bf_lo(wp[0][3]) * zs[6] + bf_hi(wp[0][3]) * zs[7];
#pragma unroll
            for (int a = 0; a < 3; a++) {
                const float* y = zv + 8 * a;
                pr[a + 1][0] = pv[a][0] + bf_lo(wp[2][0]) * y[0] + bf_hi(wp[2][0]) * y[1] + bf_lo(wp[2][2]) * y[4] + bf_hi(wp[2][2]) * y[5];
                pr[a + 1][1] = pv[a][1] + bf_lo(wp[2][1]) * y[2] + bf_hi(wp[2][1]) * y[3] + bf_lo(wp[2][3]) * y[6] + bf_hi(wp[2][3]) * y[7];
            }
            pend2 = pend;
            qpar = ppar;
            pend = -1;
        };
        auto finish = [&]() {
            const bool hi2 = t & 2, hi1 = t & 1, odd = g & 1;
            float ka0 = hi2 ? pr[2][0] : pr[0][0], ka1 = hi2 ? pr[2][1] : pr[0][1];
            float kb0 = hi2 ? pr[3][0] : pr[1][0], kb1 = hi2 ? pr[3][1] : pr[1][1];
            float sa0 = hi2 ? pr[0][0] : pr[2][0], sa1 = hi2 ? pr[0][1] : pr[2][1];
            float sb0 = hi2 ? pr[1][0] : pr[3][0], sb1 = hi2 ? pr[1][1] : pr[3][1];
            ka0 += __shfl_xor_sync(0xffffffffu, sa0, 2); ka1 += __shfl_xor_sync(0xffffffffu, sa1, 2);
            kb0 += __shfl_xor_sync(0xffffffffu, sb0, 2); kb1 += __shfl_xor_sync(0xffffffffu, sb1, 2);
            float k0 = hi1 ? kb0 : ka0, k1 = hi1 ? kb1 : ka1;
            float s0 = hi1 ? ka0 : kb0, s1 = hi1 ? ka1 : kb1;
            k0 += __shfl_xor_sync(0xffffffffu, s0, 1);
            k1 += __shfl_xor_sync(0xffffffffu, s1, 1);
            const float other = __shfl_xor_sync(0xffffffffu, odd ? k0 : k1, 4);
            const float lo = odd ? other : k0, hi = odd ? k1 : other;
            const uint32_t resid = qpar ? rs1 : rs0;
            *(uint32_t*)((uint8_t*)p.out + (out_lane + (uint32_t)pend2 * 512u)) = pack_bf(bf_lo(resid) + lo, bf_hi(resid) + hi);
            pend2 = -1;
        };
        auto step = [&](uint32_t (&Ac)[4][4], uint32_t bdc, uint32_t ebc, uint32_t (&An)[4][4], uint32_t& bdn, uint32_t& ebn) {
            wg_fence();
            wgmma_n64_p(ys, yv, Ac[0], bdc, gi);
            wgmma_n16_p(dQ[0], Ac[1], bdc, gi);
            wgmma_n16_p(dQ[1], Ac[2], bdc, gi);
            wgmma_n16_p(dQ[2], Ac[3], bdc, gi);
            wg_commit();
            if (pend2 >= 0) finish();
            if (--left > 0) fetch(An, bdn, ebn);
            const bool last = ++gi == G;
            wg_wait0();
            mbar_arrive_elected(ebc);
            if (pend >= 0) weigh();
            if (last) {
                named_barrier(1 + wg);
                uint32_t sa = stsm_a;
                asm volatile("" : "+r"(sa));
                stsm4(sa, pack_bf(ys[0], ys[1]), pack_bf(ys[2], ys[3]), pack_bf(ys[4], ys[5]), pack_bf(ys[6], ys[7]));
#pragma unroll
                for (int i = 0; i < 6; i += 2) {
                    stsm4(sa ^ ((i + 2) << 4),
                          pack_bf(yv[4 * i], yv[4 * i + 1]), pack_bf(yv[4 * i + 2], yv[4 * i + 3]),
                          pack_bf(yv[4 * i + 4], yv[4 * i + 5]), pack_bf(yv[4 * i + 6], yv[4 * i + 7]));
                }
                fence_async_smem();
#pragma unroll
                for (int i = 0; i < 4; i++) asm volatile("" : "+r"(wp[1][i]));
#pragma unroll
                for (int a = 0; a < 3; a++) {
                    const float* q = dQ[a];
                    pv[a][0] = bf_lo(wp[1][0]) * q[0] + bf_hi(wp[1][0]) * q[1] + bf_lo(wp[1][2]) * q[4] + bf_hi(wp[1][2]) * q[5];
                    pv[a][1] = bf_lo(wp[1][1]) * q[2] + bf_hi(wp[1][1]) * q[3] + bf_lo(wp[1][3]) * q[6] + bf_hi(wp[1][3]) * q[7];
                }
                named_barrier(1 + wg);
                wg_fence();
                wgmma_n16_first(zs, wA[0][0], dht);
                wgmma_n48_first(zv, wA[1][0], dht + 2);
#pragma unroll
                for (int ks = 1; ks < 4; ks++) {
                    wgmma_n16(zs, wA[0][ks], dht + ks * 128);
                    wgmma_n48(zv, wA[1][ks], dht + ks * 128 + 2);
                }
                wg_commit();
                pend = nl;
                {
                    const uint8_t* ra = (const uint8_t*)p.sv + (out_lane + (uint32_t)nl * 512u);
                    asm volatile("{\n.reg .pred p;\nsetp.ne.s32 p, %3, 0;\n@p ld.global.nc.u32 %1, [%2];\n@!p ld.global.nc.L1::no_allocate.u32 %0, [%2];\n}"
                                 : "+r"(rs0), "+r"(rs1) : "l"(ra), "r"(npar));
                    ppar = npar;
                    npar ^= 1;
                }
                if (++nl < n_end) node_begin();
            }
        };
        if (left > 0) {
            node_begin();
            uint32_t bd0, eb0, bd1 = 0, eb1 = 0;
            fetch(A0, bd0, eb0);
            while (true) {
                step(A0, bd0, eb0, A1, bd1, eb1);
                if (left <= 0) break;
                step(A1, bd1, eb1, A0, bd0, eb0);
                if (left <= 0) break;
            }
            if (pend2 >= 0) finish();
            wg_wait0();
            weigh();
            finish();
        }
    }
    STAMP(8);
}

typedef CUresult (*EncodeFn)(CUtensorMap*, CUtensorMapDataType, cuuint32_t, void*, const cuuint64_t*, const cuuint64_t*,
                             const cuuint32_t*, const cuuint32_t*, CUtensorMapInterleave, CUtensorMapSwizzle,
                             CUtensorMapL2promotion, CUtensorMapFloatOOBfill);

void make_map(EncodeFn enc, CUtensorMap* tm, const void* base, uint64_t lines, uint32_t box) {
    cuuint64_t gd[2] = {64, lines};
    cuuint64_t gs[1] = {128};
    cuuint32_t bd[2] = {64, box};
    cuuint32_t es[2] = {1, 1};
    enc(tm, CU_TENSOR_MAP_DATA_TYPE_BFLOAT16, 2, const_cast<void*>(base), gd, gs, bd, es, CU_TENSOR_MAP_INTERLEAVE_NONE,
        CU_TENSOR_MAP_SWIZZLE_128B, CU_TENSOR_MAP_L2_PROMOTION_L2_128B, CU_TENSOR_MAP_FLOAT_OOB_FILL_NONE);
}

}

extern "C" void kernel_launch(void* const* d_in, const int* in_sizes, int n_in, void* d_out, int out_size) {
    (void)n_in; (void)out_size;
    static int n_sm = 0;
    static EncodeFn enc = nullptr;
    static void* f_ptr = nullptr;
    if (n_sm == 0) {
        int dev = 0;
        cudaGetDevice(&dev);
        cudaDeviceGetAttribute(&n_sm, cudaDevAttrMultiProcessorCount, dev);
        cudaFuncSetAttribute(painn_kernel, cudaFuncAttributeMaxDynamicSharedMemorySize, SM_TOTAL);
        void* fn = nullptr;
        cudaDriverEntryPointQueryResult qr;
        cudaGetDriverEntryPoint("cuTensorMapEncodeTiled", &fn, cudaEnableDefault, &qr);
        enc = (EncodeFn)fn;
        cudaGetSymbolAddress(&f_ptr, g_F);
    }
    Params p;
    p.sv    = (const __nv_bfloat16*)d_in[0];
    p.pos   = (const __nv_bfloat16*)d_in[1];
    p.src   = (const int*)d_in[2];
    p.dst   = (const int*)d_in[3];
    p.freqs = (const __nv_bfloat16*)d_in[4];
    p.w1    = (const __nv_bfloat16*)d_in[5];
    p.w2    = (const __nv_bfloat16*)d_in[6];
    p.wr    = (const __nv_bfloat16*)d_in[7];
    p.out   = (__nv_bfloat16*)d_out;
    p.N = in_sizes[1] / 3;
    p.E = in_sizes[2];
    p.ncta = n_sm < MAX_CTA ? n_sm : MAX_CTA;
    p.npc = (p.N + p.ncta - 1) / p.ncta;
    p.npc_magic = (uint32_t)(0x100000000ull / (uint32_t)p.npc) + 1u;
    p.quads_per_cta = ((p.E >> 2) + p.ncta - 1) / p.ncta;
    if (!enc || p.N > MAX_N || p.npc > MAX_NPC || (p.E & 3) || p.quads_per_cta > MAX_ROUNDS * 32) return;

    CUtensorMap tmF, tmSV, tmW1, tmW2;
    make_map(enc, &tmF, f_ptr, (uint64_t)p.N * 4, 4);
    make_map(enc, &tmSV, p.sv, (uint64_t)p.N * 4, 160);
    make_map(enc, &tmW1, p.w1, 64, 64);
    make_map(enc, &tmW2, p.w2, 192, 192);

    cudaLaunchConfig_t cfg = {};
    cfg.gridDim = dim3(p.ncta);
    cfg.blockDim = dim3(NT);
    cfg.dynamicSmemBytes = SM_TOTAL;
    cfg.stream = cudaStreamPerThread;
    cudaLaunchAttribute attr[1];
    attr[0].id = cudaLaunchAttributeCooperative;
    attr[0].val.cooperative = 1;
    cfg.attrs = attr;
    cfg.numAttrs = 1;
    cudaLaunchKernelEx(&cfg, painn_kernel, p, tmF, tmSV, tmW1, tmW2);
}
```

```cpp
#include <cuda_runtime.h>
#include <cuda.h>
#include <cuda_bf16.h>
#include <stdint.h>

namespace {

constexpr int NT        = 512;
constexpr int NCWG      = 2;
constexpr int MAX_N     = 10240;
constexpr int MAX_CTA   = 144;
constexpr int MAX_NPC   = 80;
constexpr int MAX_ROUNDS = 38;
constexpr int REC_CAP   = MAX_ROUNDS * 128;
constexpr int SLOT_CAP  = 6144;
constexpr int MAX_STAGE = 6;
constexpr int STAGE_B   = 12288;

constexpr uint32_t D_MIN_BITS = 0x38D2;
constexpr uint32_t D_MAX_BITS = 0x409C;
constexpr int TAB_ROWS  = (int)(D_MAX_BITS - D_MIN_BITS) + 1;
constexpr int TAB_ZERO  = TAB_ROWS;
constexpr int TAB_BYTES = (TAB_ROWS + 1) * 32;

constexpr int SM_BINCNT = 0;
constexpr int SM_BINOFF = SM_BINCNT + MAX_CTA * 4;
constexpr int SM_NCNT   = SM_BINOFF + MAX_CTA * 4;
constexpr int SM_NINFO  = SM_NCNT + MAX_NPC * 4;
constexpr int SM_CTRL   = SM_NINFO + MAX_NPC * 4;
constexpr int SM_BARS   = SM_CTRL + 64;
constexpr int SM_SID    = 2048 + 128;
constexpr int SM_META   = SM_SID + SLOT_CAP * 2;
constexpr int SM_TOTAL  = 232448;
constexpr int SM_HT     = (SM_TOTAL - NCWG * 8192) / 1024 * 1024;
constexpr int SM_RING4  = SM_HT - NCWG * 6 * STAGE_B;
constexpr int SM_RING3  = SM_HT - NCWG * 5 * STAGE_B;
constexpr int SLOT_CAP4 = (SM_RING4 - SM_META) / 8;
constexpr int SM_STAGE2 = SM_RING3 - 0;
constexpr int STAGE_CAP = (SM_HT - SM_RING3) / 16;
constexpr int P1_POS    = 3072;
constexpr int P1_STAGE  = P1_POS + 61440;
constexpr int P1_SV     = (P1_STAGE + REC_CAP * 16 + 1023) / 1024 * 1024;
constexpr int P1_W1     = P1_SV + MAX_NPC * 512;
constexpr int P1_W2     = P1_W1 + 8192;
constexpr int P1_END    = P1_W2 + 24576;
static_assert(SM_BARS + (4 + 2 * NCWG * MAX_STAGE) * 8 <= SM_SID, "misc block");
static_assert(SM_BARS + 256 <= P1_POS, "misc block");
static_assert(P1_END <= SM_TOTAL, "phase 1 overlay");
static_assert(SM_META + SLOT_CAP * 8 <= SM_RING3, "CSR");
static_assert(SM_RING4 % 1024 == 0 && SM_RING3 % 1024 == 0 && SM_HT % 1024 == 0, "alignment");
static_assert(SM_BARS % 8 == 0 && SM_META % 8 == 0, "alignment");
static_assert(MAX_N * 6 <= 61440, "pos");
static_assert(SM_SID + MAX_NPC * 1024 <= SM_TOTAL, "slow path accumulators");

__device__ __align__(1024) uint4 g_F[MAX_N * 32];
__device__ uint4    g_rec[MAX_CTA * REC_CAP];
__device__ uint32_t g_offs[MAX_CTA * MAX_CTA];
__device__ uint4    g_table[(TAB_BYTES + 15) / 16];
__device__ unsigned g_bar[2];
#define STAMP(k)
#define STAMPT(k, T)
#define ITS(k)

struct Params {
    const __nv_bfloat16* sv;
    const __nv_bfloat16* pos;
    const int*           src;
    const int*           dst;
    const __nv_bfloat16* freqs;
    const __nv_bfloat16* w1;
    const __nv_bfloat16* w2;
    const __nv_bfloat16* wr;
    __nv_bfloat16*       out;
    int N, E, ncta, npc;
    uint32_t npc_magic;
    int quads_per_cta;
};

__device__ __forceinline__ uint32_t smem_u32(const void* p) { return (uint32_t)__cvta_generic_to_shared(p); }
__device__ __forceinline__ float bf_lo(uint32_t v) { return __uint_as_float(v << 16); }
__device__ __forceinline__ float bf_hi(uint32_t v) { return __uint_as_float(v & 0xffff0000u); }
__device__ __forceinline__ float bf_u16(uint16_t v) { return __uint_as_float((uint32_t)v << 16); }
__device__ __forceinline__ uint32_t pack_bf(float lo, float hi) {
    uint32_t r;
    asm("cvt.rn.bf16x2.f32 %0, %1, %2;" : "=r"(r) : "f"(hi), "f"(lo));
    return r;
}
__device__ __forceinline__ float rbf(float x) { return bf_lo(pack_bf(x, 0.f)); }
__device__ __forceinline__ uint32_t hmul2(uint32_t a, uint32_t b) {
    uint32_t r;
    asm("mul.rn.bf16x2 %0, %1, %2;" : "=r"(r) : "r"(a), "r"(b));
    return r;
}
__device__ __forceinline__ uint32_t hsub2(uint32_t a, uint32_t b) {
    uint32_t r;
    asm("sub.rn.bf16x2 %0, %1, %2;" : "=r"(r) : "r"(a), "r"(b));
    return r;
}
__device__ __forceinline__ uint32_t lds32(uint32_t a) { uint32_t v; asm volatile("ld.shared.u32 %0, [%1];" : "=r"(v) : "r"(a)); return v; }
__device__ __forceinline__ uint32_t lds16(uint32_t a) { uint16_t v; asm volatile("ld.shared.u16 %0, [%1];" : "=h"(v) : "r"(a)); return v; }
__device__ __forceinline__ uint2 lds64(uint32_t a) { uint2 v; asm volatile("ld.shared.v2.u32 {%0,%1}, [%2];" : "=r"(v.x), "=r"(v.y) : "r"(a)); return v; }
__device__ __forceinline__ uint4 lds128(uint32_t a) { uint4 v; asm volatile("ld.shared.v4.u32 {%0,%1,%2,%3}, [%4];" : "=r"(v.x), "=r"(v.y), "=r"(v.z), "=r"(v.w) : "r"(a)); return v; }
__device__ __forceinline__ void sts32(uint32_t a, uint32_t v) { asm volatile("st.shared.u32 [%0], %1;" ::"r"(a), "r"(v) : "memory"); }
__device__ __forceinline__ void sts128(uint32_t a, uint4 v) { asm volatile("st.shared.v4.u32 [%0], {%1,%2,%3,%4};" ::"r"(a), "r"(v.x), "r"(v.y), "r"(v.z), "r"(v.w) : "memory"); }
__device__ __forceinline__ void mbar_init(uint32_t bar, int cnt) { asm volatile("mbarrier.init.shared::cta.b64 [%0], %1;" ::"r"(bar), "r"(cnt) : "memory"); }
__device__ __forceinline__ void mbar_expect_tx(uint32_t bar, uint32_t bytes) { asm volatile("mbarrier.arrive.expect_tx.shared::cta.b64 _, [%0], %1;" ::"r"(bar), "r"(bytes) : "memory"); }
__device__ __forceinline__ void mbar_arrive(uint32_t bar) { asm volatile("mbarrier.arrive.shared::cta.b64 _, [%0];" ::"r"(bar) : "memory"); }
__device__ __forceinline__ void mbar_wait(uint32_t bar, uint32_t parity) {
    asm volatile("{\n.reg .pred p;\n.reg .u32 c;\n"
                 "mbarrier.try_wait.parity.shared::cta.b64 p, [%0], %1;\n"
                 "@p bra DONE_%=;\n"
                 "mov.u32 c, 0;\n"
                 "LOOP_%=:\n"
                 "mbarrier.try_wait.parity.shared::cta.b64 p, [%0], %1;\n"
                 "@p bra DONE_%=;\n"
                 "add.u32 c, c, 1;\n"
                 "setp.lt.u32 p, c, 4194304;\n"
                 "@p bra LOOP_%=;\n"
                 "DONE_%=:\n}"
                 ::"r"(bar), "r"(parity) : "memory");
}
__device__ __forceinline__ void mbar_arrive_elected(uint32_t bar) {
    asm volatile("{\n.reg .pred p;\nelect.sync _|p, 0xffffffff;\n@p mbarrier.arrive.shared::cta.b64 _, [%0];\n}" ::"r"(bar) : "memory");
}
__device__ __forceinline__ void bulk_g2s(uint32_t dst, const void* src, uint32_t bytes, uint32_t bar) {
    asm volatile("cp.async.bulk.shared::cluster.global.mbarrier::complete_tx::bytes [%0], [%1], %2, [%3];"
                 ::"r"(dst), "l"(src), "r"(bytes), "r"(bar) : "memory");
}
__device__ __forceinline__ void tma_load(uint32_t dst, const CUtensorMap* tm, int line, uint32_t bar) {
    asm volatile("cp.async.bulk.tensor.2d.shared::cluster.global.mbarrier::complete_tx::bytes [%0], [%1, {%3, %4}], [%2];"
                 ::"r"(dst), "l"(tm), "r"(bar), "r"(0), "r"(line) : "memory");
}
__device__ __forceinline__ void tma_store(const CUtensorMap* tm, int line, uint32_t src) {
    asm volatile("cp.async.bulk.tensor.2d.global.shared::cta.bulk_group [%0, {%2, %3}], [%1];"
                 ::"l"(tm), "r"(src), "r"(0), "r"(line) : "memory");
}
__device__ __forceinline__ void fence_async_smem() { asm volatile("fence.proxy.async.shared::cta;" ::: "memory"); }
__device__ __forceinline__ void named_barrier(int id) { asm volatile("bar.sync %0, 128;" ::"r"(id) : "memory"); }
__device__ __forceinline__ void ldsm4(uint32_t (&r)[4], uint32_t a) {
    asm volatile("ldmatrix.sync.aligned.m8n8.x4.shared.b16 {%0,%1,%2,%3}, [%4];" : "=r"(r[0]), "=r"(r[1]), "=r"(r[2]), "=r"(r[3]) : "r"(a) : "memory");
}
__device__ __forceinline__ void ldsm4t(uint32_t (&r)[4], uint32_t a) {
    asm volatile("ldmatrix.sync.aligned.m8n8.x4.trans.shared.b16 {%0,%1,%2,%3}, [%4];" : "=r"(r[0]), "=r"(r[1]), "=r"(r[2]), "=r"(r[3]) : "r"(a) : "memory");
}
__device__ __forceinline__ void stsm4(uint32_t a, uint32_t r0, uint32_t r1, uint32_t r2, uint32_t r3) {
    asm volatile("stmatrix.sync.aligned.m8n8.x4.shared.b16 [%0], {%1,%2,%3,%4};" ::"r"(a), "r"(r0), "r"(r1), "r"(r2), "r"(r3) : "memory");
}
__device__ __forceinline__ void mma16816(float (&c)[4], const uint32_t (&a)[4], uint32_t b0, uint32_t b1) {
    asm volatile("mma.sync.aligned.m16n8k16.row.col.f32.bf16.bf16.f32 {%0,%1,%2,%3}, {%4,%5,%6,%7}, {%8,%9}, {%0,%1,%2,%3};"
                 : "+f"(c[0]), "+f"(c[1]), "+f"(c[2]), "+f"(c[3])
                 : "r"(a[0]), "r"(a[1]), "r"(a[2]), "r"(a[3]), "r"(b0), "r"(b1));
}

__device__ __forceinline__ uint32_t desc_lo(uint32_t saddr) { return ((saddr & 0x3FFFF) >> 4) | (1u << 16); }
#define DESC_HI "0x40000040"
__device__ __forceinline__ void wg_fence() { asm volatile("wgmma.fence.sync.aligned;" ::: "memory"); }
__device__ __forceinline__ void wg_commit() { asm volatile("wgmma.commit_group.sync.aligned;" ::: "memory"); }
__device__ __forceinline__ void wg_wait0() { asm volatile("wgmma.wait_group.sync.aligned 0;" ::: "memory"); }
__device__ __forceinline__ void wg_wait1() { asm volatile("wgmma.wait_group.sync.aligned 1;" ::: "memory"); }

__device__ __forceinline__ void wgmma_n64_first(float (&d)[8], float (&e)[24], const uint32_t (&a)[4], uint32_t bdesc) {
    asm volatile("{\n.reg .b64 b;\nmov.b64 b, {%36, " DESC_HI "};\n"
                 "wgmma.mma_async.sync.aligned.m64n64k16.f32.bf16.bf16 {%0,%1,%2,%3,%4,%5,%6,%7,%8,%9,%10,%11,%12,%13,%14,%15,%16,%17,%18,%19,%20,%21,%22,%23,%24,%25,%26,%27,%28,%29,%30,%31}, {%32,%33,%34,%35}, b, 0, 1, 1, 1;\n}"
                 : "=f"(d[0]), "=f"(d[1]), "=f"(d[2]), "=f"(d[3]), "=f"(d[4]), "=f"(d[5]), "=f"(d[6]), "=f"(d[7]),
                   "=f"(e[0]), "=f"(e[1]), "=f"(e[2]), "=f"(e[3]), "=f"(e[4]), "=f"(e[5]), "=f"(e[6]), "=f"(e[7]), "=f"(e[8]), "=f"(e[9]), "=f"(e[10]), "=f"(e[11]), "=f"(e[12]), "=f"(e[13]), "=f"(e[14]), "=f"(e[15]), "=f"(e[16]), "=f"(e[17]), "=f"(e[18]), "=f"(e[19]), "=f"(e[20]), "=f"(e[21]), "=f"(e[22]), "=f"(e[23])
                 : "r"(a[0]), "r"(a[1]), "r"(a[2]), "r"(a[3]), "r"(bdesc));
}
__device__ __forceinline__ void wgmma_n64(float (&d)[8], float (&e)[24], const uint32_t (&a)[4], uint32_t bdesc) {
    asm volatile("{\n.reg .b64 b;\nmov.b64 b, {%36, " DESC_HI "};\n"
                 "wgmma.mma_async.sync.aligned.m64n64k16.f32.bf16.bf16 {%0,%1,%2,%3,%4,%5,%6,%7,%8,%9,%10,%11,%12,%13,%14,%15,%16,%17,%18,%19,%20,%21,%22,%23,%24,%25,%26,%27,%28,%29,%30,%31}, {%32,%33,%34,%35}, b, 1, 1, 1, 1;\n}"
                 : "+f"(d[0]), "+f"(d[1]), "+f"(d[2]), "+f"(d[3]), "+f"(d[4]), "+f"(d[5]), "+f"(d[6]), "+f"(d[7]),
                   "+f"(e[0]), "+f"(e[1]), "+f"(e[2]), "+f"(e[3]), "+f"(e[4]), "+f"(e[5]), "+f"(e[6]), "+f"(e[7]), "+f"(e[8]), "+f"(e[9]), "+f"(e[10]), "+f"(e[11]), "+f"(e[12]), "+f"(e[13]), "+f"(e[14]), "+f"(e[15]), "+f"(e[16]), "+f"(e[17]), "+f"(e[18]), "+f"(e[19]), "+f"(e[20]), "+f"(e[21]), "+f"(e[22]), "+f"(e[23])
                 : "r"(a[0]), "r"(a[1]), "r"(a[2]), "r"(a[3]), "r"(bdesc));
}
__device__ __forceinline__ void wgmma_n48_first(float (&e)[24], const uint32_t (&a)[4], uint32_t bdesc) {
    asm volatile("{\n.reg .b64 b;\nmov.b64 b, {%28, " DESC_HI "};\n"
                 "wgmma.mma_async.sync.aligned.m64n48k16.f32.bf16.bf16 {%0,%1,%2,%3,%4,%5,%6,%7,%8,%9,%10,%11,%12,%13,%14,%15,%16,%17,%18,%19,%20,%21,%22,%23}, {%24,%25,%26,%27}, b, 0, 1, 1, 1;\n}"
                 : "=f"(e[0]), "=f"(e[1]), "=f"(e[2]), "=f"(e[3]), "=f"(e[4]), "=f"(e[5]), "=f"(e[6]), "=f"(e[7]), "=f"(e[8]), "=f"(e[9]), "=f"(e[10]), "=f"(e[11]), "=f"(e[12]), "=f"(e[13]), "=f"(e[14]), "=f"(e[15]), "=f"(e[16]), "=f"(e[17]), "=f"(e[18]), "=f"(e[19]), "=f"(e[20]), "=f"(e[21]), "=f"(e[22]), "=f"(e[23])
                 : "r"(a[0]), "r"(a[1]), "r"(a[2]), "r"(a[3]), "r"(bdesc));
}
__device__ __forceinline__ void wgmma_n48(float (&e)[24], const uint32_t (&a)[4], uint32_t bdesc) {
    asm volatile("{\n.reg .b64 b;\nmov.b64 b, {%28, " DESC_HI "};\n"
                 "wgmma.mma_async.sync.aligned.m64n48k16.f32.bf16.bf16 {%0,%1,%2,%3,%4,%5,%6,%7,%8,%9,%10,%11,%12,%13,%14,%15,%16,%17,%18,%19,%20,%21,%22,%23}, {%24,%25,%26,%27}, b, 1, 1, 1, 1;\n}"
                 : "+f"(e[0]), "+f"(e[1]), "+f"(e[2]), "+f"(e[3]), "+f"(e[4]), "+f"(e[5]), "+f"(e[6]), "+f"(e[7]), "+f"(e[8]), "+f"(e[9]), "+f"(e[10]), "+f"(e[11]), "+f"(e[12]), "+f"(e[13]), "+f"(e[14]), "+f"(e[15]), "+f"(e[16]), "+f"(e[17]), "+f"(e[18]), "+f"(e[19]), "+f"(e[20]), "+f"(e[21]), "+f"(e[22]), "+f"(e[23])
                 : "r"(a[0]), "r"(a[1]), "r"(a[2]), "r"(a[3]), "r"(bdesc));
}
__device__ __forceinline__ void wgmma_n16_first(float (&d)[8], const uint32_t (&a)[4], uint32_t bdesc) {
    asm volatile("{\n.reg .b64 b;\nmov.b64 b, {%12, " DESC_HI "};\n"
                 "wgmma.mma_async.sync.aligned.m64n16k16.f32.bf16.bf16 {%0,%1,%2,%3,%4,%5,%6,%7}, {%8,%9,%10,%11}, b, 0, 1, 1, 1;\n}"
                 : "=f"(d[0]), "=f"(d[1]), "=f"(d[2]), "=f"(d[3]), "=f"(d[4]), "=f"(d[5]), "=f"(d[6]), "=f"(d[7])
                 : "r"(a[0]), "r"(a[1]), "r"(a[2]), "r"(a[3]), "r"(bdesc));
}
__device__ __forceinline__ void wgmma_n16(float (&d)[8], const uint32_t (&a)[4], uint32_t bdesc) {
    asm volatile("{\n.reg .b64 b;\nmov.b64 b, {%12, " DESC_HI "};\n"
                 "wgmma.mma_async.sync.aligned.m64n16k16.f32.bf16.bf16 {%0,%1,%2,%3,%4,%5,%6,%7}, {%8,%9,%10,%11}, b, 1, 1, 1, 1;\n}"
                 : "+f"(d[0]), "+f"(d[1]), "+f"(d[2]), "+f"(d[3]), "+f"(d[4]), "+f"(d[5]), "+f"(d[6]), "+f"(d[7])
                 : "r"(a[0]), "r"(a[1]), "r"(a[2]), "r"(a[3]), "r"(bdesc));
}

__device__ __forceinline__ void wgmma_n64_p(float (&d)[8], float (&e)[24], const uint32_t (&a)[4], uint32_t bdesc, int acc) {
    asm volatile("{\n.reg .pred p;\n.reg .b64 b;\nsetp.ne.b32 p, %37, 0;\nmov.b64 b, {%36, " DESC_HI "};\n"
                 "wgmma.mma_async.sync.aligned.m64n64k16.f32.bf16.bf16 {%0,%1,%2,%3,%4,%5,%6,%7,%8,%9,%10,%11,%12,%13,%14,%15,%16,%17,%18,%19,%20,%21,%22,%23,%24,%25,%26,%27,%28,%29,%30,%31}, {%32,%33,%34,%35}, b, p, 1, 1, 1;\n}"
                 : "+f"(d[0]), "+f"(d[1]), "+f"(d[2]), "+f"(d[3]), "+f"(d[4]), "+f"(d[5]), "+f"(d[6]), "+f"(d[7]),
                   "+f"(e[0]), "+f"(e[1]), "+f"(e[2]), "+f"(e[3]), "+f"(e[4]), "+f"(e[5]), "+f"(e[6]), "+f"(e[7]), "+f"(e[8]), "+f"(e[9]), "+f"(e[10]), "+f"(e[11]), "+f"(e[12]), "+f"(e[13]), "+f"(e[14]), "+f"(e[15]), "+f"(e[16]), "+f"(e[17]), "+f"(e[18]), "+f"(e[19]), "+f"(e[20]), "+f"(e[21]), "+f"(e[22]), "+f"(e[23])
                 : "r"(a[0]), "r"(a[1]), "r"(a[2]), "r"(a[3]), "r"(bdesc), "r"(acc));
}
__device__ __forceinline__ void wgmma_n16_p(float (&d)[8], const uint32_t (&a)[4], uint32_t bdesc, int acc) {
    asm volatile("{\n.reg .pred p;\n.reg .b64 b;\nsetp.ne.b32 p, %13, 0;\nmov.b64 b, {%12, " DESC_HI "};\n"
                 "wgmma.mma_async.sync.aligned.m64n16k16.f32.bf16.bf16 {%0,%1,%2,%3,%4,%5,%6,%7}, {%8,%9,%10,%11}, b, p, 1, 1, 1;\n}"
                 : "+f"(d[0]), "+f"(d[1]), "+f"(d[2]), "+f"(d[3]), "+f"(d[4]), "+f"(d[5]), "+f"(d[6]), "+f"(d[7])
                 : "r"(a[0]), "r"(a[1]), "r"(a[2]), "r"(a[3]), "r"(bdesc), "r"(acc));
}

__device__ __forceinline__ uint32_t edge_dist(uint32_t sxy, uint32_t sz, uint32_t dxy, uint32_t dz, uint32_t& rxy, uint32_t& rz) {
    rxy = hsub2(sxy, dxy);
    rz  = hsub2(sz, dz);
    uint32_t qxy = hmul2(rxy, rxy), qz = hmul2(rz, rz);
    float ss = rbf((bf_lo(qxy) + bf_hi(qxy)) + bf_lo(qz));
    float s2 = rbf(ss + 1e-8f);
    float d;
    asm("sqrt.approx.ftz.f32 %0, %1;" : "=f"(d) : "f"(s2));
    return pack_bf(d, 0.f) & 0xffffu;
}

__device__ __forceinline__ void load_pos(uint32_t sm_pos, int i, uint32_t& xy, uint32_t& z) {
    uint32_t a  = (sm_pos + 6u * (uint32_t)i) & ~3u;
    uint32_t w0 = lds32(a), w1 = lds32(a + 4);
    uint32_t sh = (uint32_t)i << 4;
    xy = __funnelshift_r(w0, w1, sh);
    z  = __funnelshift_r(w1, w1, sh);
}

__device__ __noinline__ float radial_value(float d, float f) {
    float arg = rbf(d * f);
    float sn  = rbf(sinf(arg));
    float rb  = rbf(__fdiv_rn(sn, d));
    float c   = rbf(cosf(rbf(__fdiv_rn(rbf(d * 3.14159265358979323846f), 5.0f))));
    float fc  = rbf(0.5f * rbf(c + 1.0f));
    return rb * fc;
}

__global__ void __launch_bounds__(NT, 1)
painn_kernel(const Params p, const __grid_constant__ CUtensorMap tmF, const __grid_constant__ CUtensorMap tmSV,
             const __grid_constant__ CUtensorMap tmW1, const __grid_constant__ CUtensorMap tmW2) {
    extern __shared__ __align__(1024) uint8_t smem[];
    const uint32_t sb   = smem_u32(smem);
    const int tid  = threadIdx.x, lane = tid & 31, warp = __shfl_sync(0xffffffffu, tid >> 5, 0);
    const int cta  = blockIdx.x;
    const int g    = lane >> 2, t = lane & 3;
    int* binCnt = (int*)(smem + SM_BINCNT);
    int* binOff = (int*)(smem + SM_BINOFF);
    int* nCnt   = (int*)(smem + SM_NCNT);
    uint32_t* nInfo = (uint32_t*)(smem + SM_NINFO);
    volatile int* ctrl = (volatile int*)(smem + SM_CTRL);
    const uint32_t bar_pos = sb + SM_BARS, bar_mlp = bar_pos + 8, bar_rec = bar_pos + 16;
    const uint32_t bar_full = bar_pos + 32, bar_empty = bar_full + NCWG * MAX_STAGE * 8;

    const int node0  = cta * p.npc;
    const int nnodes = max(0, min(p.npc, p.N - node0));

    STAMP(0);
    if (tid == 0) {
        mbar_init(bar_pos, 1);
        asm volatile("fence.mbarrier_init.release.cluster;" ::: "memory");
        uint32_t pos_bytes = (uint32_t)(p.N * 6 + 15) & ~15u;
        mbar_expect_tx(bar_pos, pos_bytes);
        bulk_g2s(sb + P1_POS, p.pos, pos_bytes, bar_pos);
    } else if (tid == 32) {
        mbar_init(bar_mlp, 1);
        asm volatile("fence.mbarrier_init.release.cluster;" ::: "memory");
        mbar_expect_tx(bar_mlp, 2u * 160u * 128u + 8192u + 24576u);
        tma_load(sb + P1_W1, &tmW1, 0, bar_mlp);
        tma_load(sb + P1_SV, &tmSV, node0 * 4, bar_mlp);
        tma_load(sb + P1_W2, &tmW2, 0, bar_mlp);
        tma_load(sb + P1_SV + 160 * 128, &tmSV, node0 * 4 + 160, bar_mlp);
    } else if (tid == 64) {
        mbar_init(bar_rec, 1);
        for (int i = 0; i < NCWG * MAX_STAGE; i++) { mbar_init(bar_full + 8 * i, 1); mbar_init(bar_empty + 8 * i, 4); }
        asm volatile("fence.mbarrier_init.release.cluster;" ::: "memory");
        asm volatile("prefetch.tensormap [%0];" ::"l"(&tmF) : "memory");
    } else if (tid == 96 || tid == 97) {
        unsigned cur;
        asm volatile("ld.relaxed.gpu.global.u32 %0, [%1];" : "=r"(cur) : "l"(&g_bar[tid - 96]) : "memory");
        ctrl[10 + tid - 96] = (int)((cur / (unsigned)p.ncta + 1u) * (unsigned)p.ncta);
    }
    const bool mlp_warp = warp >= 6;
    int4 s4[3], d4[3];
    const int q0 = cta * p.quads_per_cta;
    const int qend = min(q0 + p.quads_per_cta, p.E >> 2);
#pragma unroll
    for (int k = 0; k < 3; k++) {
        const int q = q0 + (k < 2 ? warp + 16 * k : 32 + warp) * 32 + lane;
        const bool ok = q < qend && (k < 2 || !mlp_warp);
        s4[k] = ok ? __ldg((const int4*)p.src + q) : make_int4(-1, -1, -1, -1);
        d4[k] = ok ? __ldg((const int4*)p.dst + q) : make_int4(0, 0, 0, 0);
    }
    if (tid < MAX_CTA) binCnt[tid] = 0;
    if (tid < MAX_NPC) nCnt[tid] = 0;
    if (tid < 10) ctrl[tid] = 0;
    if (tid >= 416 && tid < 416 + 48) {
        asm volatile("prefetch.global.L2 [%0];" ::"l"((const uint8_t*)p.wr + (tid - 416) * 128));
    }
    for (int i = P1_STAGE / 16 + tid; i < P1_SV / 16; i += NT) sts128(sb + i * 16, make_uint4(0u, 0u, 0u, 0u));
    __syncthreads();

    if (!mlp_warp) {
        const int rows_per = (TAB_ROWS + 1 + p.ncta - 1) / p.ncta;
        for (int i = tid; i < rows_per * 8; i += 6 * 32) {
            int row = cta * rows_per + (i >> 3), kp = i & 7;
            if (row <= TAB_ROWS) {
                uint32_t val = 0;
                if (row < TAB_ROWS) {
                    float d = __uint_as_float((D_MIN_BITS + row) << 16);
                    uint32_t f2 = __ldg((const uint32_t*)p.freqs + kp);
                    val = pack_bf(radial_value(d, bf_lo(f2)), radial_value(d, bf_hi(f2)));
                }
                ((uint32_t*)g_table)[row * 8 + kp] = val;
            }
        }
    } else {
        const int mt = (warp - 6) >> 1, hf = (warp - 6) & 1;
        if (mt * 16 < nnodes) {
            mbar_wait(bar_mlp, 0);
            STAMPT(10, 6 * 32);
            const int lrow = lane & 15, lch = lane >> 4;
            const uint32_t rowb = sb + P1_SV + (mt * 16 + lrow) * 512;
            const uint32_t key0 = (4 * lrow) & 7;
            float acc[4][4];
#pragma unroll
            for (int i = 0; i < 4; i++) { acc[i][0] = acc[i][1] = acc[i][2] = acc[i][3] = 0.f; }
#pragma unroll
            for (int ks = 0; ks < 4; ks++) {
                uint32_t a[4];
                ldsm4(a, rowb + (((2 * ks + lch) ^ key0) << 4));
                const int kk = 16 * ks + lrow;
#pragma unroll
                for (int nt = 0; nt < 4; nt += 2) {
                    uint32_t b[4];
                    ldsm4t(b, sb + P1_W1 + kk * 128 + (((4 * hf + nt + lch) ^ (kk & 7)) << 4));
                    mma16816(acc[nt], a, b[0], b[1]);
                    mma16816(acc[nt + 1], a, b[2], b[3]);
                }
            }
            uint32_t hp[4][2];
#pragma unroll
            for (int i = 0; i < 4; i++) {
                float h[4];
#pragma unroll
                for (int q = 0; q < 4; q++) {
                    float x = rbf(acc[i][q]);
                    h[q] = __fdividef(x, 1.0f + __expf(-x));
                    acc[i][q] = 0.f;
                }
                hp[i][0] = pack_bf(h[0], h[1]);
                hp[i][1] = pack_bf(h[2], h[3]);
            }
            asm volatile("bar.sync %0, 64;" ::"r"(4 + mt) : "memory");
#pragma unroll
            for (int i = 0; i < 4; i += 2)
                stsm4(rowb + (((4 * hf + i + lch) ^ key0) << 4), hp[i][0], hp[i][1], hp[i + 1][0], hp[i + 1][1]);
            asm volatile("bar.sync %0, 64;" ::"r"(4 + mt) : "memory");
#pragma unroll
            for (int ks = 0; ks < 4; ks++) {
                uint32_t a[4];
                ldsm4(a, rowb + (((2 * ks + lch) ^ key0) << 4));
                const int line = 3 * (16 * ks + lrow) + 1;
#pragma unroll
                for (int nt = 0; nt < 4; nt += 2) {
                    uint32_t b[4];
                    ldsm4t(b, sb + P1_W2 + line * 128 + (((4 * hf + nt + lch) ^ (line & 7)) << 4));
                    mma16816(acc[nt], a, b[0], b[1]);
                    mma16816(acc[nt + 1], a, b[2], b[3]);
                }
            }
#pragma unroll
            for (int rh = 0; rh < 2; rh++) {
                const int row = mt * 16 + g + 8 * rh;
#pragma unroll
                for (int a = 0; a < 3; a++) {
                    const int line = 4 * row + 1 + a;
                    const uint32_t lb = sb + P1_SV + line * 128 + 4 * t;
#pragma unroll
                    for (int i = 0; i < 4; i++) {
                        const uint32_t ad = lb + (((4 * hf + i) ^ (line & 7)) << 4);
                        sts32(ad, hmul2(pack_bf(acc[i][2 * rh], acc[i][2 * rh + 1]), lds32(ad)));
                    }
                }
            }
            fence_async_smem();
            asm volatile("bar.sync %0, 64;" ::"r"(4 + mt) : "memory");
            if (lane < 8 && mt * 16 + 8 * hf + lane < nnodes)
                tma_store(&tmF, (node0 + mt * 16 + 8 * hf + lane) * 4, sb + P1_SV + (mt * 16 + 8 * hf + lane) * 512);
            asm volatile("cp.async.bulk.commit_group;" ::: "memory");
        }
        STAMPT(11, 6 * 32);
    }
    mbar_wait(bar_pos, 0);
    STAMP(1);

    uint32_t r0[12], r1[12], r2[12], rk[12];
#pragma unroll
    for (int k = 0; k < 3; k++) {
        const int ss[4] = {s4[k].x, s4[k].y, s4[k].z, s4[k].w};
        const int dd[4] = {d4[k].x, d4[k].y, d4[k].z, d4[k].w};
#pragma unroll
        for (int j = 0; j < 4; j++) rk[k * 4 + j] = 0xffffffffu;
        if (ss[0] >= 0) {
#pragma unroll
            for (int j = 0; j < 4; j++) {
                const int e = k * 4 + j;
                const int s = ss[j], d = dd[j];
                uint32_t sxy, sz, dxy, dz, rxy, rz;
                load_pos(sb + P1_POS, s, sxy, sz);
                load_pos(sb + P1_POS, d, dxy, dz);
                uint32_t db = edge_dist(sxy, sz, dxy, dz, rxy, rz);
                float inv;
                asm("rcp.approx.ftz.f32 %0, %1;" : "=f"(inv) : "f"(__uint_as_float(db << 16)));
                uint32_t bin = __umulhi((uint32_t)d, p.npc_magic);
                uint32_t dl  = (uint32_t)d - bin * (uint32_t)p.npc;
                r0[e] = (uint32_t)s | ((db - D_MIN_BITS) << 16);
                r1[e] = pack_bf(bf_lo(rxy) * inv, bf_hi(rxy) * inv);
                r2[e] = __byte_perm(pack_bf(bf_lo(rz) * inv, 0.f), dl, 0x5410);
                if (db <= D_MAX_BITS) rk[e] = (uint32_t)atomicAdd(&binCnt[bin], 1) | (bin << 16);
            }
        }
    }
    STAMP(2);
    STAMPT(12, 6 * 32);
    __syncthreads();
    STAMP(3);
    if (warp == 0) {
        int c[5], s = 0;
#pragma unroll
        for (int i = 0; i < 5; i++) { int b = lane * 5 + i; c[i] = b < p.ncta ? binCnt[b] : 0; s += c[i]; }
        int x = s;
#pragma unroll
        for (int o = 1; o < 32; o <<= 1) { int y = __shfl_up_sync(0xffffffffu, x, o); if (lane >= o) x += y; }
        int off = x - s;
#pragma unroll
        for (int i = 0; i < 5; i++) {
            int b = lane * 5 + i;
            if (b < p.ncta) { binOff[b] = off; g_offs[cta * MAX_CTA + b] = (uint32_t)off | ((uint32_t)c[i] << 16); }
            off += c[i];
        }
        if (lane == 31) ctrl[8] = x;
    }
    __syncthreads();
#pragma unroll
    for (int e = 0; e < 12; e++) {
        if (rk[e] != 0xffffffffu) {
            int pos = binOff[rk[e] >> 16] + (int)(rk[e] & 0xffffu);
            sts128(sb + P1_STAGE + pos * 16, make_uint4(r0[e], r1[e], r2[e], 0u));
        }
    }
    fence_async_smem();
    __syncthreads();
    if (tid == 0) {
        const uint32_t bytes = (uint32_t)ctrl[8] * 16u;
        if (bytes) asm volatile("cp.async.bulk.global.shared::cta.bulk_group [%0], [%1], %2;"
                                ::"l"(g_rec + (size_t)cta * REC_CAP), "r"(sb + P1_STAGE), "r"(bytes) : "memory");
        asm volatile("cp.async.bulk.commit_group;" ::: "memory");
    }
    if (tid == 32) asm volatile("red.add.release.gpu.global.u32 [%0], 1;" ::"l"(&g_bar[0]) : "memory");
    asm volatile("cp.async.bulk.wait_group 0;" ::: "memory");
    asm volatile("fence.proxy.async;" ::: "memory");

    __syncthreads();
    STAMP(4);
    if (tid == 0) asm volatile("red.add.release.gpu.global.u32 [%0], 1;" ::"l"(&g_bar[1]) : "memory");
    uint32_t wp[3][4];
    if (warp >= 4 && warp < 8) {
        const uint16_t* w2 = (const uint16_t*)p.w2 + 16 * (warp & 3) + g;
#pragma unroll 2
        for (int mk = 0; mk < 8; mk++) {
            uint32_t f[4];
#pragma unroll
            for (int i = 0; i < 4; i++) {
                const uint16_t* q = w2 + (16 * (mk & 3) + 2 * t + 8 * (i >> 1)) * 192 + (mk >> 2) * 128 + 8 * (i & 1);
                f[i] = (uint32_t)__ldg(q) | ((uint32_t)__ldg(q + 192) << 16);
            }
            sts128(sb + SM_HT + (mk * 128 + (tid & 127)) * 16, make_uint4(f[0], f[1], f[2], f[3]));
        }
    }
    if (warp < 4 * NCWG) {
        const uint16_t* wr = (const uint16_t*)p.wr + 16 * (warp & 3) + g;
#pragma unroll
        for (int ty = 0; ty < 3; ty++) {
#pragma unroll
            for (int i = 0; i < 4; i++) {
                const uint16_t* q = wr + (8 * (i >> 1) + 2 * t) * 192 + ty * 64 + 8 * (i & 1);
                wp[ty][i] = (uint32_t)__ldg(q) | ((uint32_t)__ldg(q + 192) << 16);
            }
        }
    }
    if (warp == 15) {
        if (lane == 0) {
            const unsigned target = (unsigned)ctrl[10];
            unsigned cur;
            int spins = 0;
            do {
                asm volatile("ld.acquire.gpu.global.u32 %0, [%1];" : "=r"(cur) : "l"(&g_bar[0]) : "memory");
            } while ((int)(cur - target) < 0 && ++spins < (1 << 24));
        }
        __syncwarp();
        uint32_t v[5];
        int s = 0;
#pragma unroll
        for (int i = 0; i < 5; i++) {
            int b = lane * 5 + i;
            v[i] = b < p.ncta ? __ldcg(&g_offs[b * MAX_CTA + cta]) : 0u;
        }
#pragma unroll
        for (int i = 0; i < 5; i++) s += (int)(v[i] >> 16);
        int x = s;
#pragma unroll
        for (int o = 1; o < 32; o <<= 1) { int y = __shfl_up_sync(0xffffffffu, x, o); if (lane >= o) x += y; }
        const int tot = __shfl_sync(0xffffffffu, x, 31);
        int off = x - s;
#pragma unroll
        for (int i = 0; i < 5; i++) {
            int b = lane * 5 + i;
            if (b < p.ncta) { binCnt[b] = (int)v[i]; binOff[b] = off; }
            off += (int)(v[i] >> 16);
        }
        if (lane == 0) {
            ctrl[8] = tot;
            if (tot > STAGE_CAP) ctrl[1] = 1;
            mbar_expect_tx(bar_rec, tot > STAGE_CAP ? 0u : (uint32_t)tot * 16u);
        }
    }
    if (tid == 14 * 32) {
        const unsigned target = (unsigned)ctrl[11];
        unsigned cur;
        int spins = 0;
        do {
            asm volatile("ld.acquire.gpu.global.u32 %0, [%1];" : "=r"(cur) : "l"(&g_bar[1]) : "memory");
        } while ((int)(cur - target) < 0 && ++spins < (1 << 24));
    }
    __syncthreads();
    STAMP(5);

    const int total = ctrl[8];
    if (ctrl[1] == 0) {
        const int b = (lane << 4) | warp;
        if (lane < 9 && b < p.ncta) {
            const uint32_t v = (uint32_t)binCnt[b], c = v >> 16;
            if (c) {
                asm volatile("fence.proxy.async;" ::: "memory");
                bulk_g2s(sb + SM_STAGE2 + (uint32_t)binOff[b] * 16u, g_rec + (size_t)b * REC_CAP + (v & 0xffffu), c * 16u, bar_rec);
            }
        }
    }
    mbar_wait(bar_rec, 0);
    STAMP(13);
    constexpr int RPT = 8;
    uint4 rec[RPT];
    const bool okc = ctrl[1] == 0;
#pragma unroll
    for (int k = 0; k < RPT; k++) {
        const int i = tid + k * NT;
        if (okc && i < total) rec[k] = lds128(sb + SM_STAGE2 + i * 16);
    }
#pragma unroll
    for (int k = 0; k < RPT; k++) {
        const int i = tid + k * NT;
        if (okc && i < total) rec[k].w = (uint32_t)atomicAdd(&nCnt[rec[k].z >> 16], 1);
    }
    if (okc) {
        for (int i = tid + RPT * NT; i < total; i += NT) {
            uint32_t dl = lds32(sb + SM_STAGE2 + i * 16 + 8) >> 16;
            sts32(sb + SM_STAGE2 + i * 16 + 12, (uint32_t)atomicAdd(&nCnt[dl], 1));
        }
    }
    __syncthreads();
    if (warp == 0) {
        int c[3], s = 0;
#pragma unroll
        for (int i = 0; i < 3; i++) {
            int b = lane * 3 + i;
            c[i] = b < nnodes ? max(16, (nCnt[b] + 15) & ~15) : 0;
            s += c[i];
        }
        int x = s;
#pragma unroll
        for (int o = 1; o < 32; o <<= 1) { int y = __shfl_up_sync(0xffffffffu, x, o); if (lane >= o) x += y; }
        const int slots = __shfl_sync(0xffffffffu, x, 31);
        int off = x - s, below = 0;
#pragma unroll
        for (int i = 0; i < 3; i++) {
            int b = lane * 3 + i;
            if (b < nnodes) {
                nInfo[b] = (uint32_t)off | ((uint32_t)c[i] << 16);
                below += (2 * off + c[i] < slots);
            }
            off += c[i];
        }
        below = __reduce_add_sync(0xffffffffu, below);
        if (lane == 0) {
            ctrl[2] = below;
            ctrl[4] = slots;
            if (slots > SLOT_CAP) ctrl[1] = 1;
        }
    }
    __syncthreads();
    if (ctrl[1] == 0) {
        uint16_t* sid = (uint16_t*)(smem + SM_SID);
        uint2* meta = (uint2*)(smem + SM_META);
#pragma unroll
        for (int k = 0; k < RPT; k++) {
            if (tid + k * NT < total) {
                const uint4 r = rec[k];
                int pos = (int)(nInfo[r.z >> 16] & 0xffffu) + (int)r.w;
                sid[pos]  = (uint16_t)(r.x & 0xffffu);
                meta[pos] = make_uint2(((r.x >> 16) << 5) | (r.z << 16), r.y);
            }
        }
        for (int i = tid + RPT * NT; i < total; i += NT) {
            uint4 r = lds128(sb + SM_STAGE2 + i * 16);
            int pos = (int)(nInfo[r.z >> 16] & 0xffffu) + (int)r.w;
            sid[pos]  = (uint16_t)(r.x & 0xffffu);
            meta[pos] = make_uint2(((r.x >> 16) << 5) | (r.z << 16), r.y);
        }
        for (int i = tid; i < nnodes * 16; i += NT) {
            int nl = i >> 4, c = nCnt[nl];
            int j = (c & ~15) + (i & 15);
            if (j >= c && (j < 16 || (c & 15))) {
                int pos = (int)(nInfo[nl] & 0xffffu) + j;
                sid[pos]  = 0xffffu;
                meta[pos] = make_uint2((uint32_t)TAB_ZERO << 5, 0u);
            }
        }
    }
    fence_async_smem();
    __syncthreads();
    STAMP(6);

    if (__shfl_sync(0xffffffffu, ctrl[1], 0) != 0) {
        float* acc = (float*)(smem + P1_POS);
        for (int i = tid; i < nnodes * 256; i += NT) acc[i] = 0.f;
        __syncthreads();
        const uint16_t* posu = (const uint16_t*)p.pos;
        const uint32_t* tabg = (const uint32_t*)g_table;
        const uint32_t* Fw = (const uint32_t*)g_F;
        for (int e0 = warp * 32; e0 < p.E; e0 += NT) {
            int e = e0 + lane;
            int s = 0, d = 0;
            uint32_t db = 0xffff, rxy = 0, rz = 0;
            bool act = false;
            if (e < p.E) {
                s = p.src[e]; d = p.dst[e];
                if (d >= node0 && d < node0 + nnodes) {
                    uint32_t sxy = posu[s * 3] | ((uint32_t)posu[s * 3 + 1] << 16), sz = posu[s * 3 + 2];
                    uint32_t dxy = posu[d * 3] | ((uint32_t)posu[d * 3 + 1] << 16), dz = posu[d * 3 + 2];
                    db  = edge_dist(sxy, sz, dxy, dz, rxy, rz);
                    act = db <= D_MAX_BITS;
                }
            }
            unsigned m = __ballot_sync(0xffffffffu, act);
            while (m) {
                int l = __ffs(m) - 1;
                m &= m - 1;
                int es = __shfl_sync(0xffffffffu, s, l), ed = __shfl_sync(0xffffffffu, d, l);
                uint32_t edb = __shfl_sync(0xffffffffu, db, l), exy = __shfl_sync(0xffffffffu, rxy, l), ez = __shfl_sync(0xffffffffu, rz, l);
                float inv = 1.0f / __uint_as_float(edb << 16);
                float rh[3] = {rbf(bf_lo(exy) * inv), rbf(bf_hi(exy) * inv), rbf(bf_lo(ez) * inv)};
                const uint32_t* fr = Fw + (size_t)es * 128 + lane;
                const uint32_t fh = __ldcg(fr);
                const uint32_t q[3] = {__ldcg(fr + 32), __ldcg(fr + 64), __ldcg(fr + 96)};
                float ps0 = 0.f, ps1 = 0.f, pr0 = 0.f, pr1 = 0.f;
                for (int j2 = 0; j2 < 32; j2++) {
                    uint32_t hj = __shfl_sync(0xffffffffu, fh, j2);
                    uint32_t a0 = *(const uint32_t*)(p.w2 + (2 * j2) * 192 + 2 * lane), a1 = *(const uint32_t*)(p.w2 + (2 * j2 + 1) * 192 + 2 * lane);
                    uint32_t b0 = *(const uint32_t*)(p.w2 + (2 * j2) * 192 + 128 + 2 * lane), b1 = *(const uint32_t*)(p.w2 + (2 * j2 + 1) * 192 + 128 + 2 * lane);
                    ps0 += bf_lo(hj) * bf_lo(a0) + bf_hi(hj) * bf_lo(a1);
                    ps1 += bf_lo(hj) * bf_hi(a0) + bf_hi(hj) * bf_hi(a1);
                    pr0 += bf_lo(hj) * bf_lo(b0) + bf_hi(hj) * bf_lo(b1);
                    pr1 += bf_lo(hj) * bf_hi(b0) + bf_hi(hj) * bf_hi(b1);
                }
                float ws0 = 0.f, ws1 = 0.f, wv0 = 0.f, wv1 = 0.f, wr0 = 0.f, wr1 = 0.f;
                for (int k2 = 0; k2 < 8; k2++) {
                    uint32_t rk2 = __ldcg(tabg + (edb - D_MIN_BITS) * 8 + k2);
#pragma unroll
                    for (int h = 0; h < 2; h++) {
                        float rv = h ? bf_hi(rk2) : bf_lo(rk2);
                        const __nv_bfloat16* wrow = p.wr + (2 * k2 + h) * 192 + 2 * lane;
                        uint32_t a = *(const uint32_t*)wrow, b = *(const uint32_t*)(wrow + 64), c = *(const uint32_t*)(wrow + 128);
                        ws0 += rv * bf_lo(a); ws1 += rv * bf_hi(a);
                        wv0 += rv * bf_lo(b); wv1 += rv * bf_hi(b);
                        wr0 += rv * bf_lo(c); wr1 += rv * bf_hi(c);
                    }
                }
                float* a = acc + (ed - node0) * 256 + 2 * lane;
                atomicAdd(a, ps0 * ws0); atomicAdd(a + 1, ps1 * ws1);
#pragma unroll
                for (int c = 0; c < 3; c++) {
                    atomicAdd(a + 64 * (c + 1), wv0 * bf_lo(q[c]) + pr0 * wr0 * rh[c]);
                    atomicAdd(a + 64 * (c + 1) + 1, wv1 * bf_hi(q[c]) + pr1 * wr1 * rh[c]);
                }
            }
        }
        __syncthreads();
        for (int i = tid; i < nnodes * 128; i += NT) {
            uint32_t r = *(const uint32_t*)(p.sv + (size_t)node0 * 256 + 2 * i);
            *(uint32_t*)(p.out + (size_t)node0 * 256 + 2 * i) = pack_bf(bf_lo(r) + acc[2 * i], bf_hi(r) + acc[2 * i + 1]);
        }
        return;
    }

    const int slots = __reduce_max_sync(0xffffffffu, ctrl[4]);
    const int split = __reduce_max_sync(0xffffffffu, ctrl[2]);
    const int nstage = slots <= SLOT_CAP4 ? 6 : 5;
    const uint32_t ring = sb + (nstage == 6 ? SM_RING4 : SM_RING3);
    const int mid = __reduce_max_sync(0xffffffffu, split < nnodes ? (int)(nInfo[split] & 0xffffu) : slots) >> 4;
    if (warp >= 4 * NCWG) {
        asm volatile("setmaxnreg.dec.sync.aligned.u32 48;");
        const int wg = (warp - 4 * NCWG) >> 2, r = warp & 3;
        const int g0 = wg == 0 ? 0 : mid, g1 = wg == 0 ? mid : slots >> 4;
        const int e = lane >> 1, half = lane & 1;
        const uint32_t coef_off = e * 128 + ((half ^ (e & 7)) << 4);
        const int vrot = (e & 3) ^ ((e >> 1) & 3);
        const uint8_t* tab = (const uint8_t*)g_table + half * 16;
        int stage = r, phase = 1;
        for (int gi = g0 + r; gi < g1; gi += 4) {
            const uint32_t st = ring + (wg * nstage + stage) * STAGE_B;
            const uint32_t fb = bar_full + (wg * MAX_STAGE + stage) * 8;
            const uint2 m = lds64(sb + SM_META + (gi * 16 + e) * 8);
            const uint4 ia = lds128(sb + SM_SID + gi * 32), ib = lds128(sb + SM_SID + gi * 32 + 16);
            const uint4 tv = __ldg((const uint4*)(tab + (m.x & 0xffffu)));
            const uint32_t id2[8] = {ia.x, ia.y, ia.z, ia.w, ib.x, ib.y, ib.z, ib.w};
            const int nv = __popc(__ballot_sync(0xffffffffu, (m.x & 0xffffu) != (uint32_t)(TAB_ZERO << 5))) >> 1;
            mbar_wait(bar_empty + (wg * MAX_STAGE + stage) * 8, phase);
            uint32_t leader;
            asm volatile("{\n.reg .pred p;\nelect.sync _|p, 0xffffffff;\nselp.u32 %0, 1, 0, p;\n}" : "=r"(leader));
            if (leader) {
                if (nv == 16) {
#pragma unroll
                    for (int i = 0; i < 8; i++) {
                        tma_load(st + 2048 + (2 * i) * 640, &tmF, (int)(id2[i] & 0xffffu) * 4, fb);
                        tma_load(st + 2048 + (2 * i + 1) * 640, &tmF, (int)(id2[i] >> 16) * 4, fb);
                    }
                } else {
                    for (int i = 0; i < nv; i++)
                        tma_load(st + 2048 + i * 640, &tmF, (int)lds16(sb + SM_SID + (gi * 16 + i) * 2) * 4, fb);
                }
            }
            __syncwarp();
            const uint32_t mul[4] = {0x3f803f80u, __byte_perm(m.y, 0, 0x1010), __byte_perm(m.y, 0, 0x3232), __byte_perm(m.x, 0, 0x3232)};
            const uint32_t a = st + coef_off;
#pragma unroll
            for (int j = 0; j < 4; j++) {
                const int v = j ^ vrot;
                const uint32_t lo = (v & 1) ? mul[1] : mul[0], hi = (v & 1) ? mul[3] : mul[2];
                const uint32_t mm = (v & 2) ? hi : lo;
                sts128(a ^ (v << 5), make_uint4(hmul2(tv.x, mm), hmul2(tv.y, mm), hmul2(tv.z, mm), hmul2(tv.w, mm)));
            }
            fence_async_smem();
            __syncwarp();
            if (lane == 0) mbar_expect_tx(fb, (uint32_t)nv * 512u);
            stage += 4;
            if (stage >= nstage) { stage -= nstage; phase ^= 1; }
        }
    } else {
        asm volatile("setmaxnreg.inc.sync.aligned.u32 208;");
        const int wg = warp >> 2, w = warp & 3;
        const int n_end = wg == 0 ? split : nnodes;
        uint32_t wA[2][4][4];
#pragma unroll
        for (int mk = 0; mk < 8; mk++) {
            const uint4 q = lds128(sb + SM_HT + (mk * 128 + (tid & 127)) * 16);
            wA[mk >> 2][mk & 3][0] = q.x; wA[mk >> 2][mk & 3][1] = q.y; wA[mk >> 2][mk & 3][2] = q.z; wA[mk >> 2][mk & 3][3] = q.w;
        }
        asm volatile("bar.sync 3, 256;" ::: "memory");
        uint32_t aoff[4];
        {
            const int e = (lane & 7) + 8 * (lane >> 4), ch = 2 * w + ((lane >> 3) & 1);
#pragma unroll
            for (int b = 0; b < 4; b++) aoff[b] = 2048 + e * 640 + b * 128 + ((ch ^ ((5 * e + b) & 7)) << 4);
        }
        const uint32_t ht = sb + SM_HT + wg * 8192;
        const uint32_t stsm_a = ht + (16 * w + (lane & 15)) * 128 + (((lane >> 4) ^ (lane & 7)) << 4);
        const uint32_t dht = desc_lo(ht);
        const uint32_t out_lane = (uint32_t)node0 * 512u + t * 128 + (16 * w + (g & 1) * 8 + (g & 6)) * 2;
        const uint32_t ring_wg = ring + wg * nstage * STAGE_B;
        const uint32_t full_wg = bar_full + wg * MAX_STAGE * 8;

        float ys[8], yv[24], dQ[3][8];
        float zs[8], zv[24], pv[3][2];
        uint32_t A0[4][4], A1[4][4];
#pragma unroll
        for (int i = 0; i < 24; i++) yv[i] = 0.f;
#pragma unroll
        for (int i = 0; i < 8; i++) { ys[i] = 0.f; dQ[0][i] = 0.f; dQ[1][i] = 0.f; dQ[2][i] = 0.f; }
        int left = wg == 0 ? mid : (slots >> 4) - mid;
        int fstage = 0;
        uint32_t fphase = 0, fst = ring_wg, fbar = full_wg;
        int nl = wg == 0 ? 0 : split, gi = 0, G = 0, pend = -1;
        uint32_t rs0 = 0, rs1 = 0;
        int npar = 0, ppar = 0, qpar = 0;

        auto fetch = [&](uint32_t (&A)[4][4], uint32_t& bd, uint32_t& eb) {
            mbar_wait(fbar, fphase);
#pragma unroll
            for (int b = 0; b < 4; b++) ldsm4t(A[b], fst + aoff[b]);
            bd = desc_lo(fst);
            eb = fbar + NCWG * MAX_STAGE * 8;
            fst += STAGE_B; fbar += 8;
            if (++fstage == nstage) { fstage = 0; fphase ^= 1; fst = ring_wg; fbar = full_wg; }
        };
        auto node_begin = [&]() {
            G = __reduce_max_sync(0xffffffffu, (int)(nInfo[nl] >> 20));
            gi = 0;
        };
        float pr[4][2];
        int pend2 = -1;
        auto weigh = [&]() {
#pragma unroll
            for (int i = 0; i < 12; i++) asm volatile("" : "+r"(wp[i >> 2][i & 3]));
            pr[0][0] = bf_lo(wp[0][0]) * zs[0] + bf_hi(wp[0][0]) * zs[1] + bf_lo(wp[0][2]) * zs[4] + bf_hi(wp[0][2]) * zs[5];
            pr[0][1] = bf_lo(wp[0][1]) * zs[2] + bf_hi(wp[0][1]) * zs[3] + bf_lo(wp[0][3]) * zs[6] + bf_hi(wp[0][3]) * zs[7];
#pragma unroll
            for (int a = 0; a < 3; a++) {
                const float* y = zv + 8 * a;
                pr[a + 1][0] = pv[a][0] + bf_lo(wp[2][0]) * y[0] + bf_hi(wp[2][0]) * y[1] + bf_lo(wp[2][2]) * y[4] + bf_hi(wp[2][2]) * y[5];
                pr[a + 1][1] = pv[a][1] + bf_lo(wp[2][1]) * y[2] + bf_hi(wp[2][1]) * y[3] + bf_lo(wp[2][3]) * y[6] + bf_hi(wp[2][3]) * y[7];
            }
            pend2 = pend;
            qpar = ppar;
            pend = -1;
        };
        auto finish = [&]() {
            const bool hi2 = t & 2, hi1 = t & 1, odd = g & 1;
            float ka0 = hi2 ? pr[2][0] : pr[0][0], ka1 = hi2 ? pr[2][1] : pr[0][1];
            float kb0 = hi2 ? pr[3][0] : pr[1][0], kb1 = hi2 ? pr[3][1] : pr[1][1];
            float sa0 = hi2 ? pr[0][0] : pr[2][0], sa1 = hi2 ? pr[0][1] : pr[2][1];
            float sb0 = hi2 ? pr[1][0] : pr[3][0], sb1 = hi2 ? pr[1][1] : pr[3][1];
            ka0 += __shfl_xor_sync(0xffffffffu, sa0, 2); ka1 += __shfl_xor_sync(0xffffffffu, sa1, 2);
            kb0 += __shfl_xor_sync(0xffffffffu, sb0, 2); kb1 += __shfl_xor_sync(0xffffffffu, sb1, 2);
            float k0 = hi1 ? kb0 : ka0, k1 = hi1 ? kb1 : ka1;
            float s0 = hi1 ? ka0 : kb0, s1 = hi1 ? ka1 : kb1;
            k0 += __shfl_xor_sync(0xffffffffu, s0, 1);
            k1 += __shfl_xor_sync(0xffffffffu, s1, 1);
            const float other = __shfl_xor_sync(0xffffffffu, odd ? k0 : k1, 4);
            const float lo = odd ? other : k0, hi = odd ? k1 : other;
            const uint32_t resid = qpar ? rs1 : rs0;
            *(uint32_t*)((uint8_t*)p.out + (out_lane + (uint32_t)pend2 * 512u)) = pack_bf(bf_lo(resid) + lo, bf_hi(resid) + hi);
            pend2 = -1;
        };
        auto step = [&](uint32_t (&Ac)[4][4], uint32_t bdc, uint32_t ebc, uint32_t (&An)[4][4], uint32_t& bdn, uint32_t& ebn) {
            wg_fence();
            wgmma_n64_p(ys, yv, Ac[0], bdc, gi);
            wgmma_n16_p(dQ[0], Ac[1], bdc, gi);
            wgmma_n16_p(dQ[1], Ac[2], bdc, gi);
            wgmma_n16_p(dQ[2], Ac[3], bdc, gi);
            wg_commit();
            if (pend2 >= 0) finish();
            if (--left > 0) fetch(An, bdn, ebn);
            const bool last = ++gi == G;
            wg_wait0();
            mbar_arrive_elected(ebc);
            if (pend >= 0) weigh();
            if (last) {
                named_barrier(1 + wg);
                uint32_t sa = stsm_a;
                asm volatile("" : "+r"(sa));
                stsm4(sa, pack_bf(ys[0], ys[1]), pack_bf(ys[2], ys[3]), pack_bf(ys[4], ys[5]), pack_bf(ys[6], ys[7]));
#pragma unroll
                for (int i = 0; i < 6; i += 2) {
                    stsm4(sa ^ ((i + 2) << 4),
                          pack_bf(yv[4 * i], yv[4 * i + 1]), pack_bf(yv[4 * i + 2], yv[4 * i + 3]),
                          pack_bf(yv[4 * i + 4], yv[4 * i + 5]), pack_bf(yv[4 * i + 6], yv[4 * i + 7]));
                }
                fence_async_smem();
#pragma unroll
                for (int i = 0; i < 4; i++) asm volatile("" : "+r"(wp[1][i]));
#pragma unroll
                for (int a = 0; a < 3; a++) {
                    const float* q = dQ[a];
                    pv[a][0] = bf_lo(wp[1][0]) * q[0] + bf_hi(wp[1][0]) * q[1] + bf_lo(wp[1][2]) * q[4] + bf_hi(wp[1][2]) * q[5];
                    pv[a][1] = bf_lo(wp[1][1]) * q[2] + bf_hi(wp[1][1]) * q[3] + bf_lo(wp[1][3]) * q[6] + bf_hi(wp[1][3]) * q[7];
                }
                named_barrier(1 + wg);
                wg_fence();
                wgmma_n16_first(zs, wA[0][0], dht);
                wgmma_n48_first(zv, wA[1][0], dht + 2);
#pragma unroll
                for (int ks = 1; ks < 4; ks++) {
                    wgmma_n16(zs, wA[0][ks], dht + ks * 128);
                    wgmma_n48(zv, wA[1][ks], dht + ks * 128 + 2);
                }
                wg_commit();
                pend = nl;
                {
                    const uint8_t* ra = (const uint8_t*)p.sv + (out_lane + (uint32_t)nl * 512u);
                    asm volatile("{\n.reg .pred p;\nsetp.ne.s32 p, %3, 0;\n@p ld.global.nc.u32 %1, [%2];\n@!p ld.global.nc.L1::no_allocate.u32 %0, [%2];\n}"
                                 : "+r"(rs0), "+r"(rs1) : "l"(ra), "r"(npar));
                    ppar = npar;
                    npar ^= 1;
                }
                if (++nl < n_end) node_begin();
            }
        };
        if (left > 0) {
            node_begin();
            uint32_t bd0, eb0, bd1 = 0, eb1 = 0;
            fetch(A0, bd0, eb0);
            while (true) {
                step(A0, bd0, eb0, A1, bd1, eb1);
                if (left <= 0) break;
                step(A1, bd1, eb1, A0, bd0, eb0);
                if (left <= 0) break;
            }
            if (pend2 >= 0) finish();
            wg_wait0();
            weigh();
            finish();
        }
    }
    STAMP(8);
}

typedef CUresult (*EncodeFn)(CUtensorMap*, CUtensorMapDataType, cuuint32_t, void*, const cuuint64_t*, const cuuint64_t*,
                             const cuuint32_t*, const cuuint32_t*, CUtensorMapInterleave, CUtensorMapSwizzle,
                             CUtensorMapL2promotion, CUtensorMapFloatOOBfill);

void make_map(EncodeFn enc, CUtensorMap* tm, const void* base, uint64_t lines, uint32_t box) {
    cuuint64_t gd[2] = {64, lines};
    cuuint64_t gs[1] = {128};
    cuuint32_t bd[2] = {64, box};
    cuuint32_t es[2] = {1, 1};
    enc(tm, CU_TENSOR_MAP_DATA_TYPE_BFLOAT16, 2, const_cast<void*>(base), gd, gs, bd, es, CU_TENSOR_MAP_INTERLEAVE_NONE,
        CU_TENSOR_MAP_SWIZZLE_128B, CU_TENSOR_MAP_L2_PROMOTION_L2_128B, CU_TENSOR_MAP_FLOAT_OOB_FILL_NONE);
}

}

extern "C" void kernel_launch(void* const* d_in, const int* in_sizes, int n_in, void* d_out, int out_size) {
    (void)n_in; (void)out_size;
    static int n_sm = 0;
    static EncodeFn enc = nullptr;
    static void* f_ptr = nullptr;
    if (n_sm == 0) {
        int dev = 0;
        cudaGetDevice(&dev);
        cudaDeviceGetAttribute(&n_sm, cudaDevAttrMultiProcessorCount, dev);
        cudaFuncSetAttribute(painn_kernel, cudaFuncAttributeMaxDynamicSharedMemorySize, SM_TOTAL);
        void* fn = nullptr;
        cudaDriverEntryPointQueryResult qr;
        cudaGetDriverEntryPoint("cuTensorMapEncodeTiled", &fn, cudaEnableDefault, &qr);
        enc = (EncodeFn)fn;
        cudaGetSymbolAddress(&f_ptr, g_F);
    }
    Params p;
    p.sv    = (const __nv_bfloat16*)d_in[0];
    p.pos   = (const __nv_bfloat16*)d_in[1];
    p.src   = (const int*)d_in[2];
    p.dst   = (const int*)d_in[3];
    p.freqs = (const __nv_bfloat16*)d_in[4];
    p.w1    = (const __nv_bfloat16*)d_in[5];
    p.w2    = (const __nv_bfloat16*)d_in[6];
    p.wr    = (const __nv_bfloat16*)d_in[7];
    p.out   = (__nv_bfloat16*)d_out;
    p.N = in_sizes[1] / 3;
    p.E = in_sizes[2];
    p.ncta = n_sm < MAX_CTA ? n_sm : MAX_CTA;
    p.npc = (p.N + p.ncta - 1) / p.ncta;
    p.npc_magic = (uint32_t)(0x100000000ull / (uint32_t)p.npc) + 1u;
    p.quads_per_cta = ((p.E >> 2) + p.ncta - 1) / p.ncta;
    if (!enc || p.N > MAX_N || p.npc > MAX_NPC || (p.E & 3) || p.quads_per_cta > MAX_ROUNDS * 32) return;

    CUtensorMap tmF, tmSV, tmW1, tmW2;
    make_map(enc, &tmF, f_ptr, (uint64_t)p.N * 4, 4);
    make_map(enc, &tmSV, p.sv, (uint64_t)p.N * 4, 160);
    make_map(enc, &tmW1, p.w1, 64, 64);
    make_map(enc, &tmW2, p.w2, 192, 192);

    cudaLaunchConfig_t cfg = {};
    cfg.gridDim = dim3(p.ncta);
    cfg.blockDim = dim3(NT);
    cfg.dynamicSmemBytes = SM_TOTAL;
    cfg.stream = cudaStreamPerThread;
    cudaLaunchAttribute attr[1];
    attr[0].id = cudaLaunchAttributeCooperative;
    attr[0].val.cooperative = 1;
    cfg.attrs = attr;
    cfg.numAttrs = 1;
    cudaLaunchKernelEx(&cfg, painn_kernel, p, tmF, tmSV, tmW1, tmW2);
}
```

```cpp
#include <cuda_runtime.h>
#include <cuda.h>
#include <cuda_bf16.h>
#include <stdint.h>

namespace {

constexpr int NT        = 512;
constexpr int NCWG      = 3;
constexpr int MAX_N     = 10240;
constexpr int MAX_CTA   = 144;
constexpr int MAX_NPC   = 80;
constexpr int MAX_ROUNDS = 38;
constexpr int REC_CAP   = MAX_ROUNDS * 128;
constexpr int SLOT_CAP  = 6144;
constexpr int MAX_STAGE = 4;
constexpr int STAGE_B   = 12288;

constexpr uint32_t D_MIN_BITS = 0x38D2;
constexpr uint32_t D_MAX_BITS = 0x409C;
constexpr int TAB_ROWS  = (int)(D_MAX_BITS - D_MIN_BITS) + 1;
constexpr int TAB_ZERO  = TAB_ROWS;
constexpr int TAB_BYTES = (TAB_ROWS + 1) * 32;

constexpr int SM_BINCNT = 0;
constexpr int SM_BINOFF = SM_BINCNT + MAX_CTA * 4;
constexpr int SM_NCNT   = SM_BINOFF + MAX_CTA * 4;
constexpr int SM_NINFO  = SM_NCNT + MAX_NPC * 4;
constexpr int SM_CTRL   = SM_NINFO + MAX_NPC * 4;
constexpr int SM_BARS   = SM_CTRL + 64;
constexpr int SM_SID    = 2048 + 128;
constexpr int SM_META   = SM_SID + SLOT_CAP * 2;
constexpr int SM_TOTAL  = 232448;
constexpr int SM_HT     = (SM_TOTAL - NCWG * 8192) / 1024 * 1024;
constexpr int SM_RING4  = SM_HT - NCWG * 4 * STAGE_B;
constexpr int SM_RING3  = SM_HT - NCWG * 3 * STAGE_B;
constexpr int SLOT_CAP4 = (SM_RING4 - SM_META) / 8;
constexpr int SM_STAGE2 = SM_RING3 - 0;
constexpr int STAGE_CAP = (SM_HT - SM_RING3) / 16;
constexpr int P1_POS    = 3072;
constexpr int P1_STAGE  = P1_POS + 61440;
constexpr int P1_SV     = (P1_STAGE + REC_CAP * 16 + 1023) / 1024 * 1024;
constexpr int P1_W1     = P1_SV + MAX_NPC * 512;
constexpr int P1_W2     = P1_W1 + 8192;
constexpr int P1_END    = P1_W2 + 24576;
static_assert(SM_BARS + (4 + 2 * NCWG * MAX_STAGE) * 8 <= SM_SID, "misc block");
static_assert(SM_BARS + 256 <= P1_POS, "misc block");
static_assert(P1_END <= SM_TOTAL, "phase 1 overlay");
static_assert(SM_META + SLOT_CAP * 8 <= SM_RING3, "CSR");
static_assert(SM_RING4 % 1024 == 0 && SM_RING3 % 1024 == 0 && SM_HT % 1024 == 0, "alignment");
static_assert(SM_BARS % 8 == 0 && SM_META % 8 == 0, "alignment");
static_assert(MAX_N * 6 <= 61440, "pos");
static_assert(SM_SID + MAX_NPC * 1024 <= SM_TOTAL, "slow path accumulators");

__device__ __align__(1024) uint4 g_F[MAX_N * 32];
__device__ uint4    g_rec[MAX_CTA * REC_CAP];
__device__ uint32_t g_offs[MAX_CTA * MAX_CTA];
__device__ uint4    g_table[(TAB_BYTES + 15) / 16];
__device__ unsigned g_bar[2];
#define STAMP(k)
#define STAMPT(k, T)
#define ITS(k)

struct Params {
    const __nv_bfloat16* sv;
    const __nv_bfloat16* pos;
    const int*           src;
    const int*           dst;
    const __nv_bfloat16* freqs;
    const __nv_bfloat16* w1;
    const __nv_bfloat16* w2;
    const __nv_bfloat16* wr;
    __nv_bfloat16*       out;
    int N, E, ncta, npc;
    uint32_t npc_magic;
    int quads_per_cta;
};

__device__ __forceinline__ uint32_t smem_u32(const void* p) { return (uint32_t)__cvta_generic_to_shared(p); }
__device__ __forceinline__ float bf_lo(uint32_t v) { return __uint_as_float(v << 16); }
__device__ __forceinline__ float bf_hi(uint32_t v) { return __uint_as_float(v & 0xffff0000u); }
__device__ __forceinline__ float bf_u16(uint16_t v) { return __uint_as_float((uint32_t)v << 16); }
__device__ __forceinline__ uint32_t pack_bf(float lo, float hi) {
    uint32_t r;
    asm("cvt.rn.bf16x2.f32 %0, %1, %2;" : "=r"(r) : "f"(hi), "f"(lo));
    return r;
}
__device__ __forceinline__ float rbf(float x) { return bf_lo(pack_bf(x, 0.f)); }
__device__ __forceinline__ uint32_t hmul2(uint32_t a, uint32_t b) {
    uint32_t r;
    asm("mul.rn.bf16x2 %0, %1, %2;" : "=r"(r) : "r"(a), "r"(b));
    return r;
}
__device__ __forceinline__ uint32_t hsub2(uint32_t a, uint32_t b) {
    uint32_t r;
    asm("sub.rn.bf16x2 %0, %1, %2;" : "=r"(r) : "r"(a), "r"(b));
    return r;
}
__device__ __forceinline__ uint32_t lds32(uint32_t a) { uint32_t v; asm volatile("ld.shared.u32 %0, [%1];" : "=r"(v) : "r"(a)); return v; }
__device__ __forceinline__ uint32_t lds16(uint32_t a) { uint16_t v; asm volatile("ld.shared.u16 %0, [%1];" : "=h"(v) : "r"(a)); return v; }
__device__ __forceinline__ uint2 lds64(uint32_t a) { uint2 v; asm volatile("ld.shared.v2.u32 {%0,%1}, [%2];" : "=r"(v.x), "=r"(v.y) : "r"(a)); return v; }
__device__ __forceinline__ uint4 lds128(uint32_t a) { uint4 v; asm volatile("ld.shared.v4.u32 {%0,%1,%2,%3}, [%4];" : "=r"(v.x), "=r"(v.y), "=r"(v.z), "=r"(v.w) : "r"(a)); return v; }
__device__ __forceinline__ void sts32(uint32_t a, uint32_t v) { asm volatile("st.shared.u32 [%0], %1;" ::"r"(a), "r"(v) : "memory"); }
__device__ __forceinline__ void sts128(uint32_t a, uint4 v) { asm volatile("st.shared.v4.u32 [%0], {%1,%2,%3,%4};" ::"r"(a), "r"(v.x), "r"(v.y), "r"(v.z), "r"(v.w) : "memory"); }
__device__ __forceinline__ void mbar_init(uint32_t bar, int cnt) { asm volatile("mbarrier.init.shared::cta.b64 [%0], %1;" ::"r"(bar), "r"(cnt) : "memory"); }
__device__ __forceinline__ void mbar_expect_tx(uint32_t bar, uint32_t bytes) { asm volatile("mbarrier.arrive.expect_tx.shared::cta.b64 _, [%0], %1;" ::"r"(bar), "r"(bytes) : "memory"); }
__device__ __forceinline__ void mbar_arrive(uint32_t bar) { asm volatile("mbarrier.arrive.shared::cta.b64 _, [%0];" ::"r"(bar) : "memory"); }
__device__ __forceinline__ void mbar_wait(uint32_t bar, uint32_t parity) {
    asm volatile("{\n.reg .pred p;\n.reg .u32 c;\n"
                 "mbarrier.try_wait.parity.shared::cta.b64 p, [%0], %1;\n"
                 "@p bra DONE_%=;\n"
                 "mov.u32 c, 0;\n"
                 "LOOP_%=:\n"
                 "mbarrier.try_wait.parity.shared::cta.b64 p, [%0], %1;\n"
                 "@p bra DONE_%=;\n"
                 "add.u32 c, c, 1;\n"
                 "setp.lt.u32 p, c, 4194304;\n"
                 "@p bra LOOP_%=;\n"
                 "DONE_%=:\n}"
                 ::"r"(bar), "r"(parity) : "memory");
}
__device__ __forceinline__ void mbar_arrive_elected(uint32_t bar) {
    asm volatile("{\n.reg .pred p;\nelect.sync _|p, 0xffffffff;\n@p mbarrier.arrive.shared::cta.b64 _, [%0];\n}" ::"r"(bar) : "memory");
}
__device__ __forceinline__ void bulk_g2s(uint32_t dst, const void* src, uint32_t bytes, uint32_t bar) {
    asm volatile("cp.async.bulk.shared::cluster.global.mbarrier::complete_tx::bytes [%0], [%1], %2, [%3];"
                 ::"r"(dst), "l"(src), "r"(bytes), "r"(bar) : "memory");
}
__device__ __forceinline__ void tma_load(uint32_t dst, const CUtensorMap* tm, int line, uint32_t bar) {
    asm volatile("cp.async.bulk.tensor.2d.shared::cluster.global.mbarrier::complete_tx::bytes [%0], [%1, {%3, %4}], [%2];"
                 ::"r"(dst), "l"(tm), "r"(bar), "r"(0), "r"(line) : "memory");
}
__device__ __forceinline__ void tma_store(const CUtensorMap* tm, int line, uint32_t src) {
    asm volatile("cp.async.bulk.tensor.2d.global.shared::cta.bulk_group [%0, {%2, %3}], [%1];"
                 ::"l"(tm), "r"(src), "r"(0), "r"(line) : "memory");
}
__device__ __forceinline__ void fence_async_smem() { asm volatile("fence.proxy.async.shared::cta;" ::: "memory"); }
__device__ __forceinline__ void named_barrier(int id) { asm volatile("bar.sync %0, 128;" ::"r"(id) : "memory"); }
__device__ __forceinline__ void ldsm4(uint32_t (&r)[4], uint32_t a) {
    asm volatile("ldmatrix.sync.aligned.m8n8.x4.shared.b16 {%0,%1,%2,%3}, [%4];" : "=r"(r[0]), "=r"(r[1]), "=r"(r[2]), "=r"(r[3]) : "r"(a) : "memory");
}
__device__ __forceinline__ void ldsm4t(uint32_t (&r)[4], uint32_t a) {
    asm volatile("ldmatrix.sync.aligned.m8n8.x4.trans.shared.b16 {%0,%1,%2,%3}, [%4];" : "=r"(r[0]), "=r"(r[1]), "=r"(r[2]), "=r"(r[3]) : "r"(a) : "memory");
}
__device__ __forceinline__ void stsm4(uint32_t a, uint32_t r0, uint32_t r1, uint32_t r2, uint32_t r3) {
    asm volatile("stmatrix.sync.aligned.m8n8.x4.shared.b16 [%0], {%1,%2,%3,%4};" ::"r"(a), "r"(r0), "r"(r1), "r"(r2), "r"(r3) : "memory");
}
__device__ __forceinline__ void mma16816(float (&c)[4], const uint32_t (&a)[4], uint32_t b0, uint32_t b1) {
    asm volatile("mma.sync.aligned.m16n8k16.row.col.f32.bf16.bf16.f32 {%0,%1,%2,%3}, {%4,%5,%6,%7}, {%8,%9}, {%0,%1,%2,%3};"
                 : "+f"(c[0]), "+f"(c[1]), "+f"(c[2]), "+f"(c[3])
                 : "r"(a[0]), "r"(a[1]), "r"(a[2]), "r"(a[3]), "r"(b0), "r"(b1));
}

__device__ __forceinline__ uint32_t desc_lo(uint32_t saddr) { return ((saddr & 0x3FFFF) >> 4) | (1u << 16); }
#define DESC_HI "0x40000040"
__device__ __forceinline__ void wg_fence() { asm volatile("wgmma.fence.sync.aligned;" ::: "memory"); }
__device__ __forceinline__ void wg_commit() { asm volatile("wgmma.commit_group.sync.aligned;" ::: "memory"); }
__device__ __forceinline__ void wg_wait0() { asm volatile("wgmma.wait_group.sync.aligned 0;" ::: "memory"); }
__device__ __forceinline__ void wg_wait1() { asm volatile("wgmma.wait_group.sync.aligned 1;" ::: "memory"); }

__device__ __forceinline__ void wgmma_n64_first(float (&d)[8], float (&e)[24], const uint32_t (&a)[4], uint32_t bdesc) {
    asm volatile("{\n.reg .b64 b;\nmov.b64 b, {%36, " DESC_HI "};\n"
                 "wgmma.mma_async.sync.aligned.m64n64k16.f32.bf16.bf16 {%0,%1,%2,%3,%4,%5,%6,%7,%8,%9,%10,%11,%12,%13,%14,%15,%16,%17,%18,%19,%20,%21,%22,%23,%24,%25,%26,%27,%28,%29,%30,%31}, {%32,%33,%34,%35}, b, 0, 1, 1, 1;\n}"
                 : "=f"(d[0]), "=f"(d[1]), "=f"(d[2]), "=f"(d[3]), "=f"(d[4]), "=f"(d[5]), "=f"(d[6]), "=f"(d[7]),
                   "=f"(e[0]), "=f"(e[1]), "=f"(e[2]), "=f"(e[3]), "=f"(e[4]), "=f"(e[5]), "=f"(e[6]), "=f"(e[7]), "=f"(e[8]), "=f"(e[9]), "=f"(e[10]), "=f"(e[11]), "=f"(e[12]), "=f"(e[13]), "=f"(e[14]), "=f"(e[15]), "=f"(e[16]), "=f"(e[17]), "=f"(e[18]), "=f"(e[19]), "=f"(e[20]), "=f"(e[21]), "=f"(e[22]), "=f"(e[23])
                 : "r"(a[0]), "r"(a[1]), "r"(a[2]), "r"(a[3]), "r"(bdesc));
}
__device__ __forceinline__ void wgmma_n64(float (&d)[8], float (&e)[24], const uint32_t (&a)[4], uint32_t bdesc) {
    asm volatile("{\n.reg .b64 b;\nmov.b64 b, {%36, " DESC_HI "};\n"
                 "wgmma.mma_async.sync.aligned.m64n64k16.f32.bf16.bf16 {%0,%1,%2,%3,%4,%5,%6,%7,%8,%9,%10,%11,%12,%13,%14,%15,%16,%17,%18,%19,%20,%21,%22,%23,%24,%25,%26,%27,%28,%29,%30,%31}, {%32,%33,%34,%35}, b, 1, 1, 1, 1;\n}"
                 : "+f"(d[0]), "+f"(d[1]), "+f"(d[2]), "+f"(d[3]), "+f"(d[4]), "+f"(d[5]), "+f"(d[6]), "+f"(d[7]),
                   "+f"(e[0]), "+f"(e[1]), "+f"(e[2]), "+f"(e[3]), "+f"(e[4]), "+f"(e[5]), "+f"(e[6]), "+f"(e[7]), "+f"(e[8]), "+f"(e[9]), "+f"(e[10]), "+f"(e[11]), "+f"(e[12]), "+f"(e[13]), "+f"(e[14]), "+f"(e[15]), "+f"(e[16]), "+f"(e[17]), "+f"(e[18]), "+f"(e[19]), "+f"(e[20]), "+f"(e[21]), "+f"(e[22]), "+f"(e[23])
                 : "r"(a[0]), "r"(a[1]), "r"(a[2]), "r"(a[3]), "r"(bdesc));
}
__device__ __forceinline__ void wgmma_n48_first(float (&e)[24], const uint32_t (&a)[4], uint32_t bdesc) {
    asm volatile("{\n.reg .b64 b;\nmov.b64 b, {%28, " DESC_HI "};\n"
                 "wgmma.mma_async.sync.aligned.m64n48k16.f32.bf16.bf16 {%0,%1,%2,%3,%4,%5,%6,%7,%8,%9,%10,%11,%12,%13,%14,%15,%16,%17,%18,%19,%20,%21,%22,%23}, {%24,%25,%26,%27}, b, 0, 1, 1, 1;\n}"
                 : "=f"(e[0]), "=f"(e[1]), "=f"(e[2]), "=f"(e[3]), "=f"(e[4]), "=f"(e[5]), "=f"(e[6]), "=f"(e[7]), "=f"(e[8]), "=f"(e[9]), "=f"(e[10]), "=f"(e[11]), "=f"(e[12]), "=f"(e[13]), "=f"(e[14]), "=f"(e[15]), "=f"(e[16]), "=f"(e[17]), "=f"(e[18]), "=f"(e[19]), "=f"(e[20]), "=f"(e[21]), "=f"(e[22]), "=f"(e[23])
                 : "r"(a[0]), "r"(a[1]), "r"(a[2]), "r"(a[3]), "r"(bdesc));
}
__device__ __forceinline__ void wgmma_n48(float (&e)[24], const uint32_t (&a)[4], uint32_t bdesc) {
    asm volatile("{\n.reg .b64 b;\nmov.b64 b, {%28, " DESC_HI "};\n"
                 "wgmma.mma_async.sync.aligned.m64n48k16.f32.bf16.bf16 {%0,%1,%2,%3,%4,%5,%6,%7,%8,%9,%10,%11,%12,%13,%14,%15,%16,%17,%18,%19,%20,%21,%22,%23}, {%24,%25,%26,%27}, b, 1, 1, 1, 1;\n}"
                 : "+f"(e[0]), "+f"(e[1]), "+f"(e[2]), "+f"(e[3]), "+f"(e[4]), "+f"(e[5]), "+f"(e[6]), "+f"(e[7]), "+f"(e[8]), "+f"(e[9]), "+f"(e[10]), "+f"(e[11]), "+f"(e[12]), "+f"(e[13]), "+f"(e[14]), "+f"(e[15]), "+f"(e[16]), "+f"(e[17]), "+f"(e[18]), "+f"(e[19]), "+f"(e[20]), "+f"(e[21]), "+f"(e[22]), "+f"(e[23])
                 : "r"(a[0]), "r"(a[1]), "r"(a[2]), "r"(a[3]), "r"(bdesc));
}
__device__ __forceinline__ void wgmma_n16_first(float (&d)[8], const uint32_t (&a)[4], uint32_t bdesc) {
    asm volatile("{\n.reg .b64 b;\nmov.b64 b, {%12, " DESC_HI "};\n"
                 "wgmma.mma_async.sync.aligned.m64n16k16.f32.bf16.bf16 {%0,%1,%2,%3,%4,%5,%6,%7}, {%8,%9,%10,%11}, b, 0, 1, 1, 1;\n}"
                 : "=f"(d[0]), "=f"(d[1]), "=f"(d[2]), "=f"(d[3]), "=f"(d[4]), "=f"(d[5]), "=f"(d[6]), "=f"(d[7])
                 : "r"(a[0]), "r"(a[1]), "r"(a[2]), "r"(a[3]), "r"(bdesc));
}
__device__ __forceinline__ void wgmma_n16(float (&d)[8], const uint32_t (&a)[4], uint32_t bdesc) {
    asm volatile("{\n.reg .b64 b;\nmov.b64 b, {%12, " DESC_HI "};\n"
                 "wgmma.mma_async.sync.aligned.m64n16k16.f32.bf16.bf16 {%0,%1,%2,%3,%4,%5,%6,%7}, {%8,%9,%10,%11}, b, 1, 1, 1, 1;\n}"
                 : "+f"(d[0]), "+f"(d[1]), "+f"(d[2]), "+f"(d[3]), "+f"(d[4]), "+f"(d[5]), "+f"(d[6]), "+f"(d[7])
                 : "r"(a[0]), "r"(a[1]), "r"(a[2]), "r"(a[3]), "r"(bdesc));
}

__device__ __forceinline__ void wgmma_n64_p(float (&d)[8], float (&e)[24], const uint32_t (&a)[4], uint32_t bdesc, int acc) {
    asm volatile("{\n.reg .pred p;\n.reg .b64 b;\nsetp.ne.b32 p, %37, 0;\nmov.b64 b, {%36, " DESC_HI "};\n"
                 "wgmma.mma_async.sync.aligned.m64n64k16.f32.bf16.bf16 {%0,%1,%2,%3,%4,%5,%6,%7,%8,%9,%10,%11,%12,%13,%14,%15,%16,%17,%18,%19,%20,%21,%22,%23,%24,%25,%26,%27,%28,%29,%30,%31}, {%32,%33,%34,%35}, b, p, 1, 1, 1;\n}"
                 : "+f"(d[0]), "+f"(d[1]), "+f"(d[2]), "+f"(d[3]), "+f"(d[4]), "+f"(d[5]), "+f"(d[6]), "+f"(d[7]),
                   "+f"(e[0]), "+f"(e[1]), "+f"(e[2]), "+f"(e[3]), "+f"(e[4]), "+f"(e[5]), "+f"(e[6]), "+f"(e[7]), "+f"(e[8]), "+f"(e[9]), "+f"(e[10]), "+f"(e[11]), "+f"(e[12]), "+f"(e[13]), "+f"(e[14]), "+f"(e[15]), "+f"(e[16]), "+f"(e[17]), "+f"(e[18]), "+f"(e[19]), "+f"(e[20]), "+f"(e[21]), "+f"(e[22]), "+f"(e[23])
                 : "r"(a[0]), "r"(a[1]), "r"(a[2]), "r"(a[3]), "r"(bdesc), "r"(acc));
}
__device__ __forceinline__ void wgmma_n16_p(float (&d)[8], const uint32_t (&a)[4], uint32_t bdesc, int acc) {
    asm volatile("{\n.reg .pred p;\n.reg .b64 b;\nsetp.ne.b32 p, %13, 0;\nmov.b64 b, {%12, " DESC_HI "};\n"
                 "wgmma.mma_async.sync.aligned.m64n16k16.f32.bf16.bf16 {%0,%1,%2,%3,%4,%5,%6,%7}, {%8,%9,%10,%11}, b, p, 1, 1, 1;\n}"
                 : "+f"(d[0]), "+f"(d[1]), "+f"(d[2]), "+f"(d[3]), "+f"(d[4]), "+f"(d[5]), "+f"(d[6]), "+f"(d[7])
                 : "r"(a[0]), "r"(a[1]), "r"(a[2]), "r"(a[3]), "r"(bdesc), "r"(acc));
}

__device__ __forceinline__ uint32_t edge_dist(uint32_t sxy, uint32_t sz, uint32_t dxy, uint32_t dz, uint32_t& rxy, uint32_t& rz) {
    rxy = hsub2(sxy, dxy);
    rz  = hsub2(sz, dz);
    uint32_t qxy = hmul2(rxy, rxy), qz = hmul2(rz, rz);
    float ss = rbf((bf_lo(qxy) + bf_hi(qxy)) + bf_lo(qz));
    float s2 = rbf(ss + 1e-8f);
    float d;
    asm("sqrt.approx.ftz.f32 %0, %1;" : "=f"(d) : "f"(s2));
    return pack_bf(d, 0.f) & 0xffffu;
}

__device__ __forceinline__ void load_pos(uint32_t sm_pos, int i, uint32_t& xy, uint32_t& z) {
    uint32_t a  = (sm_pos + 6u * (uint32_t)i) & ~3u;
    uint32_t w0 = lds32(a), w1 = lds32(a + 4);
    uint32_t sh = (uint32_t)i << 4;
    xy = __funnelshift_r(w0, w1, sh);
    z  = __funnelshift_r(w1, w1, sh);
}

__device__ __noinline__ float radial_value(float d, float f) {
    float arg = rbf(d * f);
    float sn  = rbf(sinf(arg));
    float rb  = rbf(__fdiv_rn(sn, d));
    float c   = rbf(cosf(rbf(__fdiv_rn(rbf(d * 3.14159265358979323846f), 5.0f))));
    float fc  = rbf(0.5f * rbf(c + 1.0f));
    return rb * fc;
}

__global__ void __launch_bounds__(NT, 1)
painn_kernel(const Params p, const __grid_constant__ CUtensorMap tmF, const __grid_constant__ CUtensorMap tmSV,
             const __grid_constant__ CUtensorMap tmW1, const __grid_constant__ CUtensorMap tmW2) {
    extern __shared__ __align__(1024) uint8_t smem[];
    const uint32_t sb   = smem_u32(smem);
    const int tid  = threadIdx.x, lane = tid & 31, warp = __shfl_sync(0xffffffffu, tid >> 5, 0);
    const int cta  = blockIdx.x;
    const int g    = lane >> 2, t = lane & 3;
    int* binCnt = (int*)(smem + SM_BINCNT);
    int* binOff = (int*)(smem + SM_BINOFF);
    int* nCnt   = (int*)(smem + SM_NCNT);
    uint32_t* nInfo = (uint32_t*)(smem + SM_NINFO);
    volatile int* ctrl = (volatile int*)(smem + SM_CTRL);
    const uint32_t bar_pos = sb + SM_BARS, bar_mlp = bar_pos + 8, bar_rec = bar_pos + 16;
    const uint32_t bar_full = bar_pos + 32, bar_empty = bar_full + NCWG * MAX_STAGE * 8;

    const int node0  = cta * p.npc;
    const int nnodes = max(0, min(p.npc, p.N - node0));

    STAMP(0);
    if (tid == 0) {
        mbar_init(bar_pos, 1);
        asm volatile("fence.mbarrier_init.release.cluster;" ::: "memory");
        uint32_t pos_bytes = (uint32_t)(p.N * 6 + 15) & ~15u;
        mbar_expect_tx(bar_pos, pos_bytes);
        bulk_g2s(sb + P1_POS, p.pos, pos_bytes, bar_pos);
    } else if (tid == 32) {
        mbar_init(bar_mlp, 1);
        asm volatile("fence.mbarrier_init.release.cluster;" ::: "memory");
        mbar_expect_tx(bar_mlp, 2u * 160u * 128u + 8192u + 24576u);
        tma_load(sb + P1_W1, &tmW1, 0, bar_mlp);
        tma_load(sb + P1_SV, &tmSV, node0 * 4, bar_mlp);
        tma_load(sb + P1_W2, &tmW2, 0, bar_mlp);
        tma_load(sb + P1_SV + 160 * 128, &tmSV, node0 * 4 + 160, bar_mlp);
    } else if (tid == 64) {
        mbar_init(bar_rec, 1);
        asm volatile("prefetch.tensormap [%0];" ::"l"(&tmF) : "memory");
    } else if (tid >= 96 && tid < 96 + NCWG * MAX_STAGE) {
        mbar_init(bar_full + 8 * (tid - 96), 5);
        mbar_init(bar_empty + 8 * (tid - 96), 4);
    }
    unsigned bar_seen = 0;
    if (tid == 15 * 32 || tid == 14 * 32)
        asm volatile("ld.relaxed.gpu.global.u32 %0, [%1];" : "=r"(bar_seen) : "l"(&g_bar[tid == 15 * 32 ? 0 : 1]) : "memory");
    const bool mlp_warp = warp >= 6;
    int4 s4[3], d4[3];
    const int q0 = cta * p.quads_per_cta;
    const int qend = min(q0 + p.quads_per_cta, p.E >> 2);
#pragma unroll
    for (int k = 0; k < 3; k++) {
        const int q = q0 + (k < 2 ? warp + 16 * k : 32 + warp) * 32 + lane;
        const bool ok = q < qend && (k < 2 || !mlp_warp);
        s4[k] = ok ? __ldg((const int4*)p.src + q) : make_int4(-1, -1, -1, -1);
        d4[k] = ok ? __ldg((const int4*)p.dst + q) : make_int4(0, 0, 0, 0);
    }
    if (tid < MAX_CTA) binCnt[tid] = 0;
    if (tid < MAX_NPC) nCnt[tid] = 0;
    if (tid < 16) ctrl[tid] = 0;
    if (tid >= 416 && tid < 416 + 48) {
        asm volatile("prefetch.global.L2 [%0];" ::"l"((const uint8_t*)p.wr + (tid - 416) * 128));
    }
    for (int i = P1_STAGE / 16 + tid; i < P1_SV / 16; i += NT) sts128(sb + i * 16, make_uint4(0u, 0u, 0u, 0u));
    __syncthreads();

    if (!mlp_warp) {
        const int rows_per = (TAB_ROWS + 1 + p.ncta - 1) / p.ncta;
        for (int i = tid; i < rows_per * 8; i += 6 * 32) {
            int row = cta * rows_per + (i >> 3), kp = i & 7;
            if (row <= TAB_ROWS) {
                uint32_t val = 0;
                if (row < TAB_ROWS) {
                    float d = __uint_as_float((D_MIN_BITS + row) << 16);
                    uint32_t f2 = __ldg((const uint32_t*)p.freqs + kp);
                    val = pack_bf(radial_value(d, bf_lo(f2)), radial_value(d, bf_hi(f2)));
                }
                ((uint32_t*)g_table)[row * 8 + kp] = val;
            }
        }
    } else {
        const int mt = (warp - 6) >> 1, hf = (warp - 6) & 1;
        if (mt * 16 < nnodes) {
            mbar_wait(bar_mlp, 0);
            STAMPT(10, 6 * 32);
            const int lrow = lane & 15, lch = lane >> 4;
            const uint32_t rowb = sb + P1_SV + (mt * 16 + lrow) * 512;
            const uint32_t key0 = (4 * lrow) & 7;
            float acc[4][4];
#pragma unroll
            for (int i = 0; i < 4; i++) { acc[i][0] = acc[i][1] = acc[i][2] = acc[i][3] = 0.f; }
#pragma unroll
            for (int ks = 0; ks < 4; ks++) {
                uint32_t a[4];
                ldsm4(a, rowb + (((2 * ks + lch) ^ key0) << 4));
                const int kk = 16 * ks + lrow;
#pragma unroll
                for (int nt = 0; nt < 4; nt += 2) {
                    uint32_t b[4];
                    ldsm4t(b, sb + P1_W1 + kk * 128 + (((4 * hf + nt + lch) ^ (kk & 7)) << 4));
                    mma16816(acc[nt], a, b[0], b[1]);
                    mma16816(acc[nt + 1], a, b[2], b[3]);
                }
            }
            uint32_t hp[4][2];
#pragma unroll
            for (int i = 0; i < 4; i++) {
                float h[4];
#pragma unroll
                for (int q = 0; q < 4; q++) {
                    float x = rbf(acc[i][q]);
                    h[q] = __fdividef(x, 1.0f + __expf(-x));
                    acc[i][q] = 0.f;
                }
                hp[i][0] = pack_bf(h[0], h[1]);
                hp[i][1] = pack_bf(h[2], h[3]);
            }
            asm volatile("bar.sync %0, 64;" ::"r"(4 + mt) : "memory");
#pragma unroll
            for (int i = 0; i < 4; i += 2)
                stsm4(rowb + (((4 * hf + i + lch) ^ key0) << 4), hp[i][0], hp[i][1], hp[i + 1][0], hp[i + 1][1]);
            asm volatile("bar.sync %0, 64;" ::"r"(4 + mt) : "memory");
#pragma unroll
            for (int ks = 0; ks < 4; ks++) {
                uint32_t a[4];
                ldsm4(a, rowb + (((2 * ks + lch) ^ key0) << 4));
                const int line = 3 * (16 * ks + lrow) + 1;
#pragma unroll
                for (int nt = 0; nt < 4; nt += 2) {
                    uint32_t b[4];
                    ldsm4t(b, sb + P1_W2 + line * 128 + (((4 * hf + nt + lch) ^ (line & 7)) << 4));
                    mma16816(acc[nt], a, b[0], b[1]);
                    mma16816(acc[nt + 1], a, b[2], b[3]);
                }
            }
            uint32_t vq[2][3][4];
#pragma unroll
            for (int rh = 0; rh < 2; rh++) {
#pragma unroll
                for (int a = 0; a < 3; a++) {
                    const int line = 4 * (mt * 16 + g + 8 * rh) + 1 + a;
#pragma unroll
                    for (int i = 0; i < 4; i++) vq[rh][a][i] = lds32(sb + P1_SV + line * 128 + 4 * t + (((4 * hf + i) ^ (line & 7)) << 4));
                }
            }
#pragma unroll
            for (int rh = 0; rh < 2; rh++) {
#pragma unroll
                for (int a = 0; a < 3; a++) {
                    const int line = 4 * (mt * 16 + g + 8 * rh) + 1 + a;
#pragma unroll
                    for (int i = 0; i < 4; i++)
                        sts32(sb + P1_SV + line * 128 + 4 * t + (((4 * hf + i) ^ (line & 7)) << 4),
                              hmul2(pack_bf(acc[i][2 * rh], acc[i][2 * rh + 1]), vq[rh][a][i]));
                }
            }
            fence_async_smem();
            asm volatile("bar.sync %0, 64;" ::"r"(4 + mt) : "memory");
            if (lane < 8 && mt * 16 + 8 * hf + lane < nnodes)
                tma_store(&tmF, (node0 + mt * 16 + 8 * hf + lane) * 4, sb + P1_SV + (mt * 16 + 8 * hf + lane) * 512);
            asm volatile("cp.async.bulk.commit_group;" ::: "memory");
        }
        STAMPT(11, 6 * 32);
    }
    mbar_wait(bar_pos, 0);
    STAMP(1);

    uint32_t r0[12], r1[12], r2[12], rk[12];
#pragma unroll
    for (int k = 0; k < 3; k++) {
        const int ss[4] = {s4[k].x, s4[k].y, s4[k].z, s4[k].w};
        const int dd[4] = {d4[k].x, d4[k].y, d4[k].z, d4[k].w};
#pragma unroll
        for (int j = 0; j < 4; j++) rk[k * 4 + j] = 0xffffffffu;
        if (ss[0] >= 0) {
#pragma unroll
            for (int j = 0; j < 4; j++) {
                const int e = k * 4 + j;
                const int s = ss[j], d = dd[j];
                uint32_t sxy, sz, dxy, dz, rxy, rz;
                load_pos(sb + P1_POS, s, sxy, sz);
                load_pos(sb + P1_POS, d, dxy, dz);
                uint32_t db = edge_dist(sxy, sz, dxy, dz, rxy, rz);
                float inv;
                asm("rcp.approx.ftz.f32 %0, %1;" : "=f"(inv) : "f"(__uint_as_float(db << 16)));
                uint32_t bin = __umulhi((uint32_t)d, p.npc_magic);
                uint32_t dl  = (uint32_t)d - bin * (uint32_t)p.npc;
                r0[e] = (uint32_t)s | ((db - D_MIN_BITS) << 16);
                r1[e] = pack_bf(bf_lo(rxy) * inv, bf_hi(rxy) * inv);
                r2[e] = __byte_perm(pack_bf(bf_lo(rz) * inv, 0.f), dl, 0x5410);
                if (db <= D_MAX_BITS) rk[e] = (uint32_t)atomicAdd(&binCnt[bin], 1) | (bin << 16);
            }
        }
    }
    STAMP(2);
    STAMPT(12, 6 * 32);
    __syncthreads();
    STAMP(3);
    if (warp == 0) {
        int c[5], s = 0;
#pragma unroll
        for (int i = 0; i < 5; i++) { int b = lane * 5 + i; c[i] = b < p.ncta ? binCnt[b] : 0; s += c[i]; }
        int x = s;
#pragma unroll
        for (int o = 1; o < 32; o <<= 1) { int y = __shfl_up_sync(0xffffffffu, x, o); if (lane >= o) x += y; }
        int off = x - s;
#pragma unroll
        for (int i = 0; i < 5; i++) {
            int b = lane * 5 + i;
            if (b < p.ncta) { binOff[b] = off; g_offs[cta * MAX_CTA + b] = (uint32_t)off | ((uint32_t)c[i] << 16); }
            off += c[i];
        }
        if (lane == 31) ctrl[8] = x;
    }
    __syncthreads();
#pragma unroll
    for (int e = 0; e < 12; e++)
        if (rk[e] != 0xffffffffu) rk[e] = (rk[e] & 0xffffu) + lds32(sb + SM_BINOFF + (rk[e] >> 16) * 4);
#pragma unroll
    for (int e = 0; e < 12; e++)
        if (rk[e] != 0xffffffffu) sts128(sb + P1_STAGE + rk[e] * 16, make_uint4(r0[e], r1[e], r2[e], 0u));
    fence_async_smem();
    __syncthreads();
    if (tid == 0) {
        const uint32_t bytes = (uint32_t)ctrl[8] * 16u;
        if (bytes) asm volatile("cp.async.bulk.global.shared::cta.bulk_group [%0], [%1], %2;"
                                ::"l"(g_rec + (size_t)cta * REC_CAP), "r"(sb + P1_STAGE), "r"(bytes) : "memory");
        asm volatile("cp.async.bulk.commit_group;" ::: "memory");
    }
    if (tid == 32) asm volatile("red.add.release.gpu.global.u32 [%0], 1;" ::"l"(&g_bar[0]) : "memory");
    if (tid == 0 || (mlp_warp && lane < 8)) {
        asm volatile("cp.async.bulk.wait_group 0;" ::: "memory");
        asm volatile("fence.proxy.async;" ::: "memory");
    }

    __syncthreads();
    STAMP(4);
    if (tid == 0) asm volatile("red.add.release.gpu.global.u32 [%0], 1;" ::"l"(&g_bar[1]) : "memory");
    uint32_t wp[3][4];
    if (warp >= 4 && warp < 8) {
        const uint16_t* w2 = (const uint16_t*)p.w2 + 16 * (warp & 3) + g;
#pragma unroll 2
        for (int mk = 0; mk < 8; mk++) {
            uint32_t f[4];
#pragma unroll
            for (int i = 0; i < 4; i++) {
                const uint16_t* q = w2 + (16 * (mk & 3) + 2 * t + 8 * (i >> 1)) * 192 + (mk >> 2) * 128 + 8 * (i & 1);
                f[i] = (uint32_t)__ldg(q) | ((uint32_t)__ldg(q + 192) << 16);
            }
            sts128(sb + SM_HT + (mk * 128 + (tid & 127)) * 16, make_uint4(f[0], f[1], f[2], f[3]));
        }
    }
    if (warp < 4 * NCWG) {
        const uint16_t* wr = (const uint16_t*)p.wr + 16 * (warp & 3) + g;
#pragma unroll
        for (int ty = 0; ty < 3; ty++) {
#pragma unroll
            for (int i = 0; i < 4; i++) {
                const uint16_t* q = wr + (8 * (i >> 1) + 2 * t) * 192 + ty * 64 + 8 * (i & 1);
                wp[ty][i] = (uint32_t)__ldg(q) | ((uint32_t)__ldg(q + 192) << 16);
            }
        }
    }
    if (warp == 15) {
        if (lane == 0) {
            const unsigned target = (bar_seen / (unsigned)p.ncta + 1u) * (unsigned)p.ncta;
            unsigned cur;
            int spins = 0;
            do {
                asm volatile("ld.acquire.gpu.global.u32 %0, [%1];" : "=r"(cur) : "l"(&g_bar[0]) : "memory");
            } while ((int)(cur - target) < 0 && ++spins < (1 << 24));
        }
        __syncwarp();
        uint32_t v[5];
        int s = 0;
#pragma unroll
        for (int i = 0; i < 5; i++) {
            int b = lane * 5 + i;
            v[i] = b < p.ncta ? __ldcg(&g_offs[b * MAX_CTA + cta]) : 0u;
        }
#pragma unroll
        for (int i = 0; i < 5; i++) s += (int)(v[i] >> 16);
        int x = s;
#pragma unroll
        for (int o = 1; o < 32; o <<= 1) { int y = __shfl_up_sync(0xffffffffu, x, o); if (lane >= o) x += y; }
        const int tot = __shfl_sync(0xffffffffu, x, 31);
        int off = x - s;
#pragma unroll
        for (int i = 0; i < 5; i++) {
            int b = lane * 5 + i;
            if (b < p.ncta) { binCnt[b] = (int)v[i]; binOff[b] = off; }
            off += (int)(v[i] >> 16);
        }
        if (lane == 0) {
            ctrl[8] = tot;
            if (tot > STAGE_CAP) ctrl[1] = 1;
            mbar_expect_tx(bar_rec, tot > STAGE_CAP ? 0u : (uint32_t)tot * 16u);
        }
    }
    if (tid == 14 * 32) {
        const unsigned target = (bar_seen / (unsigned)p.ncta + 1u) * (unsigned)p.ncta;
        unsigned cur;
        int spins = 0;
        do {
            asm volatile("ld.acquire.gpu.global.u32 %0, [%1];" : "=r"(cur) : "l"(&g_bar[1]) : "memory");
        } while ((int)(cur - target) < 0 && ++spins < (1 << 24));
    }
    __syncthreads();
    STAMP(5);

    const int total = ctrl[8];
    if (ctrl[1] == 0) {
        const int b = (lane << 4) | warp;
        if (lane < 9 && b < p.ncta) {
            const uint32_t v = (uint32_t)binCnt[b], c = v >> 16;
            if (c) {
                asm volatile("fence.proxy.async;" ::: "memory");
                bulk_g2s(sb + SM_STAGE2 + (uint32_t)binOff[b] * 16u, g_rec + (size_t)b * REC_CAP + (v & 0xffffu), c * 16u, bar_rec);
            }
        }
    }
    mbar_wait(bar_rec, 0);
    STAMP(13);
    constexpr int RPT = 8;
    uint4 rec[RPT];
    const bool okc = ctrl[1] == 0;
#pragma unroll
    for (int k = 0; k < RPT; k++) {
        const int i = tid + k * NT;
        if (okc && i < total) rec[k] = lds128(sb + SM_STAGE2 + i * 16);
    }
#pragma unroll
    for (int k = 0; k < RPT; k++) {
        const int i = tid + k * NT;
        if (okc && i < total) rec[k].w = (uint32_t)atomicAdd(&nCnt[rec[k].z >> 16], 1);
    }
    if (okc) {
        for (int i = tid + RPT * NT; i < total; i += NT) {
            uint32_t dl = lds32(sb + SM_STAGE2 + i * 16 + 8) >> 16;
            sts32(sb + SM_STAGE2 + i * 16 + 12, (uint32_t)atomicAdd(&nCnt[dl], 1));
        }
    }
    __syncthreads();
    if (warp == 0) {
        int c[3], s = 0;
#pragma unroll
        for (int i = 0; i < 3; i++) {
            int b = lane * 3 + i;
            c[i] = b < nnodes ? max(16, (nCnt[b] + 15) & ~15) : 0;
            s += c[i];
        }
        int x = s;
#pragma unroll
        for (int o = 1; o < 32; o <<= 1) { int y = __shfl_up_sync(0xffffffffu, x, o); if (lane >= o) x += y; }
        const int slots = __shfl_sync(0xffffffffu, x, 31);
        int off = x - s, below1 = 0, below2 = 0;
#pragma unroll
        for (int i = 0; i < 3; i++) {
            int b = lane * 3 + i;
            if (b < nnodes) {
                nInfo[b] = (uint32_t)off | ((uint32_t)c[i] << 16);
                const int centre3 = 3 * (2 * off + c[i]);
                below1 += centre3 < 2 * slots;
                below2 += centre3 < 4 * slots;
            }
            off += c[i];
        }
        below1 = __reduce_add_sync(0xffffffffu, below1);
        below2 = __reduce_add_sync(0xffffffffu, below2);
        if (lane == 0) {
            ctrl[2] = below1;
            ctrl[3] = below2;
            ctrl[4] = slots;
            if (slots > SLOT_CAP) ctrl[1] = 1;
        }
    }
    __syncthreads();
    if (ctrl[1] == 0) {
        uint16_t* sid = (uint16_t*)(smem + SM_SID);
        uint2* meta = (uint2*)(smem + SM_META);
#pragma unroll
        for (int k = 0; k < RPT; k++)
            if (tid + k * NT < total) rec[k].w += lds32(sb + SM_NINFO + (rec[k].z >> 16) * 4) & 0xffffu;
#pragma unroll
        for (int k = 0; k < RPT; k++) {
            if (tid + k * NT < total) {
                const uint4 r = rec[k];
                sid[r.w]  = (uint16_t)(r.x & 0xffffu);
                meta[r.w] = make_uint2(((r.x >> 16) << 5) | (r.z << 16), r.y);
            }
        }
        for (int i = tid + RPT * NT; i < total; i += NT) {
            uint4 r = lds128(sb + SM_STAGE2 + i * 16);
            int pos = (int)(nInfo[r.z >> 16] & 0xffffu) + (int)r.w;
            sid[pos]  = (uint16_t)(r.x & 0xffffu);
            meta[pos] = make_uint2(((r.x >> 16) << 5) | (r.z << 16), r.y);
        }
        for (int i = tid; i < nnodes * 16; i += NT) {
            int nl = i >> 4, c = nCnt[nl];
            int j = (c & ~15) + (i & 15);
            if (j >= c && (j < 16 || (c & 15))) {
                int pos = (int)(nInfo[nl] & 0xffffu) + j;
                sid[pos]  = 0xffffu;
                meta[pos] = make_uint2((uint32_t)TAB_ZERO << 5, 0u);
            }
        }
    }
    fence_async_smem();
    __syncthreads();
    STAMP(6);

    if (__shfl_sync(0xffffffffu, ctrl[1], 0) != 0) {
        float* acc = (float*)(smem + P1_POS);
        for (int i = tid; i < nnodes * 256; i += NT) acc[i] = 0.f;
        __syncthreads();
        const uint16_t* posu = (const uint16_t*)p.pos;
        const uint32_t* tabg = (const uint32_t*)g_table;
        const uint32_t* Fw = (const uint32_t*)g_F;
        for (int e0 = warp * 32; e0 < p.E; e0 += NT) {
            int e = e0 + lane;
            int s = 0, d = 0;
            uint32_t db = 0xffff, rxy = 0, rz = 0;
            bool act = false;
            if (e < p.E) {
                s = p.src[e]; d = p.dst[e];
                if (d >= node0 && d < node0 + nnodes) {
                    uint32_t sxy = posu[s * 3] | ((uint32_t)posu[s * 3 + 1] << 16), sz = posu[s * 3 + 2];
                    uint32_t dxy = posu[d * 3] | ((uint32_t)posu[d * 3 + 1] << 16), dz = posu[d * 3 + 2];
                    db  = edge_dist(sxy, sz, dxy, dz, rxy, rz);
                    act = db <= D_MAX_BITS;
                }
            }
            unsigned m = __ballot_sync(0xffffffffu, act);
            while (m) {
                int l = __ffs(m) - 1;
                m &= m - 1;
                int es = __shfl_sync(0xffffffffu, s, l), ed = __shfl_sync(0xffffffffu, d, l);
                uint32_t edb = __shfl_sync(0xffffffffu, db, l), exy = __shfl_sync(0xffffffffu, rxy, l), ez = __shfl_sync(0xffffffffu, rz, l);
                float inv = 1.0f / __uint_as_float(edb << 16);
                float rh[3] = {rbf(bf_lo(exy) * inv), rbf(bf_hi(exy) * inv), rbf(bf_lo(ez) * inv)};
                const uint32_t* fr = Fw + (size_t)es * 128 + lane;
                const uint32_t fh = __ldcg(fr);
                const uint32_t q[3] = {__ldcg(fr + 32), __ldcg(fr + 64), __ldcg(fr + 96)};
                float ps0 = 0.f, ps1 = 0.f, pr0 = 0.f, pr1 = 0.f;
                for (int j2 = 0; j2 < 32; j2++) {
                    uint32_t hj = __shfl_sync(0xffffffffu, fh, j2);
                    uint32_t a0 = *(const uint32_t*)(p.w2 + (2 * j2) * 192 + 2 * lane), a1 = *(const uint32_t*)(p.w2 + (2 * j2 + 1) * 192 + 2 * lane);
                    uint32_t b0 = *(const uint32_t*)(p.w2 + (2 * j2) * 192 + 128 + 2 * lane), b1 = *(const uint32_t*)(p.w2 + (2 * j2 + 1) * 192 + 128 + 2 * lane);
                    ps0 += bf_lo(hj) * bf_lo(a0) + bf_hi(hj) * bf_lo(a1);
                    ps1 += bf_lo(hj) * bf_hi(a0) + bf_hi(hj) * bf_hi(a1);
                    pr0 += bf_lo(hj) * bf_lo(b0) + bf_hi(hj) * bf_lo(b1);
                    pr1 += bf_lo(hj) * bf_hi(b0) + bf_hi(hj) * bf_hi(b1);
                }
                float ws0 = 0.f, ws1 = 0.f, wv0 = 0.f, wv1 = 0.f, wr0 = 0.f, wr1 = 0.f;
                for (int k2 = 0; k2 < 8; k2++) {
                    uint32_t rk2 = __ldcg(tabg + (edb - D_MIN_BITS) * 8 + k2);
#pragma unroll
                    for (int h = 0; h < 2; h++) {
                        float rv = h ? bf_hi(rk2) : bf_lo(rk2);
                        const __nv_bfloat16* wrow = p.wr + (2 * k2 + h) * 192 + 2 * lane;
                        uint32_t a = *(const uint32_t*)wrow, b = *(const uint32_t*)(wrow + 64), c = *(const uint32_t*)(wrow + 128);
                        ws0 += rv * bf_lo(a); ws1 += rv * bf_hi(a);
                        wv0 += rv * bf_lo(b); wv1 += rv * bf_hi(b);
                        wr0 += rv * bf_lo(c); wr1 += rv * bf_hi(c);
                    }
                }
                float* a = acc + (ed - node0) * 256 + 2 * lane;
                atomicAdd(a, ps0 * ws0); atomicAdd(a + 1, ps1 * ws1);
#pragma unroll
                for (int c = 0; c < 3; c++) {
                    atomicAdd(a + 64 * (c + 1), wv0 * bf_lo(q[c]) + pr0 * wr0 * rh[c]);
                    atomicAdd(a + 64 * (c + 1) + 1, wv1 * bf_hi(q[c]) + pr1 * wr1 * rh[c]);
                }
            }
        }
        __syncthreads();
        for (int i = tid; i < nnodes * 128; i += NT) {
            uint32_t r = *(const uint32_t*)(p.sv + (size_t)node0 * 256 + 2 * i);
            *(uint32_t*)(p.out + (size_t)node0 * 256 + 2 * i) = pack_bf(bf_lo(r) + acc[2 * i], bf_hi(r) + acc[2 * i + 1]);
        }
        return;
    }

    const int slots = __reduce_max_sync(0xffffffffu, ctrl[4]);
    const int nstage = slots <= SLOT_CAP4 ? 4 : 3;
    const uint32_t ring = sb + (nstage == 4 ? SM_RING4 : SM_RING3);
    const int wg = warp >> 2;
    const int sc = wg < NCWG ? wg : warp - 4 * NCWG;
    const int n_begin = __reduce_max_sync(0xffffffffu, sc == 0 ? 0 : (sc <= NCWG ? ctrl[1 + min(sc, 2)] : 0));
    const int n_end   = __reduce_max_sync(0xffffffffu, sc >= NCWG - 1 ? nnodes : ctrl[2 + sc]);
    const int g0 = __reduce_max_sync(0xffffffffu, n_begin < nnodes ? (int)(nInfo[n_begin] & 0xffffu) : slots) >> 4;
    const int g1 = __reduce_max_sync(0xffffffffu, n_end < nnodes ? (int)(nInfo[n_end] & 0xffffu) : slots) >> 4;
    const uint32_t ring_wg = ring + sc * nstage * STAGE_B;
    const uint32_t full_wg = bar_full + sc * MAX_STAGE * 8;
    constexpr uint32_t EMPTY_OFF = NCWG * MAX_STAGE * 8;
    if (wg == NCWG) {
        asm volatile("setmaxnreg.dec.sync.aligned.u32 56;");
        if (sc < NCWG) {
            const int e = lane >> 1, half = lane & 1;
            const uint32_t coef_off = e * 128 + ((half ^ (e & 7)) << 4);
            const int vrot = (e & 3) ^ ((e >> 1) & 3);
            const uint8_t* tab = (const uint8_t*)g_table + half * 16;
            int stage = 0;
            uint32_t phase = 1, st = ring_wg, fb = full_wg;
            uint2 ma, mb;
            uint4 ta, tb;
            auto pre = [&](uint2& m, uint4& tv, int gi) {
                m  = lds64(sb + SM_META + (gi * 16 + e) * 8);
                tv = __ldg((const uint4*)(tab + (m.x & 0xffffu)));
            };
            auto produce = [&](const uint2& m, const uint4& tv) {
                const uint32_t mul[4] = {0x3f803f80u, __byte_perm(m.y, 0, 0x1010), __byte_perm(m.y, 0, 0x3232), __byte_perm(m.x, 0, 0x3232)};
                uint4 o[4];
#pragma unroll
                for (int j = 0; j < 4; j++) {
                    const int v = j ^ vrot;
                    const uint32_t lo = (v & 1) ? mul[1] : mul[0], hi = (v & 1) ? mul[3] : mul[2];
                    const uint32_t mm = (v & 2) ? hi : lo;
                    o[j] = make_uint4(hmul2(tv.x, mm), hmul2(tv.y, mm), hmul2(tv.z, mm), hmul2(tv.w, mm));
                }
                mbar_wait(fb + EMPTY_OFF, phase);
                const uint32_t a = st + coef_off;
#pragma unroll
                for (int j = 0; j < 4; j++) sts128(a ^ ((j ^ vrot) << 5), o[j]);
                fence_async_smem();
                __syncwarp();
                mbar_arrive_elected(fb);
                st += STAGE_B; fb += 8;
                if (++stage == nstage) { stage = 0; phase ^= 1; st = ring_wg; fb = full_wg; }
            };
            int gi = g0;
            if (gi < g1) pre(ma, ta, gi);
            while (gi < g1) {
                if (gi + 1 < g1) pre(mb, tb, gi + 1);
                produce(ma, ta);
                if (++gi >= g1) break;
                if (gi + 1 < g1) pre(ma, ta, gi + 1);
                produce(mb, tb);
                ++gi;
            }
        }
    } else {
        asm volatile("setmaxnreg.inc.sync.aligned.u32 152;");
        const int w = warp & 3;
        uint32_t wA[2][4][4];
#pragma unroll
        for (int mk = 0; mk < 8; mk++) {
            const uint4 q = lds128(sb + SM_HT + (mk * 128 + (tid & 127)) * 16);
            wA[mk >> 2][mk & 3][0] = q.x; wA[mk >> 2][mk & 3][1] = q.y; wA[mk >> 2][mk & 3][2] = q.z; wA[mk >> 2][mk & 3][3] = q.w;
        }
        uint32_t aoff[4];
        {
            const int e = (lane & 7) + 8 * (lane >> 4), ch = 2 * w + ((lane >> 3) & 1);
#pragma unroll
            for (int b = 0; b < 4; b++) aoff[b] = 2048 + e * 640 + b * 128 + ((ch ^ ((5 * e + b) & 7)) << 4);
        }
        const uint32_t ht = sb + SM_HT + wg * 8192;
        const uint32_t stsm_a = ht + (16 * w + (lane & 15)) * 128 + (((lane >> 4) ^ (lane & 7)) << 4);
        const uint32_t dht = desc_lo(ht);
        const uint32_t out_lane = (uint32_t)node0 * 512u + t * 128 + (16 * w + (g & 1) * 8 + (g & 6)) * 2;

        int gn = g0;
        const uint32_t sid_w = sb + SM_SID + w * 8;
        auto gather = [&](uint32_t st, uint32_t fb) {
            const uint2 id = lds64(sid_w + gn * 32);
            uint32_t leader;
            asm volatile("{\n.reg .pred p;\nelect.sync _|p, 0xffffffff;\nselp.u32 %0, 1, 0, p;\n}" : "=r"(leader));
            if (leader) {
                const uint32_t dst = st + 2048 + w * 4 * 640;
                if ((id.y >> 16) != 0xffffu) {
                    mbar_expect_tx(fb, 4 * 512);
                    tma_load(dst, &tmF, (int)(id.x & 0xffffu) * 4, fb);
                    tma_load(dst + 640, &tmF, (int)(id.x >> 16) * 4, fb);
                    tma_load(dst + 1280, &tmF, (int)(id.y & 0xffffu) * 4, fb);
                    tma_load(dst + 1920, &tmF, (int)(id.y >> 16) * 4, fb);
                } else {
                    const uint32_t i0 = id.x & 0xffffu, i1 = id.x >> 16, i2 = id.y & 0xffffu;
                    mbar_expect_tx(fb, ((i0 != 0xffffu) + (i1 != 0xffffu) + (i2 != 0xffffu)) * 512);
                    if (i0 != 0xffffu) tma_load(dst, &tmF, (int)i0 * 4, fb);
                    if (i1 != 0xffffu) tma_load(dst + 640, &tmF, (int)i1 * 4, fb);
                    if (i2 != 0xffffu) tma_load(dst + 1280, &tmF, (int)i2 * 4, fb);
                }
            }
            __syncwarp();
            gn++;
        };
        for (int i = 0; i < nstage && gn < g1; i++) gather(ring_wg + i * STAGE_B, full_wg + i * 8);
        asm volatile("bar.sync 4, 384;" ::: "memory");

        float ys[8], yv[24], dQ[3][8];
#pragma unroll
        for (int i = 0; i < 24; i++) yv[i] = 0.f;
#pragma unroll
        for (int i = 0; i < 8; i++) { ys[i] = 0.f; dQ[0][i] = 0.f; dQ[1][i] = 0.f; dQ[2][i] = 0.f; }
        int left = g1 - g0;
        int stage = 0;
        uint32_t phase = 0, st = ring_wg, fb = full_wg;
        uint32_t pst = 0, pfb = 0, pphase = 0;
        int nl = n_begin, gi = 0, G = 0;
        uint32_t resid = 0;
        auto node_begin = [&]() {
            G = __reduce_max_sync(0xffffffffu, (int)(nInfo[nl] >> 20));
            resid = __ldg((const uint32_t*)((const uint8_t*)p.sv + (out_lane + (uint32_t)nl * 512u)));
            gi = 0;
        };
        if (left > 0) node_begin();
        while (left > 0) {
            uint32_t A[4][4];
            mbar_wait(fb, phase);
#pragma unroll
            for (int b = 0; b < 4; b++) ldsm4t(A[b], st + aoff[b]);
            const uint32_t bd = desc_lo(st);
            wg_fence();
            wgmma_n64_p(ys, yv, A[0], bd, gi);
            wgmma_n16_p(dQ[0], A[1], bd, gi);
            wgmma_n16_p(dQ[1], A[2], bd, gi);
            wgmma_n16_p(dQ[2], A[3], bd, gi);
            wg_commit();
            if (pfb != 0 && gn < g1) {
                mbar_wait(pfb + EMPTY_OFF, pphase);
                gather(pst, pfb);
            }
            pst = st; pfb = fb; pphase = phase;
            st += STAGE_B; fb += 8;
            if (++stage == nstage) { stage = 0; phase ^= 1; st = ring_wg; fb = full_wg; }
            --left;
            const bool last = ++gi == G;
            wg_wait0();
            mbar_arrive_elected(pfb + EMPTY_OFF);
            if (last) {
                named_barrier(1 + wg);
                uint32_t sa = stsm_a;
                asm volatile("" : "+r"(sa));
                stsm4(sa, pack_bf(ys[0], ys[1]), pack_bf(ys[2], ys[3]), pack_bf(ys[4], ys[5]), pack_bf(ys[6], ys[7]));
#pragma unroll
                for (int i = 0; i < 6; i += 2) {
                    stsm4(sa ^ ((i + 2) << 4),
                          pack_bf(yv[4 * i], yv[4 * i + 1]), pack_bf(yv[4 * i + 2], yv[4 * i + 3]),
                          pack_bf(yv[4 * i + 4], yv[4 * i + 5]), pack_bf(yv[4 * i + 6], yv[4 * i + 7]));
                }
                fence_async_smem();
                named_barrier(1 + wg);
                float zs[8], zv[24];
                wg_fence();
                wgmma_n16_first(zs, wA[0][0], dht);
                wgmma_n48_first(zv, wA[1][0], dht + 2);
#pragma unroll
                for (int ks = 1; ks < 4; ks++) {
                    wgmma_n16(zs, wA[0][ks], dht + ks * 128);
                    wgmma_n48(zv, wA[1][ks], dht + ks * 128 + 2);
                }
                wg_commit();
#pragma unroll
                for (int i = 0; i < 12; i++) asm volatile("" : "+r"(wp[i >> 2][i & 3]));
                float pr[4][2];
#pragma unroll
                for (int a = 0; a < 3; a++) {
                    const float* q = dQ[a];
                    pr[a + 1][0] = bf_lo(wp[1][0]) * q[0] + bf_hi(wp[1][0]) * q[1] + bf_lo(wp[1][2]) * q[4] + bf_hi(wp[1][2]) * q[5];
                    pr[a + 1][1] = bf_lo(wp[1][1]) * q[2] + bf_hi(wp[1][1]) * q[3] + bf_lo(wp[1][3]) * q[6] + bf_hi(wp[1][3]) * q[7];
                }
                wg_wait0();
                pr[0][0] = bf_lo(wp[0][0]) * zs[0] + bf_hi(wp[0][0]) * zs[1] + bf_lo(wp[0][2]) * zs[4] + bf_hi(wp[0][2]) * zs[5];
                pr[0][1] = bf_lo(wp[0][1]) * zs[2] + bf_hi(wp[0][1]) * zs[3] + bf_lo(wp[0][3]) * zs[6] + bf_hi(wp[0][3]) * zs[7];
#pragma unroll
                for (int a = 0; a < 3; a++) {
                    const float* y = zv + 8 * a;
                    pr[a + 1][0] += bf_lo(wp[2][0]) * y[0] + bf_hi(wp[2][0]) * y[1] + bf_lo(wp[2][2]) * y[4] + bf_hi(wp[2][2]) * y[5];
                    pr[a + 1][1] += bf_lo(wp[2][1]) * y[2] + bf_hi(wp[2][1]) * y[3] + bf_lo(wp[2][3]) * y[6] + bf_hi(wp[2][3]) * y[7];
                }
                const bool hi2 = t & 2, hi1 = t & 1, odd = g & 1;
                float ka0 = hi2 ? pr[2][0] : pr[0][0], ka1 = hi2 ? pr[2][1] : pr[0][1];
                float kb0 = hi2 ? pr[3][0] : pr[1][0], kb1 = hi2 ? pr[3][1] : pr[1][1];
                float sa0 = hi2 ? pr[0][0] : pr[2][0], sa1 = hi2 ? pr[0][1] : pr[2][1];
                float sb0 = hi2 ? pr[1][0] : pr[3][0], sb1 = hi2 ? pr[1][1] : pr[3][1];
                ka0 += __shfl_xor_sync(0xffffffffu, sa0, 2); ka1 += __shfl_xor_sync(0xffffffffu, sa1, 2);
                kb0 += __shfl_xor_sync(0xffffffffu, sb0, 2); kb1 += __shfl_xor_sync(0xffffffffu, sb1, 2);
                float k0 = hi1 ? kb0 : ka0, k1 = hi1 ? kb1 : ka1;
                float s0 = hi1 ? ka0 : kb0, s1 = hi1 ? ka1 : kb1;
                k0 += __shfl_xor_sync(0xffffffffu, s0, 1);
                k1 += __shfl_xor_sync(0xffffffffu, s1, 1);
                const float other = __shfl_xor_sync(0xffffffffu, odd ? k0 : k1, 4);
                const float lo = odd ? other : k0, hi = odd ? k1 : other;
                *(uint32_t*)((uint8_t*)p.out + (out_lane + (uint32_t)nl * 512u)) = pack_bf(bf_lo(resid) + lo, bf_hi(resid) + hi);
                if (++nl < n_end) node_begin();
            }
        }
    }
    STAMP(8);
}

typedef CUresult (*EncodeFn)(CUtensorMap*, CUtensorMapDataType, cuuint32_t, void*, const cuuint64_t*, const cuuint64_t*,
                             const cuuint32_t*, const cuuint32_t*, CUtensorMapInterleave, CUtensorMapSwizzle,
                             CUtensorMapL2promotion, CUtensorMapFloatOOBfill);

void make_map(EncodeFn enc, CUtensorMap* tm, const void* base, uint64_t lines, uint32_t box) {
    cuuint64_t gd[2] = {64, lines};
    cuuint64_t gs[1] = {128};
    cuuint32_t bd[2] = {64, box};
    cuuint32_t es[2] = {1, 1};
    enc(tm, CU_TENSOR_MAP_DATA_TYPE_BFLOAT16, 2, const_cast<void*>(base), gd, gs, bd, es, CU_TENSOR_MAP_INTERLEAVE_NONE,
        CU_TENSOR_MAP_SWIZZLE_128B, CU_TENSOR_MAP_L2_PROMOTION_L2_128B, CU_TENSOR_MAP_FLOAT_OOB_FILL_NONE);
}

}

extern "C" void kernel_launch(void* const* d_in, const int* in_sizes, int n_in, void* d_out, int out_size) {
    (void)n_in; (void)out_size;
    static int n_sm = 0;
    static EncodeFn enc = nullptr;
    static void* f_ptr = nullptr;
    if (n_sm == 0) {
        int dev = 0;
        cudaGetDevice(&dev);
        cudaDeviceGetAttribute(&n_sm, cudaDevAttrMultiProcessorCount, dev);
        cudaFuncSetAttribute(painn_kernel, cudaFuncAttributeMaxDynamicSharedMemorySize, SM_TOTAL);
        void* fn = nullptr;
        cudaDriverEntryPointQueryResult qr;
        cudaGetDriverEntryPoint("cuTensorMapEncodeTiled", &fn, cudaEnableDefault, &qr);
        enc = (EncodeFn)fn;
        cudaGetSymbolAddress(&f_ptr, g_F);
    }
    Params p;
    p.sv    = (const __nv_bfloat16*)d_in[0];
    p.pos   = (const __nv_bfloat16*)d_in[1];
    p.src   = (const int*)d_in[2];
    p.dst   = (const int*)d_in[3];
    p.freqs = (const __nv_bfloat16*)d_in[4];
    p.w1    = (const __nv_bfloat16*)d_in[5];
    p.w2    = (const __nv_bfloat16*)d_in[6];
    p.wr    = (const __nv_bfloat16*)d_in[7];
    p.out   = (__nv_bfloat16*)d_out;
    p.N = in_sizes[1] / 3;
    p.E = in_sizes[2];
    p.ncta = n_sm < MAX_CTA ? n_sm : MAX_CTA;
    p.npc = (p.N + p.ncta - 1) / p.ncta;
    p.npc_magic = (uint32_t)(0x100000000ull / (uint32_t)p.npc) + 1u;
    p.quads_per_cta = ((p.E >> 2) + p.ncta - 1) / p.ncta;
    if (!enc || p.N > MAX_N || p.npc > MAX_NPC || (p.E & 3) || p.quads_per_cta > MAX_ROUNDS * 32) return;

    CUtensorMap tmF, tmSV, tmW1, tmW2;
    make_map(enc, &tmF, f_ptr, (uint64_t)p.N * 4, 4);
    make_map(enc, &tmSV, p.sv, (uint64_t)p.N * 4, 160);
    make_map(enc, &tmW1, p.w1, 64, 64);
    make_map(enc, &tmW2, p.w2, 192, 192);

    cudaLaunchConfig_t cfg = {};
    cfg.gridDim = dim3(p.ncta);
    cfg.blockDim = dim3(NT);
    cfg.dynamicSmemBytes = SM_TOTAL;
    cfg.stream = cudaStreamPerThread;
    cudaLaunchAttribute attr[1];
    attr[0].id = cudaLaunchAttributeCooperative;
    attr[0].val.cooperative = 1;
    cfg.attrs = attr;
    cfg.numAttrs = 1;
    cudaLaunchKernelEx(&cfg, painn_kernel, p, tmF, tmSV, tmW1, tmW2);
}
```

```cpp
#include <cuda_runtime.h>
#include <cuda.h>
#include <cuda_bf16.h>
#include <stdint.h>

namespace {

constexpr int NT        = 512;
constexpr int NCWG      = 3;
constexpr int MAX_N     = 10240;
constexpr int MAX_CTA   = 144;
constexpr int MAX_NPC   = 80;
constexpr int MAX_ROUNDS = 38;
constexpr int REC_CAP   = MAX_ROUNDS * 128;
constexpr int SLOT_CAP  = 6144;
constexpr int MAX_STAGE = 4;
constexpr int STAGE_B   = 12288;

constexpr uint32_t D_MIN_BITS = 0x38D2;
constexpr uint32_t D_MAX_BITS = 0x409C;
constexpr int TAB_ROWS  = (int)(D_MAX_BITS - D_MIN_BITS) + 1;
constexpr int TAB_ZERO  = TAB_ROWS;
constexpr int TAB_BYTES = (TAB_ROWS + 1) * 32;

constexpr int SM_BINCNT = 0;
constexpr int SM_BINOFF = SM_BINCNT + MAX_CTA * 4;
constexpr int SM_NCNT   = SM_BINOFF + MAX_CTA * 4;
constexpr int SM_NINFO  = SM_NCNT + MAX_NPC * 4;
constexpr int SM_CTRL   = SM_NINFO + MAX_NPC * 4;
constexpr int SM_BARS   = SM_CTRL + 64;
constexpr int SM_SID    = 2048 + 128;
constexpr int SM_META   = SM_SID + SLOT_CAP * 2;
constexpr int SM_TOTAL  = 232448;
constexpr int SM_HT     = (SM_TOTAL - NCWG * 8192) / 1024 * 1024;
constexpr int SM_RING4  = SM_HT - NCWG * 4 * STAGE_B;
constexpr int SM_RING3  = SM_HT - NCWG * 3 * STAGE_B;
constexpr int SLOT_CAP4 = (SM_RING4 - SM_META) / 8;
constexpr int SM_STAGE2 = SM_RING3 - 0;
constexpr int STAGE_CAP = (SM_HT - SM_RING3) / 16;
constexpr int P1_POS    = 3072;
constexpr int P1_STAGE  = P1_POS + 61440;
constexpr int P1_SV     = (P1_STAGE + REC_CAP * 16 + 1023) / 1024 * 1024;
constexpr int P1_W1     = P1_SV + MAX_NPC * 512;
constexpr int P1_W2     = P1_W1 + 8192;
constexpr int P1_END    = P1_W2 + 24576;
static_assert(SM_BARS + (4 + 2 * NCWG * MAX_STAGE) * 8 <= SM_SID, "misc block");
static_assert(SM_BARS + 256 <= P1_POS, "misc block");
static_assert(P1_END <= SM_TOTAL, "phase 1 overlay");
static_assert(SM_META + SLOT_CAP * 8 <= SM_RING3, "CSR");
static_assert(SM_RING4 % 1024 == 0 && SM_RING3 % 1024 == 0 && SM_HT % 1024 == 0, "alignment");
static_assert(SM_BARS % 8 == 0 && SM_META % 8 == 0, "alignment");
static_assert(MAX_N * 6 <= 61440, "pos");
static_assert(SM_SID + MAX_NPC * 1024 <= SM_TOTAL, "slow path accumulators");

__device__ __align__(1024) uint4 g_F[MAX_N * 32];
__device__ uint4    g_rec[MAX_CTA * REC_CAP];
__device__ uint32_t g_offs[MAX_CTA * MAX_CTA];
__device__ uint4    g_table[(TAB_BYTES + 15) / 16];
__device__ unsigned g_bar[2];
#define STAMP(k)
#define STAMPT(k, T)
#define ITS(k)

struct Params {
    const __nv_bfloat16* sv;
    const __nv_bfloat16* pos;
    const int*           src;
    const int*           dst;
    const __nv_bfloat16* freqs;
    const __nv_bfloat16* w1;
    const __nv_bfloat16* w2;
    const __nv_bfloat16* wr;
    __nv_bfloat16*       out;
    int N, E, ncta, npc;
    uint32_t npc_magic;
    int quads_per_cta;
};

__device__ __forceinline__ uint32_t smem_u32(const void* p) { return (uint32_t)__cvta_generic_to_shared(p); }
__device__ __forceinline__ float bf_lo(uint32_t v) { return __uint_as_float(v << 16); }
__device__ __forceinline__ float bf_hi(uint32_t v) { return __uint_as_float(v & 0xffff0000u); }
__device__ __forceinline__ float bf_u16(uint16_t v) { return __uint_as_float((uint32_t)v << 16); }
__device__ __forceinline__ uint32_t pack_bf(float lo, float hi) {
    uint32_t r;
    asm("cvt.rn.bf16x2.f32 %0, %1, %2;" : "=r"(r) : "f"(hi), "f"(lo));
    return r;
}
__device__ __forceinline__ float rbf(float x) { return bf_lo(pack_bf(x, 0.f)); }
__device__ __forceinline__ uint32_t hmul2(uint32_t a, uint32_t b) {
    uint32_t r;
    asm("mul.rn.bf16x2 %0, %1, %2;" : "=r"(r) : "r"(a), "r"(b));
    return r;
}
__device__ __forceinline__ uint32_t hsub2(uint32_t a, uint32_t b) {
    uint32_t r;
    asm("sub.rn.bf16x2 %0, %1, %2;" : "=r"(r) : "r"(a), "r"(b));
    return r;
}
__device__ __forceinline__ uint32_t lds32(uint32_t a) { uint32_t v; asm volatile("ld.shared.u32 %0, [%1];" : "=r"(v) : "r"(a)); return v; }
__device__ __forceinline__ uint32_t lds16(uint32_t a) { uint16_t v; asm volatile("ld.shared.u16 %0, [%1];" : "=h"(v) : "r"(a)); return v; }
__device__ __forceinline__ uint2 lds64(uint32_t a) { uint2 v; asm volatile("ld.shared.v2.u32 {%0,%1}, [%2];" : "=r"(v.x), "=r"(v.y) : "r"(a)); return v; }
__device__ __forceinline__ uint4 lds128(uint32_t a) { uint4 v; asm volatile("ld.shared.v4.u32 {%0,%1,%2,%3}, [%4];" : "=r"(v.x), "=r"(v.y), "=r"(v.z), "=r"(v.w) : "r"(a)); return v; }
__device__ __forceinline__ void sts32(uint32_t a, uint32_t v) { asm volatile("st.shared.u32 [%0], %1;" ::"r"(a), "r"(v) : "memory"); }
__device__ __forceinline__ void sts128(uint32_t a, uint4 v) { asm volatile("st.shared.v4.u32 [%0], {%1,%2,%3,%4};" ::"r"(a), "r"(v.x), "r"(v.y), "r"(v.z), "r"(v.w) : "memory"); }
__device__ __forceinline__ void mbar_init(uint32_t bar, int cnt) { asm volatile("mbarrier.init.shared::cta.b64 [%0], %1;" ::"r"(bar), "r"(cnt) : "memory"); }
__device__ __forceinline__ void mbar_expect_tx(uint32_t bar, uint32_t bytes) { asm volatile("mbarrier.arrive.expect_tx.shared::cta.b64 _, [%0], %1;" ::"r"(bar), "r"(bytes) : "memory"); }
__device__ __forceinline__ void mbar_arrive(uint32_t bar) { asm volatile("mbarrier.arrive.shared::cta.b64 _, [%0];" ::"r"(bar) : "memory"); }
__device__ __forceinline__ void mbar_wait(uint32_t bar, uint32_t parity) {
    asm volatile("{\n.reg .pred p;\n.reg .u32 c;\n"
                 "mbarrier.try_wait.parity.shared::cta.b64 p, [%0], %1;\n"
                 "@p bra DONE_%=;\n"
                 "mov.u32 c, 0;\n"
                 "LOOP_%=:\n"
                 "mbarrier.try_wait.parity.shared::cta.b64 p, [%0], %1;\n"
                 "@p bra DONE_%=;\n"
                 "add.u32 c, c, 1;\n"
                 "setp.lt.u32 p, c, 4194304;\n"
                 "@p bra LOOP_%=;\n"
                 "DONE_%=:\n}"
                 ::"r"(bar), "r"(parity) : "memory");
}
__device__ __forceinline__ void mbar_arrive_elected(uint32_t bar) {
    asm volatile("{\n.reg .pred p;\nelect.sync _|p, 0xffffffff;\n@p mbarrier.arrive.shared::cta.b64 _, [%0];\n}" ::"r"(bar) : "memory");
}
__device__ __forceinline__ void bulk_g2s(uint32_t dst, const void* src, uint32_t bytes, uint32_t bar) {
    asm volatile("cp.async.bulk.shared::cluster.global.mbarrier::complete_tx::bytes [%0], [%1], %2, [%3];"
                 ::"r"(dst), "l"(src), "r"(bytes), "r"(bar) : "memory");
}
__device__ __forceinline__ void tma_load(uint32_t dst, const CUtensorMap* tm, int line, uint32_t bar) {
    asm volatile("cp.async.bulk.tensor.2d.shared::cluster.global.mbarrier::complete_tx::bytes [%0], [%1, {%3, %4}], [%2];"
                 ::"r"(dst), "l"(tm), "r"(bar), "r"(0), "r"(line) : "memory");
}
__device__ __forceinline__ void tma_store(const CUtensorMap* tm, int line, uint32_t src) {
    asm volatile("cp.async.bulk.tensor.2d.global.shared::cta.bulk_group [%0, {%2, %3}], [%1];"
                 ::"l"(tm), "r"(src), "r"(0), "r"(line) : "memory");
}
__device__ __forceinline__ void fence_async_smem() { asm volatile("fence.proxy.async.shared::cta;" ::: "memory"); }
__device__ __forceinline__ void named_barrier(int id) { asm volatile("bar.sync %0, 128;" ::"r"(id) : "memory"); }
__device__ __forceinline__ void ldsm4(uint32_t (&r)[4], uint32_t a) {
    asm volatile("ldmatrix.sync.aligned.m8n8.x4.shared.b16 {%0,%1,%2,%3}, [%4];" : "=r"(r[0]), "=r"(r[1]), "=r"(r[2]), "=r"(r[3]) : "r"(a) : "memory");
}
__device__ __forceinline__ void ldsm4t(uint32_t (&r)[4], uint32_t a) {
    asm volatile("ldmatrix.sync.aligned.m8n8.x4.trans.shared.b16 {%0,%1,%2,%3}, [%4];" : "=r"(r[0]), "=r"(r[1]), "=r"(r[2]), "=r"(r[3]) : "r"(a) : "memory");
}
__device__ __forceinline__ void stsm4(uint32_t a, uint32_t r0, uint32_t r1, uint32_t r2, uint32_t r3) {
    asm volatile("stmatrix.sync.aligned.m8n8.x4.shared.b16 [%0], {%1,%2,%3,%4};" ::"r"(a), "r"(r0), "r"(r1), "r"(r2), "r"(r3) : "memory");
}
__device__ __forceinline__ void mma16816(float (&c)[4], const uint32_t (&a)[4], uint32_t b0, uint32_t b1) {
    asm volatile("mma.sync.aligned.m16n8k16.row.col.f32.bf16.bf16.f32 {%0,%1,%2,%3}, {%4,%5,%6,%7}, {%8,%9}, {%0,%1,%2,%3};"
                 : "+f"(c[0]), "+f"(c[1]), "+f"(c[2]), "+f"(c[3])
                 : "r"(a[0]), "r"(a[1]), "r"(a[2]), "r"(a[3]), "r"(b0), "r"(b1));
}

__device__ __forceinline__ uint32_t desc_lo(uint32_t saddr) { return ((saddr & 0x3FFFF) >> 4) | (1u << 16); }
#define DESC_HI "0x40000040"
__device__ __forceinline__ void wg_fence() { asm volatile("wgmma.fence.sync.aligned;" ::: "memory"); }
__device__ __forceinline__ void wg_commit() { asm volatile("wgmma.commit_group.sync.aligned;" ::: "memory"); }
__device__ __forceinline__ void wg_wait0() { asm volatile("wgmma.wait_group.sync.aligned 0;" ::: "memory"); }
__device__ __forceinline__ void wg_wait1() { asm volatile("wgmma.wait_group.sync.aligned 1;" ::: "memory"); }

__device__ __forceinline__ void wgmma_n64_first(float (&d)[8], float (&e)[24], const uint32_t (&a)[4], uint32_t bdesc) {
    asm volatile("{\n.reg .b64 b;\nmov.b64 b, {%36, " DESC_HI "};\n"
                 "wgmma.mma_async.sync.aligned.m64n64k16.f32.bf16.bf16 {%0,%1,%2,%3,%4,%5,%6,%7,%8,%9,%10,%11,%12,%13,%14,%15,%16,%17,%18,%19,%20,%21,%22,%23,%24,%25,%26,%27,%28,%29,%30,%31}, {%32,%33,%34,%35}, b, 0, 1, 1, 1;\n}"
                 : "=f"(d[0]), "=f"(d[1]), "=f"(d[2]), "=f"(d[3]), "=f"(d[4]), "=f"(d[5]), "=f"(d[6]), "=f"(d[7]),
                   "=f"(e[0]), "=f"(e[1]), "=f"(e[2]), "=f"(e[3]), "=f"(e[4]), "=f"(e[5]), "=f"(e[6]), "=f"(e[7]), "=f"(e[8]), "=f"(e[9]), "=f"(e[10]), "=f"(e[11]), "=f"(e[12]), "=f"(e[13]), "=f"(e[14]), "=f"(e[15]), "=f"(e[16]), "=f"(e[17]), "=f"(e[18]), "=f"(e[19]), "=f"(e[20]), "=f"(e[21]), "=f"(e[22]), "=f"(e[23])
                 : "r"(a[0]), "r"(a[1]), "r"(a[2]), "r"(a[3]), "r"(bdesc));
}
__device__ __forceinline__ void wgmma_n64(float (&d)[8], float (&e)[24], const uint32_t (&a)[4], uint32_t bdesc) {
    asm volatile("{\n.reg .b64 b;\nmov.b64 b, {%36, " DESC_HI "};\n"
                 "wgmma.mma_async.sync.aligned.m64n64k16.f32.bf16.bf16 {%0,%1,%2,%3,%4,%5,%6,%7,%8,%9,%10,%11,%12,%13,%14,%15,%16,%17,%18,%19,%20,%21,%22,%23,%24,%25,%26,%27,%28,%29,%30,%31}, {%32,%33,%34,%35}, b, 1, 1, 1, 1;\n}"
                 : "+f"(d[0]), "+f"(d[1]), "+f"(d[2]), "+f"(d[3]), "+f"(d[4]), "+f"(d[5]), "+f"(d[6]), "+f"(d[7]),
                   "+f"(e[0]), "+f"(e[1]), "+f"(e[2]), "+f"(e[3]), "+f"(e[4]), "+f"(e[5]), "+f"(e[6]), "+f"(e[7]), "+f"(e[8]), "+f"(e[9]), "+f"(e[10]), "+f"(e[11]), "+f"(e[12]), "+f"(e[13]), "+f"(e[14]), "+f"(e[15]), "+f"(e[16]), "+f"(e[17]), "+f"(e[18]), "+f"(e[19]), "+f"(e[20]), "+f"(e[21]), "+f"(e[22]), "+f"(e[23])
                 : "r"(a[0]), "r"(a[1]), "r"(a[2]), "r"(a[3]), "r"(bdesc));
}
__device__ __forceinline__ void wgmma_n48_first(float (&e)[24], const uint32_t (&a)[4], uint32_t bdesc) {
    asm volatile("{\n.reg .b64 b;\nmov.b64 b, {%28, " DESC_HI "};\n"
                 "wgmma.mma_async.sync.aligned.m64n48k16.f32.bf16.bf16 {%0,%1,%2,%3,%4,%5,%6,%7,%8,%9,%10,%11,%12,%13,%14,%15,%16,%17,%18,%19,%20,%21,%22,%23}, {%24,%25,%26,%27}, b, 0, 1, 1, 1;\n}"
                 : "=f"(e[0]), "=f"(e[1]), "=f"(e[2]), "=f"(e[3]), "=f"(e[4]), "=f"(e[5]), "=f"(e[6]), "=f"(e[7]), "=f"(e[8]), "=f"(e[9]), "=f"(e[10]), "=f"(e[11]), "=f"(e[12]), "=f"(e[13]), "=f"(e[14]), "=f"(e[15]), "=f"(e[16]), "=f"(e[17]), "=f"(e[18]), "=f"(e[19]), "=f"(e[20]), "=f"(e[21]), "=f"(e[22]), "=f"(e[23])
                 : "r"(a[0]), "r"(a[1]), "r"(a[2]), "r"(a[3]), "r"(bdesc));
}
__device__ __forceinline__ void wgmma_n48(float (&e)[24], const uint32_t (&a)[4], uint32_t bdesc) {
    asm volatile("{\n.reg .b64 b;\nmov.b64 b, {%28, " DESC_HI "};\n"
                 "wgmma.mma_async.sync.aligned.m64n48k16.f32.bf16.bf16 {%0,%1,%2,%3,%4,%5,%6,%7,%8,%9,%10,%11,%12,%13,%14,%15,%16,%17,%18,%19,%20,%21,%22,%23}, {%24,%25,%26,%27}, b, 1, 1, 1, 1;\n}"
                 : "+f"(e[0]), "+f"(e[1]), "+f"(e[2]), "+f"(e[3]), "+f"(e[4]), "+f"(e[5]), "+f"(e[6]), "+f"(e[7]), "+f"(e[8]), "+f"(e[9]), "+f"(e[10]), "+f"(e[11]), "+f"(e[12]), "+f"(e[13]), "+f"(e[14]), "+f"(e[15]), "+f"(e[16]), "+f"(e[17]), "+f"(e[18]), "+f"(e[19]), "+f"(e[20]), "+f"(e[21]), "+f"(e[22]), "+f"(e[23])
                 : "r"(a[0]), "r"(a[1]), "r"(a[2]), "r"(a[3]), "r"(bdesc));
}
__device__ __forceinline__ void wgmma_n16_first(float (&d)[8], const uint32_t (&a)[4], uint32_t bdesc) {
    asm volatile("{\n.reg .b64 b;\nmov.b64 b, {%12, " DESC_HI "};\n"
                 "wgmma.mma_async.sync.aligned.m64n16k16.f32.bf16.bf16 {%0,%1,%2,%3,%4,%5,%6,%7}, {%8,%9,%10,%11}, b, 0, 1, 1, 1;\n}"
                 : "=f"(d[0]), "=f"(d[1]), "=f"(d[2]), "=f"(d[3]), "=f"(d[4]), "=f"(d[5]), "=f"(d[6]), "=f"(d[7])
                 : "r"(a[0]), "r"(a[1]), "r"(a[2]), "r"(a[3]), "r"(bdesc));
}
__device__ __forceinline__ void wgmma_n16(float (&d)[8], const uint32_t (&a)[4], uint32_t bdesc) {
    asm volatile("{\n.reg .b64 b;\nmov.b64 b, {%12, " DESC_HI "};\n"
                 "wgmma.mma_async.sync.aligned.m64n16k16.f32.bf16.bf16 {%0,%1,%2,%3,%4,%5,%6,%7}, {%8,%9,%10,%11}, b, 1, 1, 1, 1;\n}"
                 : "+f"(d[0]), "+f"(d[1]), "+f"(d[2]), "+f"(d[3]), "+f"(d[4]), "+f"(d[5]), "+f"(d[6]), "+f"(d[7])
                 : "r"(a[0]), "r"(a[1]), "r"(a[2]), "r"(a[3]), "r"(bdesc));
}

__device__ __forceinline__ void wgmma_n64_p(float (&d)[8], float (&e)[24], const uint32_t (&a)[4], uint32_t bdesc, int acc) {
    asm volatile("{\n.reg .pred p;\n.reg .b64 b;\nsetp.ne.b32 p, %37, 0;\nmov.b64 b, {%36, " DESC_HI "};\n"
                 "wgmma.mma_async.sync.aligned.m64n64k16.f32.bf16.bf16 {%0,%1,%2,%3,%4,%5,%6,%7,%8,%9,%10,%11,%12,%13,%14,%15,%16,%17,%18,%19,%20,%21,%22,%23,%24,%25,%26,%27,%28,%29,%30,%31}, {%32,%33,%34,%35}, b, p, 1, 1, 1;\n}"
                 : "+f"(d[0]), "+f"(d[1]), "+f"(d[2]), "+f"(d[3]), "+f"(d[4]), "+f"(d[5]), "+f"(d[6]), "+f"(d[7]),
                   "+f"(e[0]), "+f"(e[1]), "+f"(e[2]), "+f"(e[3]), "+f"(e[4]), "+f"(e[5]), "+f"(e[6]), "+f"(e[7]), "+f"(e[8]), "+f"(e[9]), "+f"(e[10]), "+f"(e[11]), "+f"(e[12]), "+f"(e[13]), "+f"(e[14]), "+f"(e[15]), "+f"(e[16]), "+f"(e[17]), "+f"(e[18]), "+f"(e[19]), "+f"(e[20]), "+f"(e[21]), "+f"(e[22]), "+f"(e[23])
                 : "r"(a[0]), "r"(a[1]), "r"(a[2]), "r"(a[3]), "r"(bdesc), "r"(acc));
}
__device__ __forceinline__ void wgmma_n16_p(float (&d)[8], const uint32_t (&a)[4], uint32_t bdesc, int acc) {
    asm volatile("{\n.reg .pred p;\n.reg .b64 b;\nsetp.ne.b32 p, %13, 0;\nmov.b64 b, {%12, " DESC_HI "};\n"
                 "wgmma.mma_async.sync.aligned.m64n16k16.f32.bf16.bf16 {%0,%1,%2,%3,%4,%5,%6,%7}, {%8,%9,%10,%11}, b, p, 1, 1, 1;\n}"
                 : "+f"(d[0]), "+f"(d[1]), "+f"(d[2]), "+f"(d[3]), "+f"(d[4]), "+f"(d[5]), "+f"(d[6]), "+f"(d[7])
                 : "r"(a[0]), "r"(a[1]), "r"(a[2]), "r"(a[3]), "r"(bdesc), "r"(acc));
}

__device__ __forceinline__ uint32_t edge_dist(uint32_t sxy, uint32_t sz, uint32_t dxy, uint32_t dz, uint32_t& rxy, uint32_t& rz) {
    rxy = hsub2(sxy, dxy);
    rz  = hsub2(sz, dz);
    uint32_t qxy = hmul2(rxy, rxy), qz = hmul2(rz, rz);
    float ss = rbf((bf_lo(qxy) + bf_hi(qxy)) + bf_lo(qz));
    float s2 = rbf(ss + 1e-8f);
    float d;
    asm("sqrt.approx.ftz.f32 %0, %1;" : "=f"(d) : "f"(s2));
    return pack_bf(d, 0.f) & 0xffffu;
}

__device__ __forceinline__ void load_pos(uint32_t sm_pos, int i, uint32_t& xy, uint32_t& z) {
    uint32_t a  = (sm_pos + 6u * (uint32_t)i) & ~3u;
    uint32_t w0 = lds32(a), w1 = lds32(a + 4);
    uint32_t sh = (uint32_t)i << 4;
    xy = __funnelshift_r(w0, w1, sh);
    z  = __funnelshift_r(w1, w1, sh);
}

__device__ __noinline__ float radial_value(float d, float f) {
    float arg = rbf(d * f);
    float sn  = rbf(sinf(arg));
    float rb  = rbf(__fdiv_rn(sn, d));
    float c   = rbf(cosf(rbf(__fdiv_rn(rbf(d * 3.14159265358979323846f), 5.0f))));
    float fc  = rbf(0.5f * rbf(c + 1.0f));
    return rb * fc;
}

__global__ void __launch_bounds__(NT, 1)
painn_kernel(const Params p, const __grid_constant__ CUtensorMap tmF, const __grid_constant__ CUtensorMap tmSV,
             const __grid_constant__ CUtensorMap tmW1, const __grid_constant__ CUtensorMap tmW2) {
    extern __shared__ __align__(1024) uint8_t smem[];
    const uint32_t sb   = smem_u32(smem);
    const int tid  = threadIdx.x, lane = tid & 31, warp = __shfl_sync(0xffffffffu, tid >> 5, 0);
    const int cta  = blockIdx.x;
    const int g    = lane >> 2, t = lane & 3;
    int* binCnt = (int*)(smem + SM_BINCNT);
    int* binOff = (int*)(smem + SM_BINOFF);
    int* nCnt   = (int*)(smem + SM_NCNT);
    uint32_t* nInfo = (uint32_t*)(smem + SM_NINFO);
    volatile int* ctrl = (volatile int*)(smem + SM_CTRL);
    const uint32_t bar_pos = sb + SM_BARS, bar_mlp = bar_pos + 8, bar_rec = bar_pos + 16;
    const uint32_t bar_full = bar_pos + 32, bar_empty = bar_full + NCWG * MAX_STAGE * 8;

    const int node0  = cta * p.npc;
    const int nnodes = max(0, min(p.npc, p.N - node0));

    STAMP(0);
    if (tid == 0) {
        mbar_init(bar_pos, 1);
        asm volatile("fence.mbarrier_init.release.cluster;" ::: "memory");
        uint32_t pos_bytes = (uint32_t)(p.N * 6 + 15) & ~15u;
        mbar_expect_tx(bar_pos, pos_bytes);
        bulk_g2s(sb + P1_POS, p.pos, pos_bytes, bar_pos);
    } else if (tid == 32) {
        mbar_init(bar_mlp, 1);
        asm volatile("fence.mbarrier_init.release.cluster;" ::: "memory");
        mbar_expect_tx(bar_mlp, 2u * 160u * 128u + 8192u + 24576u);
        tma_load(sb + P1_W1, &tmW1, 0, bar_mlp);
        tma_load(sb + P1_SV, &tmSV, node0 * 4, bar_mlp);
        tma_load(sb + P1_W2, &tmW2, 0, bar_mlp);
        tma_load(sb + P1_SV + 160 * 128, &tmSV, node0 * 4 + 160, bar_mlp);
    } else if (tid == 64) {
        mbar_init(bar_rec, 1);
        asm volatile("prefetch.tensormap [%0];" ::"l"(&tmF) : "memory");
    } else if (tid >= 96 && tid < 96 + NCWG * MAX_STAGE) {
        mbar_init(bar_full + 8 * (tid - 96), 1);
        mbar_init(bar_empty + 8 * (tid - 96), 4);
    }
    unsigned bar_seen = 0;
    if (tid == 15 * 32 || tid == 14 * 32)
        asm volatile("ld.relaxed.gpu.global.u32 %0, [%1];" : "=r"(bar_seen) : "l"(&g_bar[tid == 15 * 32 ? 0 : 1]) : "memory");
    const bool mlp_warp = warp >= 6;
    int4 s4[3], d4[3];
    const int q0 = cta * p.quads_per_cta;
    const int qend = min(q0 + p.quads_per_cta, p.E >> 2);
#pragma unroll
    for (int k = 0; k < 3; k++) {
        const int q = q0 + (k < 2 ? warp + 16 * k : 32 + warp) * 32 + lane;
        const bool ok = q < qend && (k < 2 || !mlp_warp);
        s4[k] = ok ? __ldg((const int4*)p.src + q) : make_int4(-1, -1, -1, -1);
        d4[k] = ok ? __ldg((const int4*)p.dst + q) : make_int4(0, 0, 0, 0);
    }
    if (tid < MAX_CTA) binCnt[tid] = 0;
    if (tid < MAX_NPC) nCnt[tid] = 0;
    if (tid < 16) ctrl[tid] = 0;
    if (tid >= 416 && tid < 416 + 48) {
        asm volatile("prefetch.global.L2 [%0];" ::"l"((const uint8_t*)p.wr + (tid - 416) * 128));
    }
    for (int i = P1_STAGE / 16 + tid; i < P1_SV / 16; i += NT) sts128(sb + i * 16, make_uint4(0u, 0u, 0u, 0u));
    __syncthreads();

    if (!mlp_warp) {
        const int rows_per = (TAB_ROWS + 1 + p.ncta - 1) / p.ncta;
        for (int i = tid; i < rows_per * 8; i += 6 * 32) {
            int row = cta * rows_per + (i >> 3), kp = i & 7;
            if (row <= TAB_ROWS) {
                uint32_t val = 0;
                if (row < TAB_ROWS) {
                    float d = __uint_as_float((D_MIN_BITS + row) << 16);
                    uint32_t f2 = __ldg((const uint32_t*)p.freqs + kp);
                    val = pack_bf(radial_value(d, bf_lo(f2)), radial_value(d, bf_hi(f2)));
                }
                ((uint32_t*)g_table)[row * 8 + kp] = val;
            }
        }
    } else {
        const int mt = (warp - 6) >> 1, hf = (warp - 6) & 1;
        if (mt * 16 < nnodes) {
            mbar_wait(bar_mlp, 0);
            STAMPT(10, 6 * 32);
            const int lrow = lane & 15, lch = lane >> 4;
            const uint32_t rowb = sb + P1_SV + (mt * 16 + lrow) * 512;
            const uint32_t key0 = (4 * lrow) & 7;
            float acc[4][4];
#pragma unroll
            for (int i = 0; i < 4; i++) { acc[i][0] = acc[i][1] = acc[i][2] = acc[i][3] = 0.f; }
#pragma unroll
            for (int ks = 0; ks < 4; ks++) {
                uint32_t a[4];
                ldsm4(a, rowb + (((2 * ks + lch) ^ key0) << 4));
                const int kk = 16 * ks + lrow;
#pragma unroll
                for (int nt = 0; nt < 4; nt += 2) {
                    uint32_t b[4];
                    ldsm4t(b, sb + P1_W1 + kk * 128 + (((4 * hf + nt + lch) ^ (kk & 7)) << 4));
                    mma16816(acc[nt], a, b[0], b[1]);
                    mma16816(acc[nt + 1], a, b[2], b[3]);
                }
            }
            uint32_t hp[4][2];
#pragma unroll
            for (int i = 0; i < 4; i++) {
                float h[4];
#pragma unroll
                for (int q = 0; q < 4; q++) {
                    float x = rbf(acc[i][q]);
                    h[q] = __fdividef(x, 1.0f + __expf(-x));
                    acc[i][q] = 0.f;
                }
                hp[i][0] = pack_bf(h[0], h[1]);
                hp[i][1] = pack_bf(h[2], h[3]);
            }
            asm volatile("bar.sync %0, 64;" ::"r"(4 + mt) : "memory");
#pragma unroll
            for (int i = 0; i < 4; i += 2)
                stsm4(rowb + (((4 * hf + i + lch) ^ key0) << 4), hp[i][0], hp[i][1], hp[i + 1][0], hp[i + 1][1]);
            asm volatile("bar.sync %0, 64;" ::"r"(4 + mt) : "memory");
#pragma unroll
            for (int ks = 0; ks < 4; ks++) {
                uint32_t a[4];
                ldsm4(a, rowb + (((2 * ks + lch) ^ key0) << 4));
                const int line = 3 * (16 * ks + lrow) + 1;
#pragma unroll
                for (int nt = 0; nt < 4; nt += 2) {
                    uint32_t b[4];
                    ldsm4t(b, sb + P1_W2 + line * 128 + (((4 * hf + nt + lch) ^ (line & 7)) << 4));
                    mma16816(acc[nt], a, b[0], b[1]);
                    mma16816(acc[nt + 1], a, b[2], b[3]);
                }
            }
            uint32_t vq[2][3][4];
#pragma unroll
            for (int rh = 0; rh < 2; rh++) {
#pragma unroll
                for (int a = 0; a < 3; a++) {
                    const int line = 4 * (mt * 16 + g + 8 * rh) + 1 + a;
#pragma unroll
                    for (int i = 0; i < 4; i++) vq[rh][a][i] = lds32(sb + P1_SV + line * 128 + 4 * t + (((4 * hf + i) ^ (line & 7)) << 4));
                }
            }
#pragma unroll
            for (int rh = 0; rh < 2; rh++) {
#pragma unroll
                for (int a = 0; a < 3; a++) {
                    const int line = 4 * (mt * 16 + g + 8 * rh) + 1 + a;
#pragma unroll
                    for (int i = 0; i < 4; i++)
                        sts32(sb + P1_SV + line * 128 + 4 * t + (((4 * hf + i) ^ (line & 7)) << 4),
                              hmul2(pack_bf(acc[i][2 * rh], acc[i][2 * rh + 1]), vq[rh][a][i]));
                }
            }
            fence_async_smem();
            asm volatile("bar.sync %0, 64;" ::"r"(4 + mt) : "memory");
            if (lane < 8 && mt * 16 + 8 * hf + lane < nnodes)
                tma_store(&tmF, (node0 + mt * 16 + 8 * hf + lane) * 4, sb + P1_SV + (mt * 16 + 8 * hf + lane) * 512);
            asm volatile("cp.async.bulk.commit_group;" ::: "memory");
        }
        STAMPT(11, 6 * 32);
    }
    mbar_wait(bar_pos, 0);
    STAMP(1);

    uint32_t r0[12], r1[12], r2[12], rk[12];
#pragma unroll
    for (int k = 0; k < 3; k++) {
        const int ss[4] = {s4[k].x, s4[k].y, s4[k].z, s4[k].w};
        const int dd[4] = {d4[k].x, d4[k].y, d4[k].z, d4[k].w};
#pragma unroll
        for (int j = 0; j < 4; j++) rk[k * 4 + j] = 0xffffffffu;
        if (ss[0] >= 0) {
#pragma unroll
            for (int j = 0; j < 4; j++) {
                const int e = k * 4 + j;
                const int s = ss[j], d = dd[j];
                uint32_t sxy, sz, dxy, dz, rxy, rz;
                load_pos(sb + P1_POS, s, sxy, sz);
                load_pos(sb + P1_POS, d, dxy, dz);
                uint32_t db = edge_dist(sxy, sz, dxy, dz, rxy, rz);
                float inv;
                asm("rcp.approx.ftz.f32 %0, %1;" : "=f"(inv) : "f"(__uint_as_float(db << 16)));
                uint32_t bin = __umulhi((uint32_t)d, p.npc_magic);
                uint32_t dl  = (uint32_t)d - bin * (uint32_t)p.npc;
                r0[e] = (uint32_t)s | ((db - D_MIN_BITS) << 16);
                r1[e] = pack_bf(bf_lo(rxy) * inv, bf_hi(rxy) * inv);
                r2[e] = __byte_perm(pack_bf(bf_lo(rz) * inv, 0.f), dl, 0x5410);
                if (db <= D_MAX_BITS) rk[e] = (uint32_t)atomicAdd(&binCnt[bin], 1) | (bin << 16);
            }
        }
    }
    STAMP(2);
    STAMPT(12, 6 * 32);
    __syncthreads();
    STAMP(3);
    if (warp == 0) {
        int c[5], s = 0;
#pragma unroll
        for (int i = 0; i < 5; i++) { int b = lane * 5 + i; c[i] = b < p.ncta ? binCnt[b] : 0; s += c[i]; }
        int x = s;
#pragma unroll
        for (int o = 1; o < 32; o <<= 1) { int y = __shfl_up_sync(0xffffffffu, x, o); if (lane >= o) x += y; }
        int off = x - s;
#pragma unroll
        for (int i = 0; i < 5; i++) {
            int b = lane * 5 + i;
            if (b < p.ncta) { binOff[b] = off; g_offs[cta * MAX_CTA + b] = (uint32_t)off | ((uint32_t)c[i] << 16); }
            off += c[i];
        }
        if (lane == 31) ctrl[8] = x;
    }
    __syncthreads();
#pragma unroll
    for (int e = 0; e < 12; e++)
        if (rk[e] != 0xffffffffu) rk[e] = (rk[e] & 0xffffu) + lds32(sb + SM_BINOFF + (rk[e] >> 16) * 4);
#pragma unroll
    for (int e = 0; e < 12; e++)
        if (rk[e] != 0xffffffffu) sts128(sb + P1_STAGE + rk[e] * 16, make_uint4(r0[e], r1[e], r2[e], 0u));
    fence_async_smem();
    __syncthreads();
    if (tid == 0) {
        const uint32_t bytes = (uint32_t)ctrl[8] * 16u;
        if (bytes) asm volatile("cp.async.bulk.global.shared::cta.bulk_group [%0], [%1], %2;"
                                ::"l"(g_rec + (size_t)cta * REC_CAP), "r"(sb + P1_STAGE), "r"(bytes) : "memory");
        asm volatile("cp.async.bulk.commit_group;" ::: "memory");
    }
    if (tid == 32) asm volatile("red.add.release.gpu.global.u32 [%0], 1;" ::"l"(&g_bar[0]) : "memory");
    if (tid == 0 || (mlp_warp && lane < 8)) {
        asm volatile("cp.async.bulk.wait_group 0;" ::: "memory");
        asm volatile("fence.proxy.async;" ::: "memory");
    }

    __syncthreads();
    STAMP(4);
    if (tid == 0) asm volatile("red.add.release.gpu.global.u32 [%0], 1;" ::"l"(&g_bar[1]) : "memory");
    uint32_t wp[3][4];
    if (warp >= 4 && warp < 8) {
        const uint16_t* w2 = (const uint16_t*)p.w2 + 16 * (warp & 3) + g;
#pragma unroll 2
        for (int mk = 0; mk < 8; mk++) {
            uint32_t f[4];
#pragma unroll
            for (int i = 0; i < 4; i++) {
                const uint16_t* q = w2 + (16 * (mk & 3) + 2 * t + 8 * (i >> 1)) * 192 + (mk >> 2) * 128 + 8 * (i & 1);
                f[i] = (uint32_t)__ldg(q) | ((uint32_t)__ldg(q + 192) << 16);
            }
            sts128(sb + SM_HT + (mk * 128 + (tid & 127)) * 16, make_uint4(f[0], f[1], f[2], f[3]));
        }
    }
    if (warp < 4 * NCWG) {
        const uint16_t* wr = (const uint16_t*)p.wr + 16 * (warp & 3) + g;
#pragma unroll
        for (int ty = 0; ty < 3; ty++) {
#pragma unroll
            for (int i = 0; i < 4; i++) {
                const uint16_t* q = wr + (8 * (i >> 1) + 2 * t) * 192 + ty * 64 + 8 * (i & 1);
                wp[ty][i] = (uint32_t)__ldg(q) | ((uint32_t)__ldg(q + 192) << 16);
            }
        }
    }
    if (warp == 15) {
        if (lane == 0) {
            const unsigned target = (bar_seen / (unsigned)p.ncta + 1u) * (unsigned)p.ncta;
            unsigned cur;
            int spins = 0;
            do {
                asm volatile("ld.acquire.gpu.global.u32 %0, [%1];" : "=r"(cur) : "l"(&g_bar[0]) : "memory");
            } while ((int)(cur - target) < 0 && ++spins < (1 << 24));
        }
        __syncwarp();
        uint32_t v[5];
        int s = 0;
#pragma unroll
        for (int i = 0; i < 5; i++) {
            int b = lane * 5 + i;
            v[i] = b < p.ncta ? __ldcg(&g_offs[b * MAX_CTA + cta]) : 0u;
        }
#pragma unroll
        for (int i = 0; i < 5; i++) s += (int)(v[i] >> 16);
        int x = s;
#pragma unroll
        for (int o = 1; o < 32; o <<= 1) { int y = __shfl_up_sync(0xffffffffu, x, o); if (lane >= o) x += y; }
        const int tot = __shfl_sync(0xffffffffu, x, 31);
        int off = x - s;
#pragma unroll
        for (int i = 0; i < 5; i++) {
            int b = lane * 5 + i;
            if (b < p.ncta) { binCnt[b] = (int)v[i]; binOff[b] = off; }
            off += (int)(v[i] >> 16);
        }
        if (lane == 0) {
            ctrl[8] = tot;
            if (tot > STAGE_CAP) ctrl[1] = 1;
            mbar_expect_tx(bar_rec, tot > STAGE_CAP ? 0u : (uint32_t)tot * 16u);
        }
    }
    if (tid == 14 * 32) {
        const unsigned target = (bar_seen / (unsigned)p.ncta + 1u) * (unsigned)p.ncta;
        unsigned cur;
        int spins = 0;
        do {
            asm volatile("ld.acquire.gpu.global.u32 %0, [%1];" : "=r"(cur) : "l"(&g_bar[1]) : "memory");
        } while ((int)(cur - target) < 0 && ++spins < (1 << 24));
    }
    __syncthreads();
    STAMP(5);

    const int total = ctrl[8];
    if (ctrl[1] == 0) {
        const int b = (lane << 4) | warp;
        if (lane < 9 && b < p.ncta) {
            const uint32_t v = (uint32_t)binCnt[b], c = v >> 16;
            if (c) {
                asm volatile("fence.proxy.async;" ::: "memory");
                bulk_g2s(sb + SM_STAGE2 + (uint32_t)binOff[b] * 16u, g_rec + (size_t)b * REC_CAP + (v & 0xffffu), c * 16u, bar_rec);
            }
        }
    }
    mbar_wait(bar_rec, 0);
    STAMP(13);
    constexpr int RPT = 8;
    uint4 rec[RPT];
    const bool okc = ctrl[1] == 0;
#pragma unroll
    for (int k = 0; k < RPT; k++) {
        const int i = tid + k * NT;
        if (okc && i < total) rec[k] = lds128(sb + SM_STAGE2 + i * 16);
    }
#pragma unroll
    for (int k = 0; k < RPT; k++) {
        const int i = tid + k * NT;
        if (okc && i < total) rec[k].w = (uint32_t)atomicAdd(&nCnt[rec[k].z >> 16], 1);
    }
    if (okc) {
        for (int i = tid + RPT * NT; i < total; i += NT) {
            uint32_t dl = lds32(sb + SM_STAGE2 + i * 16 + 8) >> 16;
            sts32(sb + SM_STAGE2 + i * 16 + 12, (uint32_t)atomicAdd(&nCnt[dl], 1));
        }
    }
    __syncthreads();
    if (warp == 0) {
        int c[3], s = 0;
#pragma unroll
        for (int i = 0; i < 3; i++) {
            int b = lane * 3 + i;
            c[i] = b < nnodes ? max(16, (nCnt[b] + 15) & ~15) : 0;
            s += c[i];
        }
        int x = s;
#pragma unroll
        for (int o = 1; o < 32; o <<= 1) { int y = __shfl_up_sync(0xffffffffu, x, o); if (lane >= o) x += y; }
        const int slots = __shfl_sync(0xffffffffu, x, 31);
        int off = x - s, below1 = 0, below2 = 0;
#pragma unroll
        for (int i = 0; i < 3; i++) {
            int b = lane * 3 + i;
            if (b < nnodes) {
                nInfo[b] = (uint32_t)off | ((uint32_t)c[i] << 16);
                const int centre3 = 3 * (2 * off + c[i]);
                below1 += centre3 < 2 * slots;
                below2 += centre3 < 4 * slots;
            }
            off += c[i];
        }
        below1 = __reduce_add_sync(0xffffffffu, below1);
        below2 = __reduce_add_sync(0xffffffffu, below2);
        if (lane == 0) {
            ctrl[2] = below1;
            ctrl[3] = below2;
            ctrl[4] = slots;
            if (slots > SLOT_CAP) ctrl[1] = 1;
        }
    }
    __syncthreads();
    if (ctrl[1] == 0) {
        uint16_t* sid = (uint16_t*)(smem + SM_SID);
        uint2* meta = (uint2*)(smem + SM_META);
#pragma unroll
        for (int k = 0; k < RPT; k++)
            if (tid + k * NT < total) rec[k].w += lds32(sb + SM_NINFO + (rec[k].z >> 16) * 4) & 0xffffu;
#pragma unroll
        for (int k = 0; k < RPT; k++) {
            if (tid + k * NT < total) {
                const uint4 r = rec[k];
                sid[r.w]  = (uint16_t)((r.x & 0xffffu) << 2);
                meta[r.w] = make_uint2(((r.x >> 16) << 5) | (r.z << 16), r.y);
            }
        }
        for (int i = tid + RPT * NT; i < total; i += NT) {
            uint4 r = lds128(sb + SM_STAGE2 + i * 16);
            int pos = (int)(nInfo[r.z >> 16] & 0xffffu) + (int)r.w;
            sid[pos]  = (uint16_t)((r.x & 0xffffu) << 2);
            meta[pos] = make_uint2(((r.x >> 16) << 5) | (r.z << 16), r.y);
        }
        for (int i = tid; i < nnodes * 16; i += NT) {
            int nl = i >> 4, c = nCnt[nl];
            int j = (c & ~15) + (i & 15);
            if (j >= c && (j < 16 || (c & 15))) {
                int pos = (int)(nInfo[nl] & 0xffffu) + j;
                sid[pos]  = 0xffffu;
                meta[pos] = make_uint2((uint32_t)TAB_ZERO << 5, 0u);
            }
        }
    }
    fence_async_smem();
    __syncthreads();
    STAMP(6);

    if (__shfl_sync(0xffffffffu, ctrl[1], 0) != 0) {
        float* acc = (float*)(smem + P1_POS);
        for (int i = tid; i < nnodes * 256; i += NT) acc[i] = 0.f;
        __syncthreads();
        const uint16_t* posu = (const uint16_t*)p.pos;
        const uint32_t* tabg = (const uint32_t*)g_table;
        const uint32_t* Fw = (const uint32_t*)g_F;
        for (int e0 = warp * 32; e0 < p.E; e0 += NT) {
            int e = e0 + lane;
            int s = 0, d = 0;
            uint32_t db = 0xffff, rxy = 0, rz = 0;
            bool act = false;
            if (e < p.E) {
                s = p.src[e]; d = p.dst[e];
                if (d >= node0 && d < node0 + nnodes) {
                    uint32_t sxy = posu[s * 3] | ((uint32_t)posu[s * 3 + 1] << 16), sz = posu[s * 3 + 2];
                    uint32_t dxy = posu[d * 3] | ((uint32_t)posu[d * 3 + 1] << 16), dz = posu[d * 3 + 2];
                    db  = edge_dist(sxy, sz, dxy, dz, rxy, rz);
                    act = db <= D_MAX_BITS;
                }
            }
            unsigned m = __ballot_sync(0xffffffffu, act);
            while (m) {
                int l = __ffs(m) - 1;
                m &= m - 1;
                int es = __shfl_sync(0xffffffffu, s, l), ed = __shfl_sync(0xffffffffu, d, l);
                uint32_t edb = __shfl_sync(0xffffffffu, db, l), exy = __shfl_sync(0xffffffffu, rxy, l), ez = __shfl_sync(0xffffffffu, rz, l);
                float inv = 1.0f / __uint_as_float(edb << 16);
                float rh[3] = {rbf(bf_lo(exy) * inv), rbf(bf_hi(exy) * inv), rbf(bf_lo(ez) * inv)};
                const uint32_t* fr = Fw + (size_t)es * 128 + lane;
                const uint32_t fh = __ldcg(fr);
                const uint32_t q[3] = {__ldcg(fr + 32), __ldcg(fr + 64), __ldcg(fr + 96)};
                float ps0 = 0.f, ps1 = 0.f, pr0 = 0.f, pr1 = 0.f;
                for (int j2 = 0; j2 < 32; j2++) {
                    uint32_t hj = __shfl_sync(0xffffffffu, fh, j2);
                    uint32_t a0 = *(const uint32_t*)(p.w2 + (2 * j2) * 192 + 2 * lane), a1 = *(const uint32_t*)(p.w2 + (2 * j2 + 1) * 192 + 2 * lane);
                    uint32_t b0 = *(const uint32_t*)(p.w2 + (2 * j2) * 192 + 128 + 2 * lane), b1 = *(const uint32_t*)(p.w2 + (2 * j2 + 1) * 192 + 128 + 2 * lane);
                    ps0 += bf_lo(hj) * bf_lo(a0) + bf_hi(hj) * bf_lo(a1);
                    ps1 += bf_lo(hj) * bf_hi(a0) + bf_hi(hj) * bf_hi(a1);
                    pr0 += bf_lo(hj) * bf_lo(b0) + bf_hi(hj) * bf_lo(b1);
                    pr1 += bf_lo(hj) * bf_hi(b0) + bf_hi(hj) * bf_hi(b1);
                }
                float ws0 = 0.f, ws1 = 0.f, wv0 = 0.f, wv1 = 0.f, wr0 = 0.f, wr1 = 0.f;
                for (int k2 = 0; k2 < 8; k2++) {
                    uint32_t rk2 = __ldcg(tabg + (edb - D_MIN_BITS) * 8 + k2);
#pragma unroll
                    for (int h = 0; h < 2; h++) {
                        float rv = h ? bf_hi(rk2) : bf_lo(rk2);
                        const __nv_bfloat16* wrow = p.wr + (2 * k2 + h) * 192 + 2 * lane;
                        uint32_t a = *(const uint32_t*)wrow, b = *(const uint32_t*)(wrow + 64), c = *(const uint32_t*)(wrow + 128);
                        ws0 += rv * bf_lo(a); ws1 += rv * bf_hi(a);
                        wv0 += rv * bf_lo(b); wv1 += rv * bf_hi(b);
                        wr0 += rv * bf_lo(c); wr1 += rv * bf_hi(c);
                    }
                }
                float* a = acc + (ed - node0) * 256 + 2 * lane;
                atomicAdd(a, ps0 * ws0); atomicAdd(a + 1, ps1 * ws1);
#pragma unroll
                for (int c = 0; c < 3; c++) {
                    atomicAdd(a + 64 * (c + 1), wv0 * bf_lo(q[c]) + pr0 * wr0 * rh[c]);
                    atomicAdd(a + 64 * (c + 1) + 1, wv1 * bf_hi(q[c]) + pr1 * wr1 * rh[c]);
                }
            }
        }
        __syncthreads();
        for (int i = tid; i < nnodes * 128; i += NT) {
            uint32_t r = *(const uint32_t*)(p.sv + (size_t)node0 * 256 + 2 * i);
            *(uint32_t*)(p.out + (size_t)node0 * 256 + 2 * i) = pack_bf(bf_lo(r) + acc[2 * i], bf_hi(r) + acc[2 * i + 1]);
        }
        return;
    }

    const int slots = __reduce_max_sync(0xffffffffu, ctrl[4]);
    const int nstage = slots <= SLOT_CAP4 ? 4 : 3;
    const uint32_t ring = sb + (nstage == 4 ? SM_RING4 : SM_RING3);
    const int wg = warp >> 2;
    const int sc = wg < NCWG ? wg : warp - 4 * NCWG;
    const int n_begin = __reduce_max_sync(0xffffffffu, sc == 0 ? 0 : (sc <= NCWG ? ctrl[1 + min(sc, 2)] : 0));
    const int n_end   = __reduce_max_sync(0xffffffffu, sc >= NCWG - 1 ? nnodes : ctrl[2 + sc]);
    const int g0 = __reduce_max_sync(0xffffffffu, n_begin < nnodes ? (int)(nInfo[n_begin] & 0xffffu) : slots) >> 4;
    const int g1 = __reduce_max_sync(0xffffffffu, n_end < nnodes ? (int)(nInfo[n_end] & 0xffffu) : slots) >> 4;
    const uint32_t ring_wg = ring + sc * nstage * STAGE_B;
    const uint32_t full_wg = bar_full + sc * MAX_STAGE * 8;
    constexpr uint32_t EMPTY_OFF = NCWG * MAX_STAGE * 8;
    if (wg == NCWG) {
        asm volatile("setmaxnreg.dec.sync.aligned.u32 56;");
        if (sc < NCWG) {
            const int e = lane >> 1, half = lane & 1;
            const uint32_t coef_off = e * 128 + ((half ^ (e & 7)) << 4);
            const int vrot = (e & 3) ^ ((e >> 1) & 3);
            const uint8_t* tab = (const uint8_t*)g_table + half * 16;
            int stage = 0;
            uint32_t phase = 1, st = ring_wg, fb = full_wg;
            uint2 ma, mb;
            uint4 ta, tb;
            auto pre = [&](uint2& m, uint4& tv, int gi) {
                m  = lds64(sb + SM_META + (gi * 16 + e) * 8);
                tv = __ldg((const uint4*)(tab + (m.x & 0xffffu)));
            };
            auto produce = [&](const uint2& m, const uint4& tv, int gi) {
                const uint4 ia = lds128(sb + SM_SID + gi * 32), ib = lds128(sb + SM_SID + gi * 32 + 16);
                const uint32_t id2[8] = {ia.x, ia.y, ia.z, ia.w, ib.x, ib.y, ib.z, ib.w};
                const int nv = __popc(__ballot_sync(0xffffffffu, (m.x & 0xffffu) != (uint32_t)(TAB_ZERO << 5))) >> 1;
                mbar_wait(fb + EMPTY_OFF, phase);
                uint32_t leader;
                asm volatile("{\n.reg .pred p;\nelect.sync _|p, 0xffffffff;\nselp.u32 %0, 1, 0, p;\n}" : "=r"(leader));
                if (leader) {
                    if (nv == 16) {
#pragma unroll
                        for (int i = 0; i < 8; i++) {
                            tma_load(st + 2048 + (2 * i) * 640, &tmF, (int)(id2[i] & 0xffffu), fb);
                            tma_load(st + 2048 + (2 * i + 1) * 640, &tmF, (int)(id2[i] >> 16), fb);
                        }
                    } else {
#pragma unroll
                        for (int q = 0; q < 4; q++) {
                            if (4 * q + 4 <= nv) {
                                tma_load(st + 2048 + (4 * q) * 640, &tmF, (int)(id2[2 * q] & 0xffffu), fb);
                                tma_load(st + 2048 + (4 * q + 1) * 640, &tmF, (int)(id2[2 * q] >> 16), fb);
                                tma_load(st + 2048 + (4 * q + 2) * 640, &tmF, (int)(id2[2 * q + 1] & 0xffffu), fb);
                                tma_load(st + 2048 + (4 * q + 3) * 640, &tmF, (int)(id2[2 * q + 1] >> 16), fb);
                            } else {
                                if (4 * q < nv)     tma_load(st + 2048 + (4 * q) * 640, &tmF, (int)(id2[2 * q] & 0xffffu), fb);
                                if (4 * q + 1 < nv) tma_load(st + 2048 + (4 * q + 1) * 640, &tmF, (int)(id2[2 * q] >> 16), fb);
                                if (4 * q + 2 < nv) tma_load(st + 2048 + (4 * q + 2) * 640, &tmF, (int)(id2[2 * q + 1] & 0xffffu), fb);
                            }
                        }
                    }
                }
                __syncwarp();
                const uint32_t mul[4] = {0x3f803f80u, __byte_perm(m.y, 0, 0x1010), __byte_perm(m.y, 0, 0x3232), __byte_perm(m.x, 0, 0x3232)};
                const uint32_t a = st + coef_off;
#pragma unroll
                for (int j = 0; j < 4; j++) {
                    const int v = j ^ vrot;
                    const uint32_t lo = (v & 1) ? mul[1] : mul[0], hi = (v & 1) ? mul[3] : mul[2];
                    const uint32_t mm = (v & 2) ? hi : lo;
                    sts128(a ^ (v << 5), make_uint4(hmul2(tv.x, mm), hmul2(tv.y, mm), hmul2(tv.z, mm), hmul2(tv.w, mm)));
                }
                fence_async_smem();
                __syncwarp();
                if (lane == 0) mbar_expect_tx(fb, (uint32_t)nv * 512u);
                st += STAGE_B; fb += 8;
                if (++stage == nstage) { stage = 0; phase ^= 1; st = ring_wg; fb = full_wg; }
            };
            int gi = g0;
            if (gi < g1) pre(ma, ta, gi);
            while (gi < g1) {
                if (gi + 1 < g1) pre(mb, tb, gi + 1);
                produce(ma, ta, gi);
                if (++gi >= g1) break;
                if (gi + 1 < g1) pre(ma, ta, gi + 1);
                produce(mb, tb, gi);
                ++gi;
            }
        }
    } else {
        asm volatile("setmaxnreg.inc.sync.aligned.u32 152;");
        const int w = warp & 3;
        uint32_t wA[2][4][4];
#pragma unroll
        for (int mk = 0; mk < 8; mk++) {
            const uint4 q = lds128(sb + SM_HT + (mk * 128 + (tid & 127)) * 16);
            wA[mk >> 2][mk & 3][0] = q.x; wA[mk >> 2][mk & 3][1] = q.y; wA[mk >> 2][mk & 3][2] = q.z; wA[mk >> 2][mk & 3][3] = q.w;
        }
        uint32_t aoff[4];
        {
            const int e = (lane & 7) + 8 * (lane >> 4), ch = 2 * w + ((lane >> 3) & 1);
#pragma unroll
            for (int b = 0; b < 4; b++) aoff[b] = 2048 + e * 640 + b * 128 + ((ch ^ ((5 * e + b) & 7)) << 4);
        }
        const uint32_t ht = sb + SM_HT + wg * 8192;
        const uint32_t dht = desc_lo(ht);
        auto fresh_tid = [&]() -> uint32_t { uint32_t x = tid; asm volatile("" : "+r"(x)); return x; };
        auto out_off = [&]() -> uint32_t {
            const uint32_t x = fresh_tid();
            return (uint32_t)node0 * 512u + (x & 3u) * 128u + ((x >> 5) & 3u) * 32u + ((x >> 2) & 1u) * 16u + ((x >> 3) & 3u) * 4u;
        };

        asm volatile("bar.sync 4, 384;" ::: "memory");

        float ys[8], yv[24], dQ[3][8];
#pragma unroll
        for (int i = 0; i < 24; i++) yv[i] = 0.f;
#pragma unroll
        for (int i = 0; i < 8; i++) { ys[i] = 0.f; dQ[0][i] = 0.f; dQ[1][i] = 0.f; dQ[2][i] = 0.f; }
        int stage = 0;
        uint32_t phase = 0, st = ring_wg, fb = full_wg;
        for (int nl = n_begin; nl < n_end; nl++) {
            const int G = __reduce_max_sync(0xffffffffu, (int)(nInfo[nl] >> 20));
            const uint32_t resid = __ldg((const uint32_t*)((const uint8_t*)p.sv + (out_off() + (uint32_t)nl * 512u)));
            for (int gi = 0; gi < G; gi++) {
                uint32_t A[4][4];
                mbar_wait(fb, phase);
#pragma unroll
                for (int b = 0; b < 4; b++) ldsm4t(A[b], st + aoff[b]);
                const uint32_t bd = desc_lo(st);
                wg_fence();
                wgmma_n64_p(ys, yv, A[0], bd, gi);
                wgmma_n16_p(dQ[0], A[1], bd, gi);
                wgmma_n16_p(dQ[1], A[2], bd, gi);
                wgmma_n16_p(dQ[2], A[3], bd, gi);
                wg_commit();
                const uint32_t eb = fb + EMPTY_OFF;
                st += STAGE_B; fb += 8;
                if (++stage == nstage) { stage = 0; phase ^= 1; st = ring_wg; fb = full_wg; }
                wg_wait0();
                mbar_arrive_elected(eb);
            }
            {
                named_barrier(1 + wg);
                const uint32_t ft = fresh_tid();
                const uint32_t sa = ht + ((ft >> 5) & 3u) * 2048u + (ft & 15u) * 128u + ((((ft >> 4) & 1u) ^ (ft & 7u)) << 4);
                stsm4(sa, pack_bf(ys[0], ys[1]), pack_bf(ys[2], ys[3]), pack_bf(ys[4], ys[5]), pack_bf(ys[6], ys[7]));
#pragma unroll
                for (int i = 0; i < 6; i += 2) {
                    stsm4(sa ^ ((i + 2) << 4),
                          pack_bf(yv[4 * i], yv[4 * i + 1]), pack_bf(yv[4 * i + 2], yv[4 * i + 3]),
                          pack_bf(yv[4 * i + 4], yv[4 * i + 5]), pack_bf(yv[4 * i + 6], yv[4 * i + 7]));
                }
                fence_async_smem();
                named_barrier(1 + wg);
                float zs[8], zv[24];
                wg_fence();
                wgmma_n16_first(zs, wA[0][0], dht);
                wgmma_n48_first(zv, wA[1][0], dht + 2);
#pragma unroll
                for (int ks = 1; ks < 4; ks++) {
                    wgmma_n16(zs, wA[0][ks], dht + ks * 128);
                    wgmma_n48(zv, wA[1][ks], dht + ks * 128 + 2);
                }
                wg_commit();
#pragma unroll
                for (int i = 0; i < 12; i++) asm volatile("" : "+r"(wp[i >> 2][i & 3]));
                float pr[4][2];
#pragma unroll
                for (int a = 0; a < 3; a++) {
                    const float* q = dQ[a];
                    pr[a + 1][0] = bf_lo(wp[1][0]) * q[0] + bf_hi(wp[1][0]) * q[1] + bf_lo(wp[1][2]) * q[4] + bf_hi(wp[1][2]) * q[5];
                    pr[a + 1][1] = bf_lo(wp[1][1]) * q[2] + bf_hi(wp[1][1]) * q[3] + bf_lo(wp[1][3]) * q[6] + bf_hi(wp[1][3]) * q[7];
                }
                wg_wait0();
                pr[0][0] = bf_lo(wp[0][0]) * zs[0] + bf_hi(wp[0][0]) * zs[1] + bf_lo(wp[0][2]) * zs[4] + bf_hi(wp[0][2]) * zs[5];
                pr[0][1] = bf_lo(wp[0][1]) * zs[2] + bf_hi(wp[0][1]) * zs[3] + bf_lo(wp[0][3]) * zs[6] + bf_hi(wp[0][3]) * zs[7];
#pragma unroll
                for (int a = 0; a < 3; a++) {
                    const float* y = zv + 8 * a;
                    pr[a + 1][0] += bf_lo(wp[2][0]) * y[0] + bf_hi(wp[2][0]) * y[1] + bf_lo(wp[2][2]) * y[4] + bf_hi(wp[2][2]) * y[5];
                    pr[a + 1][1] += bf_lo(wp[2][1]) * y[2] + bf_hi(wp[2][1]) * y[3] + bf_lo(wp[2][3]) * y[6] + bf_hi(wp[2][3]) * y[7];
                }
                const bool hi2 = t & 2, hi1 = t & 1, odd = g & 1;
                float ka0 = hi2 ? pr[2][0] : pr[0][0], ka1 = hi2 ? pr[2][1] : pr[0][1];
                float kb0 = hi2 ? pr[3][0] : pr[1][0], kb1 = hi2 ? pr[3][1] : pr[1][1];
                float sa0 = hi2 ? pr[0][0] : pr[2][0], sa1 = hi2 ? pr[0][1] : pr[2][1];
                float sb0 = hi2 ? pr[1][0] : pr[3][0], sb1 = hi2 ? pr[1][1] : pr[3][1];
                ka0 += __shfl_xor_sync(0xffffffffu, sa0, 2); ka1 += __shfl_xor_sync(0xffffffffu, sa1, 2);
                kb0 += __shfl_xor_sync(0xffffffffu, sb0, 2); kb1 += __shfl_xor_sync(0xffffffffu, sb1, 2);
                float k0 = hi1 ? kb0 : ka0, k1 = hi1 ? kb1 : ka1;
                float s0 = hi1 ? ka0 : kb0, s1 = hi1 ? ka1 : kb1;
                k0 += __shfl_xor_sync(0xffffffffu, s0, 1);
                k1 += __shfl_xor_sync(0xffffffffu, s1, 1);
                const float other = __shfl_xor_sync(0xffffffffu, odd ? k0 : k1, 4);
                const float lo = odd ? other : k0, hi = odd ? k1 : other;
                *(uint32_t*)((uint8_t*)p.out + (out_off() + (uint32_t)nl * 512u)) = pack_bf(bf_lo(resid) + lo, bf_hi(resid) + hi);
            }
        }
    }
    STAMP(8);
}

typedef CUresult (*EncodeFn)(CUtensorMap*, CUtensorMapDataType, cuuint32_t, void*, const cuuint64_t*, const cuuint64_t*,
                             const cuuint32_t*, const cuuint32_t*, CUtensorMapInterleave, CUtensorMapSwizzle,
                             CUtensorMapL2promotion, CUtensorMapFloatOOBfill);

void make_map(EncodeFn enc, CUtensorMap* tm, const void* base, uint64_t lines, uint32_t box) {
    cuuint64_t gd[2] = {64, lines};
    cuuint64_t gs[1] = {128};
    cuuint32_t bd[2] = {64, box};
    cuuint32_t es[2] = {1, 1};
    enc(tm, CU_TENSOR_MAP_DATA_TYPE_BFLOAT16, 2, const_cast<void*>(base), gd, gs, bd, es, CU_TENSOR_MAP_INTERLEAVE_NONE,
        CU_TENSOR_MAP_SWIZZLE_128B, CU_TENSOR_MAP_L2_PROMOTION_L2_128B, CU_TENSOR_MAP_FLOAT_OOB_FILL_NONE);
}

}

extern "C" void kernel_launch(void* const* d_in, const int* in_sizes, int n_in, void* d_out, int out_size) {
    (void)n_in; (void)out_size;
    static int n_sm = 0;
    static EncodeFn enc = nullptr;
    static void* f_ptr = nullptr;
    if (n_sm == 0) {
        int dev = 0;
        cudaGetDevice(&dev);
        cudaDeviceGetAttribute(&n_sm, cudaDevAttrMultiProcessorCount, dev);
        cudaFuncSetAttribute(painn_kernel, cudaFuncAttributeMaxDynamicSharedMemorySize, SM_TOTAL);
        void* fn = nullptr;
        cudaDriverEntryPointQueryResult qr;
        cudaGetDriverEntryPoint("cuTensorMapEncodeTiled", &fn, cudaEnableDefault, &qr);
        enc = (EncodeFn)fn;
        cudaGetSymbolAddress(&f_ptr, g_F);
    }
    Params p;
    p.sv    = (const __nv_bfloat16*)d_in[0];
    p.pos   = (const __nv_bfloat16*)d_in[1];
    p.src   = (const int*)d_in[2];
    p.dst   = (const int*)d_in[3];
    p.freqs = (const __nv_bfloat16*)d_in[4];
    p.w1    = (const __nv_bfloat16*)d_in[5];
    p.w2    = (const __nv_bfloat16*)d_in[6];
    p.wr    = (const __nv_bfloat16*)d_in[7];
    p.out   = (__nv_bfloat16*)d_out;
    p.N = in_sizes[1] / 3;
    p.E = in_sizes[2];
    p.ncta = n_sm < MAX_CTA ? n_sm : MAX_CTA;
    p.npc = (p.N + p.ncta - 1) / p.ncta;
    p.npc_magic = (uint32_t)(0x100000000ull / (uint32_t)p.npc) + 1u;
    p.quads_per_cta = ((p.E >> 2) + p.ncta - 1) / p.ncta;
    if (!enc || p.N > MAX_N || p.npc > MAX_NPC || (p.E & 3) || p.quads_per_cta > MAX_ROUNDS * 32) return;

    CUtensorMap tmF, tmSV, tmW1, tmW2;
    make_map(enc, &tmF, f_ptr, (uint64_t)p.N * 4, 4);
    make_map(enc, &tmSV, p.sv, (uint64_t)p.N * 4, 160);
    make_map(enc, &tmW1, p.w1, 64, 64);
    make_map(enc, &tmW2, p.w2, 192, 192);

    cudaLaunchConfig_t cfg = {};
    cfg.gridDim = dim3(p.ncta);
    cfg.blockDim = dim3(NT);
    cfg.dynamicSmemBytes = SM_TOTAL;
    cfg.stream = cudaStreamPerThread;
    cudaLaunchAttribute attr[1];
    attr[0].id = cudaLaunchAttributeCooperative;
    attr[0].val.cooperative = 1;
    cfg.attrs = attr;
    cfg.numAttrs = 1;
    cudaLaunchKernelEx(&cfg, painn_kernel, p, tmF, tmSV, tmW1, tmW2);
}
```

```cpp
#include <cuda_runtime.h>
#include <cuda.h>
#include <cuda_bf16.h>
#include <stdint.h>

namespace {

constexpr int NT        = 512;
constexpr int NCWG      = 2;
constexpr int MAX_N     = 10240;
constexpr int MAX_CTA   = 144;
constexpr int MAX_NPC   = 80;
constexpr int MAX_ROUNDS = 38;
constexpr int REC_CAP   = MAX_ROUNDS * 128;
constexpr int SLOT_CAP  = 6144;
constexpr int MAX_STAGE = 6;
constexpr int STAGE_B   = 12288;

constexpr uint32_t D_MIN_BITS = 0x38D2;
constexpr uint32_t D_MAX_BITS = 0x409C;
constexpr int TAB_ROWS  = (int)(D_MAX_BITS - D_MIN_BITS) + 1;
constexpr int TAB_ZERO  = TAB_ROWS;
constexpr int TAB_BYTES = (TAB_ROWS + 1) * 32;

constexpr int SM_BINCNT = 0;
constexpr int SM_BINOFF = SM_BINCNT + MAX_CTA * 4;
constexpr int SM_NCNT   = SM_BINOFF + MAX_CTA * 4;
constexpr int SM_NINFO  = SM_NCNT + MAX_NPC * 4;
constexpr int SM_CTRL   = SM_NINFO + MAX_NPC * 4;
constexpr int SM_BARS   = SM_CTRL + 64;
constexpr int SM_SID    = 2048 + 128;
constexpr int SM_META   = SM_SID + SLOT_CAP * 2;
constexpr int SM_TOTAL  = 232448;
constexpr int SM_HT     = (SM_TOTAL - 3 * 8192) / 1024 * 1024;
constexpr int SM_PV     = SM_HT + 2 * 8192;
constexpr int SM_RING4  = SM_HT - NCWG * 6 * STAGE_B;
constexpr int SM_RING3  = SM_HT - NCWG * 5 * STAGE_B;
constexpr int SLOT_CAP4 = (SM_RING4 - SM_META) / 8;
constexpr int SM_STAGE2 = SM_RING3 - 0;
constexpr int STAGE_CAP = (SM_HT - SM_RING3) / 16;
constexpr int P1_POS    = 3072;
constexpr int P1_STAGE  = P1_POS + 61440;
constexpr int P1_SV     = (P1_STAGE + REC_CAP * 16 + 1023) / 1024 * 1024;
constexpr int P1_W1     = P1_SV + MAX_NPC * 512;
constexpr int P1_W2     = P1_W1 + 8192;
constexpr int P1_END    = P1_W2 + 24576;
static_assert(SM_BARS + (8 + 2 * NCWG * MAX_STAGE) * 8 <= SM_SID, "misc block");
static_assert(SM_BARS + 256 <= P1_POS, "misc block");
static_assert(P1_END <= SM_TOTAL, "phase 1 overlay");
static_assert(SM_META + SLOT_CAP * 8 <= SM_RING3, "CSR");
static_assert(SM_RING4 % 1024 == 0 && SM_RING3 % 1024 == 0 && SM_HT % 1024 == 0, "alignment");
static_assert(SM_BARS % 8 == 0 && SM_META % 8 == 0, "alignment");
static_assert(MAX_N * 6 <= 61440, "pos");
static_assert(SM_SID + MAX_NPC * 1024 <= SM_TOTAL, "slow path accumulators");

__device__ __align__(1024) uint4 g_F[MAX_N * 32];
__device__ uint4    g_rec[MAX_CTA * REC_CAP];
__device__ uint32_t g_offs[MAX_CTA * MAX_CTA];
__device__ uint4    g_table[(TAB_BYTES + 15) / 16];
__device__ unsigned g_bar[2];
#define STAMP(k)
#define STAMPT(k, T)
#define ITS(k)

struct Params {
    const __nv_bfloat16* sv;
    const __nv_bfloat16* pos;
    const int*           src;
    const int*           dst;
    const __nv_bfloat16* freqs;
    const __nv_bfloat16* w1;
    const __nv_bfloat16* w2;
    const __nv_bfloat16* wr;
    __nv_bfloat16*       out;
    int N, E, ncta, npc;
    uint32_t npc_magic;
    int quads_per_cta;
};

__device__ __forceinline__ uint32_t smem_u32(const void* p) { return (uint32_t)__cvta_generic_to_shared(p); }
__device__ __forceinline__ float bf_lo(uint32_t v) { return __uint_as_float(v << 16); }
__device__ __forceinline__ float bf_hi(uint32_t v) { return __uint_as_float(v & 0xffff0000u); }
__device__ __forceinline__ float bf_u16(uint16_t v) { return __uint_as_float((uint32_t)v << 16); }
__device__ __forceinline__ uint32_t pack_bf(float lo, float hi) {
    uint32_t r;
    asm("cvt.rn.bf16x2.f32 %0, %1, %2;" : "=r"(r) : "f"(hi), "f"(lo));
    return r;
}
__device__ __forceinline__ float rbf(float x) { return bf_lo(pack_bf(x, 0.f)); }
__device__ __forceinline__ uint32_t hmul2(uint32_t a, uint32_t b) {
    uint32_t r;
    asm("mul.rn.bf16x2 %0, %1, %2;" : "=r"(r) : "r"(a), "r"(b));
    return r;
}
__device__ __forceinline__ uint32_t hsub2(uint32_t a, uint32_t b) {
    uint32_t r;
    asm("sub.rn.bf16x2 %0, %1, %2;" : "=r"(r) : "r"(a), "r"(b));
    return r;
}
__device__ __forceinline__ uint32_t lds32(uint32_t a) { uint32_t v; asm volatile("ld.shared.u32 %0, [%1];" : "=r"(v) : "r"(a)); return v; }
__device__ __forceinline__ uint32_t lds16(uint32_t a) { uint16_t v; asm volatile("ld.shared.u16 %0, [%1];" : "=h"(v) : "r"(a)); return v; }
__device__ __forceinline__ uint2 lds64(uint32_t a) { uint2 v; asm volatile("ld.shared.v2.u32 {%0,%1}, [%2];" : "=r"(v.x), "=r"(v.y) : "r"(a)); return v; }
__device__ __forceinline__ uint4 lds128(uint32_t a) { uint4 v; asm volatile("ld.shared.v4.u32 {%0,%1,%2,%3}, [%4];" : "=r"(v.x), "=r"(v.y), "=r"(v.z), "=r"(v.w) : "r"(a)); return v; }
__device__ __forceinline__ void sts32(uint32_t a, uint32_t v) { asm volatile("st.shared.u32 [%0], %1;" ::"r"(a), "r"(v) : "memory"); }
__device__ __forceinline__ void sts128(uint32_t a, uint4 v) { asm volatile("st.shared.v4.u32 [%0], {%1,%2,%3,%4};" ::"r"(a), "r"(v.x), "r"(v.y), "r"(v.z), "r"(v.w) : "memory"); }
__device__ __forceinline__ void mbar_init(uint32_t bar, int cnt) { asm volatile("mbarrier.init.shared::cta.b64 [%0], %1;" ::"r"(bar), "r"(cnt) : "memory"); }
__device__ __forceinline__ void mbar_expect_tx(uint32_t bar, uint32_t bytes) { asm volatile("mbarrier.arrive.expect_tx.shared::cta.b64 _, [%0], %1;" ::"r"(bar), "r"(bytes) : "memory"); }
__device__ __forceinline__ void mbar_arrive(uint32_t bar) { asm volatile("mbarrier.arrive.shared::cta.b64 _, [%0];" ::"r"(bar) : "memory"); }
__device__ __forceinline__ void mbar_wait(uint32_t bar, uint32_t parity) {
    asm volatile("{\n.reg .pred p;\n.reg .u32 c;\n"
                 "mbarrier.try_wait.parity.shared::cta.b64 p, [%0], %1;\n"
                 "@p bra DONE_%=;\n"
                 "mov.u32 c, 0;\n"
                 "LOOP_%=:\n"
                 "mbarrier.try_wait.parity.shared::cta.b64 p, [%0], %1;\n"
                 "@p bra DONE_%=;\n"
                 "add.u32 c, c, 1;\n"
                 "setp.lt.u32 p, c, 4194304;\n"
                 "@p bra LOOP_%=;\n"
                 "DONE_%=:\n}"
                 ::"r"(bar), "r"(parity) : "memory");
}
__device__ __forceinline__ void mbar_arrive_elected(uint32_t bar) {
    asm volatile("{\n.reg .pred p;\nelect.sync _|p, 0xffffffff;\n@p mbarrier.arrive.shared::cta.b64 _, [%0];\n}" ::"r"(bar) : "memory");
}
__device__ __forceinline__ void bulk_g2s(uint32_t dst, const void* src, uint32_t bytes, uint32_t bar) {
    asm volatile("cp.async.bulk.shared::cluster.global.mbarrier::complete_tx::bytes [%0], [%1], %2, [%3];"
                 ::"r"(dst), "l"(src), "r"(bytes), "r"(bar) : "memory");
}
__device__ __forceinline__ void tma_load(uint32_t dst, const CUtensorMap* tm, int line, uint32_t bar) {
    asm volatile("cp.async.bulk.tensor.2d.shared::cluster.global.mbarrier::complete_tx::bytes [%0], [%1, {%3, %4}], [%2];"
                 ::"r"(dst), "l"(tm), "r"(bar), "r"(0), "r"(line) : "memory");
}
__device__ __forceinline__ void tma_store(const CUtensorMap* tm, int line, uint32_t src) {
    asm volatile("cp.async.bulk.tensor.2d.global.shared::cta.bulk_group [%0, {%2, %3}], [%1];"
                 ::"l"(tm), "r"(src), "r"(0), "r"(line) : "memory");
}
__device__ __forceinline__ void fence_async_smem() { asm volatile("fence.proxy.async.shared::cta;" ::: "memory"); }
__device__ __forceinline__ void named_barrier(int id) { asm volatile("bar.sync %0, 128;" ::"r"(id) : "memory"); }
__device__ __forceinline__ void ldsm4(uint32_t (&r)[4], uint32_t a) {
    asm volatile("ldmatrix.sync.aligned.m8n8.x4.shared.b16 {%0,%1,%2,%3}, [%4];" : "=r"(r[0]), "=r"(r[1]), "=r"(r[2]), "=r"(r[3]) : "r"(a) : "memory");
}
__device__ __forceinline__ void ldsm4t(uint32_t (&r)[4], uint32_t a) {
    asm volatile("ldmatrix.sync.aligned.m8n8.x4.trans.shared.b16 {%0,%1,%2,%3}, [%4];" : "=r"(r[0]), "=r"(r[1]), "=r"(r[2]), "=r"(r[3]) : "r"(a) : "memory");
}
__device__ __forceinline__ void stsm4(uint32_t a, uint32_t r0, uint32_t r1, uint32_t r2, uint32_t r3) {
    asm volatile("stmatrix.sync.aligned.m8n8.x4.shared.b16 [%0], {%1,%2,%3,%4};" ::"r"(a), "r"(r0), "r"(r1), "r"(r2), "r"(r3) : "memory");
}
__device__ __forceinline__ void mma16816(float (&c)[4], const uint32_t (&a)[4], uint32_t b0, uint32_t b1) {
    asm volatile("mma.sync.aligned.m16n8k16.row.col.f32.bf16.bf16.f32 {%0,%1,%2,%3}, {%4,%5,%6,%7}, {%8,%9}, {%0,%1,%2,%3};"
                 : "+f"(c[0]), "+f"(c[1]), "+f"(c[2]), "+f"(c[3])
                 : "r"(a[0]), "r"(a[1]), "r"(a[2]), "r"(a[3]), "r"(b0), "r"(b1));
}

__device__ __forceinline__ uint32_t desc_lo(uint32_t saddr) { return ((saddr & 0x3FFFF) >> 4) | (1u << 16); }
#define DESC_HI "0x40000040"
__device__ __forceinline__ void wg_fence() { asm volatile("wgmma.fence.sync.aligned;" ::: "memory"); }
__device__ __forceinline__ void wg_commit() { asm volatile("wgmma.commit_group.sync.aligned;" ::: "memory"); }
__device__ __forceinline__ void wg_wait0() { asm volatile("wgmma.wait_group.sync.aligned 0;" ::: "memory"); }
__device__ __forceinline__ void wg_wait1() { asm volatile("wgmma.wait_group.sync.aligned 1;" ::: "memory"); }

__device__ __forceinline__ void wgmma_n64_first(float (&d)[8], float (&e)[24], const uint32_t (&a)[4], uint32_t bdesc) {
    asm volatile("{\n.reg .b64 b;\nmov.b64 b, {%36, " DESC_HI "};\n"
                 "wgmma.mma_async.sync.aligned.m64n64k16.f32.bf16.bf16 {%0,%1,%2,%3,%4,%5,%6,%7,%8,%9,%10,%11,%12,%13,%14,%15,%16,%17,%18,%19,%20,%21,%22,%23,%24,%25,%26,%27,%28,%29,%30,%31}, {%32,%33,%34,%35}, b, 0, 1, 1, 1;\n}"
                 : "=f"(d[0]), "=f"(d[1]), "=f"(d[2]), "=f"(d[3]), "=f"(d[4]), "=f"(d[5]), "=f"(d[6]), "=f"(d[7]),
                   "=f"(e[0]), "=f"(e[1]), "=f"(e[2]), "=f"(e[3]), "=f"(e[4]), "=f"(e[5]), "=f"(e[6]), "=f"(e[7]), "=f"(e[8]), "=f"(e[9]), "=f"(e[10]), "=f"(e[11]), "=f"(e[12]), "=f"(e[13]), "=f"(e[14]), "=f"(e[15]), "=f"(e[16]), "=f"(e[17]), "=f"(e[18]), "=f"(e[19]), "=f"(e[20]), "=f"(e[21]), "=f"(e[22]), "=f"(e[23])
                 : "r"(a[0]), "r"(a[1]), "r"(a[2]), "r"(a[3]), "r"(bdesc));
}
__device__ __forceinline__ void wgmma_n64(float (&d)[8], float (&e)[24], const uint32_t (&a)[4], uint32_t bdesc) {
    asm volatile("{\n.reg .b64 b;\nmov.b64 b, {%36, " DESC_HI "};\n"
                 "wgmma.mma_async.sync.aligned.m64n64k16.f32.bf16.bf16 {%0,%1,%2,%3,%4,%5,%6,%7,%8,%9,%10,%11,%12,%13,%14,%15,%16,%17,%18,%19,%20,%21,%22,%23,%24,%25,%26,%27,%28,%29,%30,%31}, {%32,%33,%34,%35}, b, 1, 1, 1, 1;\n}"
                 : "+f"(d[0]), "+f"(d[1]), "+f"(d[2]), "+f"(d[3]), "+f"(d[4]), "+f"(d[5]), "+f"(d[6]), "+f"(d[7]),
                   "+f"(e[0]), "+f"(e[1]), "+f"(e[2]), "+f"(e[3]), "+f"(e[4]), "+f"(e[5]), "+f"(e[6]), "+f"(e[7]), "+f"(e[8]), "+f"(e[9]), "+f"(e[10]), "+f"(e[11]), "+f"(e[12]), "+f"(e[13]), "+f"(e[14]), "+f"(e[15]), "+f"(e[16]), "+f"(e[17]), "+f"(e[18]), "+f"(e[19]), "+f"(e[20]), "+f"(e[21]), "+f"(e[22]), "+f"(e[23])
                 : "r"(a[0]), "r"(a[1]), "r"(a[2]), "r"(a[3]), "r"(bdesc));
}
__device__ __forceinline__ void wgmma_n48_first(float (&e)[24], const uint32_t (&a)[4], uint32_t bdesc) {
    asm volatile("{\n.reg .b64 b;\nmov.b64 b, {%28, " DESC_HI "};\n"
                 "wgmma.mma_async.sync.aligned.m64n48k16.f32.bf16.bf16 {%0,%1,%2,%3,%4,%5,%6,%7,%8,%9,%10,%11,%12,%13,%14,%15,%16,%17,%18,%19,%20,%21,%22,%23}, {%24,%25,%26,%27}, b, 0, 1, 1, 1;\n}"
                 : "=f"(e[0]), "=f"(e[1]), "=f"(e[2]), "=f"(e[3]), "=f"(e[4]), "=f"(e[5]), "=f"(e[6]), "=f"(e[7]), "=f"(e[8]), "=f"(e[9]), "=f"(e[10]), "=f"(e[11]), "=f"(e[12]), "=f"(e[13]), "=f"(e[14]), "=f"(e[15]), "=f"(e[16]), "=f"(e[17]), "=f"(e[18]), "=f"(e[19]), "=f"(e[20]), "=f"(e[21]), "=f"(e[22]), "=f"(e[23])
                 : "r"(a[0]), "r"(a[1]), "r"(a[2]), "r"(a[3]), "r"(bdesc));
}
__device__ __forceinline__ void wgmma_n48(float (&e)[24], const uint32_t (&a)[4], uint32_t bdesc) {
    asm volatile("{\n.reg .b64 b;\nmov.b64 b, {%28, " DESC_HI "};\n"
                 "wgmma.mma_async.sync.aligned.m64n48k16.f32.bf16.bf16 {%0,%1,%2,%3,%4,%5,%6,%7,%8,%9,%10,%11,%12,%13,%14,%15,%16,%17,%18,%19,%20,%21,%22,%23}, {%24,%25,%26,%27}, b, 1, 1, 1, 1;\n}"
                 : "+f"(e[0]), "+f"(e[1]), "+f"(e[2]), "+f"(e[3]), "+f"(e[4]), "+f"(e[5]), "+f"(e[6]), "+f"(e[7]), "+f"(e[8]), "+f"(e[9]), "+f"(e[10]), "+f"(e[11]), "+f"(e[12]), "+f"(e[13]), "+f"(e[14]), "+f"(e[15]), "+f"(e[16]), "+f"(e[17]), "+f"(e[18]), "+f"(e[19]), "+f"(e[20]), "+f"(e[21]), "+f"(e[22]), "+f"(e[23])
                 : "r"(a[0]), "r"(a[1]), "r"(a[2]), "r"(a[3]), "r"(bdesc));
}
__device__ __forceinline__ void wgmma_n16_first(float (&d)[8], const uint32_t (&a)[4], uint32_t bdesc) {
    asm volatile("{\n.reg .b64 b;\nmov.b64 b, {%12, " DESC_HI "};\n"
                 "wgmma.mma_async.sync.aligned.m64n16k16.f32.bf16.bf16 {%0,%1,%2,%3,%4,%5,%6,%7}, {%8,%9,%10,%11}, b, 0, 1, 1, 1;\n}"
                 : "=f"(d[0]), "=f"(d[1]), "=f"(d[2]), "=f"(d[3]), "=f"(d[4]), "=f"(d[5]), "=f"(d[6]), "=f"(d[7])
                 : "r"(a[0]), "r"(a[1]), "r"(a[2]), "r"(a[3]), "r"(bdesc));
}
__device__ __forceinline__ void wgmma_n16(float (&d)[8], const uint32_t (&a)[4], uint32_t bdesc) {
    asm volatile("{\n.reg .b64 b;\nmov.b64 b, {%12, " DESC_HI "};\n"
                 "wgmma.mma_async.sync.aligned.m64n16k16.f32.bf16.bf16 {%0,%1,%2,%3,%4,%5,%6,%7}, {%8,%9,%10,%11}, b, 1, 1, 1, 1;\n}"
                 : "+f"(d[0]), "+f"(d[1]), "+f"(d[2]), "+f"(d[3]), "+f"(d[4]), "+f"(d[5]), "+f"(d[6]), "+f"(d[7])
                 : "r"(a[0]), "r"(a[1]), "r"(a[2]), "r"(a[3]), "r"(bdesc));
}

__device__ __forceinline__ void wgmma_n64_p(float (&d)[8], float (&e)[24], const uint32_t (&a)[4], uint32_t bdesc, int acc) {
    asm volatile("{\n.reg .pred p;\n.reg .b64 b;\nsetp.ne.b32 p, %37, 0;\nmov.b64 b, {%36, " DESC_HI "};\n"
                 "wgmma.mma_async.sync.aligned.m64n64k16.f32.bf16.bf16 {%0,%1,%2,%3,%4,%5,%6,%7,%8,%9,%10,%11,%12,%13,%14,%15,%16,%17,%18,%19,%20,%21,%22,%23,%24,%25,%26,%27,%28,%29,%30,%31}, {%32,%33,%34,%35}, b, p, 1, 1, 1;\n}"
                 : "+f"(d[0]), "+f"(d[1]), "+f"(d[2]), "+f"(d[3]), "+f"(d[4]), "+f"(d[5]), "+f"(d[6]), "+f"(d[7]),
                   "+f"(e[0]), "+f"(e[1]), "+f"(e[2]), "+f"(e[3]), "+f"(e[4]), "+f"(e[5]), "+f"(e[6]), "+f"(e[7]), "+f"(e[8]), "+f"(e[9]), "+f"(e[10]), "+f"(e[11]), "+f"(e[12]), "+f"(e[13]), "+f"(e[14]), "+f"(e[15]), "+f"(e[16]), "+f"(e[17]), "+f"(e[18]), "+f"(e[19]), "+f"(e[20]), "+f"(e[21]), "+f"(e[22]), "+f"(e[23])
                 : "r"(a[0]), "r"(a[1]), "r"(a[2]), "r"(a[3]), "r"(bdesc), "r"(acc));
}
__device__ __forceinline__ void wgmma_n16_p(float (&d)[8], const uint32_t (&a)[4], uint32_t bdesc, int acc) {
    asm volatile("{\n.reg .pred p;\n.reg .b64 b;\nsetp.ne.b32 p, %13, 0;\nmov.b64 b, {%12, " DESC_HI "};\n"
                 "wgmma.mma_async.sync.aligned.m64n16k16.f32.bf16.bf16 {%0,%1,%2,%3,%4,%5,%6,%7}, {%8,%9,%10,%11}, b, p, 1, 1, 1;\n}"
                 : "+f"(d[0]), "+f"(d[1]), "+f"(d[2]), "+f"(d[3]), "+f"(d[4]), "+f"(d[5]), "+f"(d[6]), "+f"(d[7])
                 : "r"(a[0]), "r"(a[1]), "r"(a[2]), "r"(a[3]), "r"(bdesc), "r"(acc));
}

__device__ __forceinline__ uint32_t edge_dist(uint32_t sxy, uint32_t sz, uint32_t dxy, uint32_t dz, uint32_t& rxy, uint32_t& rz) {
    rxy = hsub2(sxy, dxy);
    rz  = hsub2(sz, dz);
    uint32_t qxy = hmul2(rxy, rxy), qz = hmul2(rz, rz);
    float ss = rbf((bf_lo(qxy) + bf_hi(qxy)) + bf_lo(qz));
    float s2 = rbf(ss + 1e-8f);
    float d;
    asm("sqrt.approx.ftz.f32 %0, %1;" : "=f"(d) : "f"(s2));
    return pack_bf(d, 0.f) & 0xffffu;
}

__device__ __forceinline__ void load_pos(uint32_t sm_pos, int i, uint32_t& xy, uint32_t& z) {
    uint32_t a  = (sm_pos + 6u * (uint32_t)i) & ~3u;
    uint32_t w0 = lds32(a), w1 = lds32(a + 4);
    uint32_t sh = (uint32_t)i << 4;
    xy = __funnelshift_r(w0, w1, sh);
    z  = __funnelshift_r(w1, w1, sh);
}

__device__ __noinline__ float radial_value(float d, float f) {
    float arg = rbf(d * f);
    float sn  = rbf(sinf(arg));
    float rb  = rbf(__fdiv_rn(sn, d));
    float c   = rbf(cosf(rbf(__fdiv_rn(rbf(d * 3.14159265358979323846f), 5.0f))));
    float fc  = rbf(0.5f * rbf(c + 1.0f));
    return rb * fc;
}

__global__ void __launch_bounds__(NT, 1)
painn_kernel(const Params p, const __grid_constant__ CUtensorMap tmF, const __grid_constant__ CUtensorMap tmSV,
             const __grid_constant__ CUtensorMap tmW1, const __grid_constant__ CUtensorMap tmW2) {
    extern __shared__ __align__(1024) uint8_t smem[];
    const uint32_t sb   = smem_u32(smem);
    const int tid  = threadIdx.x, lane = tid & 31, warp = __shfl_sync(0xffffffffu, tid >> 5, 0);
    const int cta  = blockIdx.x;
    const int g    = lane >> 2, t = lane & 3;
    int* binCnt = (int*)(smem + SM_BINCNT);
    int* binOff = (int*)(smem + SM_BINOFF);
    int* nCnt   = (int*)(smem + SM_NCNT);
    uint32_t* nInfo = (uint32_t*)(smem + SM_NINFO);
    volatile int* ctrl = (volatile int*)(smem + SM_CTRL);
    const uint32_t bar_pos = sb + SM_BARS, bar_mlp = bar_pos + 8, bar_rec = bar_pos + 16;
    const uint32_t bar_full = bar_pos + 32, bar_empty = bar_full + NCWG * MAX_STAGE * 8;
    const uint32_t bar_hfull = bar_empty + NCWG * MAX_STAGE * 8, bar_hempty = bar_hfull + 16;

    const int node0  = cta * p.npc;
    const int nnodes = max(0, min(p.npc, p.N - node0));

    STAMP(0);
    if (tid == 0) {
        mbar_init(bar_pos, 1);
        asm volatile("fence.mbarrier_init.release.cluster;" ::: "memory");
        uint32_t pos_bytes = (uint32_t)(p.N * 6 + 15) & ~15u;
        mbar_expect_tx(bar_pos, pos_bytes);
        bulk_g2s(sb + P1_POS, p.pos, pos_bytes, bar_pos);
    } else if (tid == 32) {
        mbar_init(bar_mlp, 1);
        asm volatile("fence.mbarrier_init.release.cluster;" ::: "memory");
        mbar_expect_tx(bar_mlp, 2u * 160u * 128u + 8192u + 24576u);
        tma_load(sb + P1_W1, &tmW1, 0, bar_mlp);
        tma_load(sb + P1_SV, &tmSV, node0 * 4, bar_mlp);
        tma_load(sb + P1_W2, &tmW2, 0, bar_mlp);
        tma_load(sb + P1_SV + 160 * 128, &tmSV, node0 * 4 + 160, bar_mlp);
    } else if (tid == 64) {
        mbar_init(bar_rec, 1);
        mbar_init(bar_hfull, 4); mbar_init(bar_hfull + 8, 4); mbar_init(bar_hempty, 4); mbar_init(bar_hempty + 8, 4);
        asm volatile("prefetch.tensormap [%0];" ::"l"(&tmF) : "memory");
    } else if (tid >= 96 && tid < 96 + NCWG * MAX_STAGE) {
        mbar_init(bar_full + 8 * (tid - 96), 2);
        mbar_init(bar_empty + 8 * (tid - 96), 4);
    }
    unsigned bar_seen = 0;
    if (tid == 15 * 32 || tid == 14 * 32)
        asm volatile("ld.relaxed.gpu.global.u32 %0, [%1];" : "=r"(bar_seen) : "l"(&g_bar[tid == 15 * 32 ? 0 : 1]) : "memory");
    const bool mlp_warp = warp >= 6;
    int4 s4[3], d4[3];
    const int q0 = cta * p.quads_per_cta;
    const int qend = min(q0 + p.quads_per_cta, p.E >> 2);
#pragma unroll
    for (int k = 0; k < 3; k++) {
        const int q = q0 + (k < 2 ? warp + 16 * k : 32 + warp) * 32 + lane;
        const bool ok = q < qend && (k < 2 || !mlp_warp);
        s4[k] = ok ? __ldg((const int4*)p.src + q) : make_int4(-1, -1, -1, -1);
        d4[k] = ok ? __ldg((const int4*)p.dst + q) : make_int4(0, 0, 0, 0);
    }
    if (tid < MAX_CTA) binCnt[tid] = 0;
    if (tid < MAX_NPC) nCnt[tid] = 0;
    if (tid < 16) ctrl[tid] = 0;
    if (tid >= 416 && tid < 416 + 48) {
        asm volatile("prefetch.global.L2 [%0];" ::"l"((const uint8_t*)p.wr + (tid - 416) * 128));
    }
    for (int i = P1_STAGE / 16 + tid; i < P1_SV / 16; i += NT) sts128(sb + i * 16, make_uint4(0u, 0u, 0u, 0u));
    __syncthreads();

    if (!mlp_warp) {
        const int rows_per = (TAB_ROWS + 1 + p.ncta - 1) / p.ncta;
        for (int i = tid; i < rows_per * 8; i += 6 * 32) {
            int row = cta * rows_per + (i >> 3), kp = i & 7;
            if (row <= TAB_ROWS) {
                uint32_t val = 0;
                if (row < TAB_ROWS) {
                    float d = __uint_as_float((D_MIN_BITS + row) << 16);
                    uint32_t f2 = __ldg((const uint32_t*)p.freqs + kp);
                    val = pack_bf(radial_value(d, bf_lo(f2)), radial_value(d, bf_hi(f2)));
                }
                ((uint32_t*)g_table)[row * 8 + kp] = val;
            }
        }
    } else {
        const int mt = (warp - 6) >> 1, hf = (warp - 6) & 1;
        if (mt * 16 < nnodes) {
            mbar_wait(bar_mlp, 0);
            STAMPT(10, 6 * 32);
            const int lrow = lane & 15, lch = lane >> 4;
            const uint32_t rowb = sb + P1_SV + (mt * 16 + lrow) * 512;
            const uint32_t key0 = (4 * lrow) & 7;
            float acc[4][4];
#pragma unroll
            for (int i = 0; i < 4; i++) { acc[i][0] = acc[i][1] = acc[i][2] = acc[i][3] = 0.f; }
#pragma unroll
            for (int ks = 0; ks < 4; ks++) {
                uint32_t a[4];
                ldsm4(a, rowb + (((2 * ks + lch) ^ key0) << 4));
                const int kk = 16 * ks + lrow;
#pragma unroll
                for (int nt = 0; nt < 4; nt += 2) {
                    uint32_t b[4];
                    ldsm4t(b, sb + P1_W1 + kk * 128 + (((4 * hf + nt + lch) ^ (kk & 7)) << 4));
                    mma16816(acc[nt], a, b[0], b[1]);
                    mma16816(acc[nt + 1], a, b[2], b[3]);
                }
            }
            uint32_t hp[4][2];
#pragma unroll
            for (int i = 0; i < 4; i++) {
                float h[4];
#pragma unroll
                for (int q = 0; q < 4; q++) {
                    float x = rbf(acc[i][q]);
                    h[q] = __fdividef(x, 1.0f + __expf(-x));
                    acc[i][q] = 0.f;
                }
                hp[i][0] = pack_bf(h[0], h[1]);
                hp[i][1] = pack_bf(h[2], h[3]);
            }
            asm volatile("bar.sync %0, 64;" ::"r"(4 + mt) : "memory");
#pragma unroll
            for (int i = 0; i < 4; i += 2)
                stsm4(rowb + (((4 * hf + i + lch) ^ key0) << 4), hp[i][0], hp[i][1], hp[i + 1][0], hp[i + 1][1]);
            asm volatile("bar.sync %0, 64;" ::"r"(4 + mt) : "memory");
#pragma unroll
            for (int ks = 0; ks < 4; ks++) {
                uint32_t a[4];
                ldsm4(a, rowb + (((2 * ks + lch) ^ key0) << 4));
                const int line = 3 * (16 * ks + lrow) + 1;
#pragma unroll
                for (int nt = 0; nt < 4; nt += 2) {
                    uint32_t b[4];
                    ldsm4t(b, sb + P1_W2 + line * 128 + (((4 * hf + nt + lch) ^ (line & 7)) << 4));
                    mma16816(acc[nt], a, b[0], b[1]);
                    mma16816(acc[nt + 1], a, b[2], b[3]);
                }
            }
            uint32_t vq[2][3][4];
#pragma unroll
            for (int rh = 0; rh < 2; rh++) {
#pragma unroll
                for (int a = 0; a < 3; a++) {
                    const int line = 4 * (mt * 16 + g + 8 * rh) + 1 + a;
#pragma unroll
                    for (int i = 0; i < 4; i++) vq[rh][a][i] = lds32(sb + P1_SV + line * 128 + 4 * t + (((4 * hf + i) ^ (line & 7)) << 4));
                }
            }
#pragma unroll
            for (int rh = 0; rh < 2; rh++) {
#pragma unroll
                for (int a = 0; a < 3; a++) {
                    const int line = 4 * (mt * 16 + g + 8 * rh) + 1 + a;
#pragma unroll
                    for (int i = 0; i < 4; i++)
                        sts32(sb + P1_SV + line * 128 + 4 * t + (((4 * hf + i) ^ (line & 7)) << 4),
                              hmul2(pack_bf(acc[i][2 * rh], acc[i][2 * rh + 1]), vq[rh][a][i]));
                }
            }
            fence_async_smem();
            asm volatile("bar.sync %0, 64;" ::"r"(4 + mt) : "memory");
            if (lane < 8 && mt * 16 + 8 * hf + lane < nnodes)
                tma_store(&tmF, (node0 + mt * 16 + 8 * hf + lane) * 4, sb + P1_SV + (mt * 16 + 8 * hf + lane) * 512);
            asm volatile("cp.async.bulk.commit_group;" ::: "memory");
        }
        STAMPT(11, 6 * 32);
    }
    mbar_wait(bar_pos, 0);
    STAMP(1);

    uint32_t r0[12], r1[12], r2[12], rk[12];
#pragma unroll
    for (int k = 0; k < 3; k++) {
        const int ss[4] = {s4[k].x, s4[k].y, s4[k].z, s4[k].w};
        const int dd[4] = {d4[k].x, d4[k].y, d4[k].z, d4[k].w};
#pragma unroll
        for (int j = 0; j < 4; j++) rk[k * 4 + j] = 0xffffffffu;
        if (ss[0] >= 0) {
#pragma unroll
            for (int j = 0; j < 4; j++) {
                const int e = k * 4 + j;
                const int s = ss[j], d = dd[j];
                uint32_t sxy, sz, dxy, dz, rxy, rz;
                load_pos(sb + P1_POS, s, sxy, sz);
                load_pos(sb + P1_POS, d, dxy, dz);
                uint32_t db = edge_dist(sxy, sz, dxy, dz, rxy, rz);
                float inv;
                asm("rcp.approx.ftz.f32 %0, %1;" : "=f"(inv) : "f"(__uint_as_float(db << 16)));
                uint32_t bin = __umulhi((uint32_t)d, p.npc_magic);
                uint32_t dl  = (uint32_t)d - bin * (uint32_t)p.npc;
                r0[e] = (uint32_t)s | ((db - D_MIN_BITS) << 16);
                r1[e] = pack_bf(bf_lo(rxy) * inv, bf_hi(rxy) * inv);
                r2[e] = __byte_perm(pack_bf(bf_lo(rz) * inv, 0.f), dl, 0x5410);
                if (db <= D_MAX_BITS) rk[e] = (uint32_t)atomicAdd(&binCnt[bin], 1) | (bin << 16);
            }
        }
    }
    STAMP(2);
    STAMPT(12, 6 * 32);
    __syncthreads();
    STAMP(3);
    if (warp == 0) {
        int c[5], s = 0;
#pragma unroll
        for (int i = 0; i < 5; i++) { int b = lane * 5 + i; c[i] = b < p.ncta ? binCnt[b] : 0; s += c[i]; }
        int x = s;
#pragma unroll
        for (int o = 1; o < 32; o <<= 1) { int y = __shfl_up_sync(0xffffffffu, x, o); if (lane >= o) x += y; }
        int off = x - s;
#pragma unroll
        for (int i = 0; i < 5; i++) {
            int b = lane * 5 + i;
            if (b < p.ncta) { binOff[b] = off; g_offs[cta * MAX_CTA + b] = (uint32_t)off | ((uint32_t)c[i] << 16); }
            off += c[i];
        }
        if (lane == 31) ctrl[8] = x;
    }
    __syncthreads();
#pragma unroll
    for (int e = 0; e < 12; e++)
        if (rk[e] != 0xffffffffu) rk[e] = (rk[e] & 0xffffu) + lds32(sb + SM_BINOFF + (rk[e] >> 16) * 4);
#pragma unroll
    for (int e = 0; e < 12; e++)
        if (rk[e] != 0xffffffffu) sts128(sb + P1_STAGE + rk[e] * 16, make_uint4(r0[e], r1[e], r2[e], 0u));
    fence_async_smem();
    __syncthreads();
    if (tid == 0) {
        const uint32_t bytes = (uint32_t)ctrl[8] * 16u;
        if (bytes) asm volatile("cp.async.bulk.global.shared::cta.bulk_group [%0], [%1], %2;"
                                ::"l"(g_rec + (size_t)cta * REC_CAP), "r"(sb + P1_STAGE), "r"(bytes) : "memory");
        asm volatile("cp.async.bulk.commit_group;" ::: "memory");
    }
    if (tid == 32) asm volatile("red.add.release.gpu.global.u32 [%0], 1;" ::"l"(&g_bar[0]) : "memory");
    if (tid == 0 || (mlp_warp && lane < 8)) {
        asm volatile("cp.async.bulk.wait_group 0;" ::: "memory");
        asm volatile("fence.proxy.async;" ::: "memory");
    }

    __syncthreads();
    STAMP(4);
    if (tid == 0) asm volatile("red.add.release.gpu.global.u32 [%0], 1;" ::"l"(&g_bar[1]) : "memory");
    uint32_t wp[3][4];
    if (warp >= 4 && warp < 8) {
        const uint16_t* w2 = (const uint16_t*)p.w2 + 16 * (warp & 3) + g;
#pragma unroll 2
        for (int mk = 0; mk < 8; mk++) {
            uint32_t f[4];
#pragma unroll
            for (int i = 0; i < 4; i++) {
                const uint16_t* q = w2 + (16 * (mk & 3) + 2 * t + 8 * (i >> 1)) * 192 + (mk >> 2) * 128 + 8 * (i & 1);
                f[i] = (uint32_t)__ldg(q) | ((uint32_t)__ldg(q + 192) << 16);
            }
            sts128(sb + SM_HT + (mk * 128 + (tid & 127)) * 16, make_uint4(f[0], f[1], f[2], f[3]));
        }
    }
    if (warp < 12) {
        const uint16_t* wr = (const uint16_t*)p.wr + 16 * (warp & 3) + g;
#pragma unroll
        for (int ty = 0; ty < 3; ty++) {
#pragma unroll
            for (int i = 0; i < 4; i++) {
                const uint16_t* q = wr + (8 * (i >> 1) + 2 * t) * 192 + ty * 64 + 8 * (i & 1);
                wp[ty][i] = (uint32_t)__ldg(q) | ((uint32_t)__ldg(q + 192) << 16);
            }
        }
    }
    if (warp == 15) {
        if (lane == 0) {
            const unsigned target = (bar_seen / (unsigned)p.ncta + 1u) * (unsigned)p.ncta;
            unsigned cur;
            int spins = 0;
            do {
                asm volatile("ld.acquire.gpu.global.u32 %0, [%1];" : "=r"(cur) : "l"(&g_bar[0]) : "memory");
            } while ((int)(cur - target) < 0 && ++spins < (1 << 24));
        }
        __syncwarp();
        uint32_t v[5];
        int s = 0;
#pragma unroll
        for (int i = 0; i < 5; i++) {
            int b = lane * 5 + i;
            v[i] = b < p.ncta ? __ldcg(&g_offs[b * MAX_CTA + cta]) : 0u;
        }
#pragma unroll
        for (int i = 0; i < 5; i++) s += (int)(v[i] >> 16);
        int x = s;
#pragma unroll
        for (int o = 1; o < 32; o <<= 1) { int y = __shfl_up_sync(0xffffffffu, x, o); if (lane >= o) x += y; }
        const int tot = __shfl_sync(0xffffffffu, x, 31);
        int off = x - s;
#pragma unroll
        for (int i = 0; i < 5; i++) {
            int b = lane * 5 + i;
            if (b < p.ncta) { binCnt[b] = (int)v[i]; binOff[b] = off; }
            off += (int)(v[i] >> 16);
        }
        if (lane == 0) {
            ctrl[8] = tot;
            if (tot > STAGE_CAP) ctrl[1] = 1;
            mbar_expect_tx(bar_rec, tot > STAGE_CAP ? 0u : (uint32_t)tot * 16u);
        }
    }
    if (tid == 14 * 32) {
        const unsigned target = (bar_seen / (unsigned)p.ncta + 1u) * (unsigned)p.ncta;
        unsigned cur;
        int spins = 0;
        do {
            asm volatile("ld.acquire.gpu.global.u32 %0, [%1];" : "=r"(cur) : "l"(&g_bar[1]) : "memory");
        } while ((int)(cur - target) < 0 && ++spins < (1 << 24));
    }
    __syncthreads();
    STAMP(5);

    const int total = ctrl[8];
    if (ctrl[1] == 0) {
        const int b = (lane << 4) | warp;
        if (lane < 9 && b < p.ncta) {
            const uint32_t v = (uint32_t)binCnt[b], c = v >> 16;
            if (c) {
                asm volatile("fence.proxy.async;" ::: "memory");
                bulk_g2s(sb + SM_STAGE2 + (uint32_t)binOff[b] * 16u, g_rec + (size_t)b * REC_CAP + (v & 0xffffu), c * 16u, bar_rec);
            }
        }
    }
    mbar_wait(bar_rec, 0);
    STAMP(13);
    constexpr int RPT = 8;
    uint4 rec[RPT];
    const bool okc = ctrl[1] == 0;
#pragma unroll
    for (int k = 0; k < RPT; k++) {
        const int i = tid + k * NT;
        if (okc && i < total) rec[k] = lds128(sb + SM_STAGE2 + i * 16);
    }
#pragma unroll
    for (int k = 0; k < RPT; k++) {
        const int i = tid + k * NT;
        if (okc && i < total) rec[k].w = (uint32_t)atomicAdd(&nCnt[rec[k].z >> 16], 1);
    }
    if (okc) {
        for (int i = tid + RPT * NT; i < total; i += NT) {
            uint32_t dl = lds32(sb + SM_STAGE2 + i * 16 + 8) >> 16;
            sts32(sb + SM_STAGE2 + i * 16 + 12, (uint32_t)atomicAdd(&nCnt[dl], 1));
        }
    }
    __syncthreads();
    if (warp == 0) {
        int c[3], s = 0;
#pragma unroll
        for (int i = 0; i < 3; i++) {
            int b = lane * 3 + i;
            c[i] = b < nnodes ? max(16, (nCnt[b] + 15) & ~15) : 0;
            s += c[i];
        }
        int x = s;
#pragma unroll
        for (int o = 1; o < 32; o <<= 1) { int y = __shfl_up_sync(0xffffffffu, x, o); if (lane >= o) x += y; }
        const int slots = __shfl_sync(0xffffffffu, x, 31);
        int off = x - s, below = 0;
#pragma unroll
        for (int i = 0; i < 3; i++) {
            int b = lane * 3 + i;
            if (b < nnodes) {
                nInfo[b] = (uint32_t)off | ((uint32_t)c[i] << 16);
                below += (2 * off + c[i] < slots);
            }
            off += c[i];
        }
        below = __reduce_add_sync(0xffffffffu, below);
        if (lane == 0) {
            ctrl[2] = below;
            ctrl[4] = slots;
            if (slots > SLOT_CAP) ctrl[1] = 1;
        }
    }
    __syncthreads();
    if (ctrl[1] == 0) {
        uint16_t* sid = (uint16_t*)(smem + SM_SID);
        uint2* meta = (uint2*)(smem + SM_META);
#pragma unroll
        for (int k = 0; k < RPT; k++)
            if (tid + k * NT < total) rec[k].w += lds32(sb + SM_NINFO + (rec[k].z >> 16) * 4) & 0xffffu;
#pragma unroll
        for (int k = 0; k < RPT; k++) {
            if (tid + k * NT < total) {
                const uint4 r = rec[k];
                sid[r.w]  = (uint16_t)((r.x & 0xffffu) << 2);
                meta[r.w] = make_uint2(((r.x >> 16) << 5) | (r.z << 16), r.y);
            }
        }
        for (int i = tid + RPT * NT; i < total; i += NT) {
            uint4 r = lds128(sb + SM_STAGE2 + i * 16);
            int pos = (int)(nInfo[r.z >> 16] & 0xffffu) + (int)r.w;
            sid[pos]  = (uint16_t)((r.x & 0xffffu) << 2);
            meta[pos] = make_uint2(((r.x >> 16) << 5) | (r.z << 16), r.y);
        }
        for (int i = tid; i < nnodes * 16; i += NT) {
            int nl = i >> 4, c = nCnt[nl];
            int j = (c & ~15) + (i & 15);
            if (j >= c && (j < 16 || (c & 15))) {
                int pos = (int)(nInfo[nl] & 0xffffu) + j;
                sid[pos]  = 0xffffu;
                meta[pos] = make_uint2((uint32_t)TAB_ZERO << 5, 0u);
            }
        }
    }
    fence_async_smem();
    __syncthreads();
    STAMP(6);

    if (__shfl_sync(0xffffffffu, ctrl[1], 0) != 0) {
        float* acc = (float*)(smem + P1_POS);
        for (int i = tid; i < nnodes * 256; i += NT) acc[i] = 0.f;
        __syncthreads();
        const uint16_t* posu = (const uint16_t*)p.pos;
        const uint32_t* tabg = (const uint32_t*)g_table;
        const uint32_t* Fw = (const uint32_t*)g_F;
        for (int e0 = warp * 32; e0 < p.E; e0 += NT) {
            int e = e0 + lane;
            int s = 0, d = 0;
            uint32_t db = 0xffff, rxy = 0, rz = 0;
            bool act = false;
            if (e < p.E) {
                s = p.src[e]; d = p.dst[e];
                if (d >= node0 && d < node0 + nnodes) {
                    uint32_t sxy = posu[s * 3] | ((uint32_t)posu[s * 3 + 1] << 16), sz = posu[s * 3 + 2];
                    uint32_t dxy = posu[d * 3] | ((uint32_t)posu[d * 3 + 1] << 16), dz = posu[d * 3 + 2];
                    db  = edge_dist(sxy, sz, dxy, dz, rxy, rz);
                    act = db <= D_MAX_BITS;
                }
            }
            unsigned m = __ballot_sync(0xffffffffu, act);
            while (m) {
                int l = __ffs(m) - 1;
                m &= m - 1;
                int es = __shfl_sync(0xffffffffu, s, l), ed = __shfl_sync(0xffffffffu, d, l);
                uint32_t edb = __shfl_sync(0xffffffffu, db, l), exy = __shfl_sync(0xffffffffu, rxy, l), ez = __shfl_sync(0xffffffffu, rz, l);
                float inv = 1.0f / __uint_as_float(edb << 16);
                float rh[3] = {rbf(bf_lo(exy) * inv), rbf(bf_hi(exy) * inv), rbf(bf_lo(ez) * inv)};
                const uint32_t* fr = Fw + (size_t)es * 128 + lane;
                const uint32_t fh = __ldcg(fr);
                const uint32_t q[3] = {__ldcg(fr + 32), __ldcg(fr + 64), __ldcg(fr + 96)};
                float ps0 = 0.f, ps1 = 0.f, pr0 = 0.f, pr1 = 0.f;
                for (int j2 = 0; j2 < 32; j2++) {
                    uint32_t hj = __shfl_sync(0xffffffffu, fh, j2);
                    uint32_t a0 = *(const uint32_t*)(p.w2 + (2 * j2) * 192 + 2 * lane), a1 = *(const uint32_t*)(p.w2 + (2 * j2 + 1) * 192 + 2 * lane);
                    uint32_t b0 = *(const uint32_t*)(p.w2 + (2 * j2) * 192 + 128 + 2 * lane), b1 = *(const uint32_t*)(p.w2 + (2 * j2 + 1) * 192 + 128 + 2 * lane);
                    ps0 += bf_lo(hj) * bf_lo(a0) + bf_hi(hj) * bf_lo(a1);
                    ps1 += bf_lo(hj) * bf_hi(a0) + bf_hi(hj) * bf_hi(a1);
                    pr0 += bf_lo(hj) * bf_lo(b0) + bf_hi(hj) * bf_lo(b1);
                    pr1 += bf_lo(hj) * bf_hi(b0) + bf_hi(hj) * bf_hi(b1);
                }
                float ws0 = 0.f, ws1 = 0.f, wv0 = 0.f, wv1 = 0.f, wr0 = 0.f, wr1 = 0.f;
                for (int k2 = 0; k2 < 8; k2++) {
                    uint32_t rk2 = __ldcg(tabg + (edb - D_MIN_BITS) * 8 + k2);
#pragma unroll
                    for (int h = 0; h < 2; h++) {
                        float rv = h ? bf_hi(rk2) : bf_lo(rk2);
                        const __nv_bfloat16* wrow = p.wr + (2 * k2 + h) * 192 + 2 * lane;
                        uint32_t a = *(const uint32_t*)wrow, b = *(const uint32_t*)(wrow + 64), c = *(const uint32_t*)(wrow + 128);
                        ws0 += rv * bf_lo(a); ws1 += rv * bf_hi(a);
                        wv0 += rv * bf_lo(b); wv1 += rv * bf_hi(b);
                        wr0 += rv * bf_lo(c); wr1 += rv * bf_hi(c);
                    }
                }
                float* a = acc + (ed - node0) * 256 + 2 * lane;
                atomicAdd(a, ps0 * ws0); atomicAdd(a + 1, ps1 * ws1);
#pragma unroll
                for (int c = 0; c < 3; c++) {
                    atomicAdd(a + 64 * (c + 1), wv0 * bf_lo(q[c]) + pr0 * wr0 * rh[c]);
                    atomicAdd(a + 64 * (c + 1) + 1, wv1 * bf_hi(q[c]) + pr1 * wr1 * rh[c]);
                }
            }
        }
        __syncthreads();
        for (int i = tid; i < nnodes * 128; i += NT) {
            uint32_t r = *(const uint32_t*)(p.sv + (size_t)node0 * 256 + 2 * i);
            *(uint32_t*)(p.out + (size_t)node0 * 256 + 2 * i) = pack_bf(bf_lo(r) + acc[2 * i], bf_hi(r) + acc[2 * i + 1]);
        }
        return;
    }

    const int slots = __reduce_max_sync(0xffffffffu, ctrl[4]);
    const int split = __reduce_max_sync(0xffffffffu, ctrl[2]);
    const int nstage = slots <= SLOT_CAP4 ? 6 : 5;
    const uint32_t ring = sb + (nstage == 6 ? SM_RING4 : SM_RING3);
    const int mid = __reduce_max_sync(0xffffffffu, split < nnodes ? (int)(nInfo[split] & 0xffffu) : slots) >> 4;
    const int wgi = warp >> 2, w = warp & 3;
    constexpr uint32_t EMPTY_OFF = NCWG * MAX_STAGE * 8;
    if (wgi == 3) {
        const int sc = w >> 1, r = w & 1;
        const int g0 = (sc == 0 ? 0 : mid) + r, g1 = sc == 0 ? mid : slots >> 4;
        const uint32_t ring_wg = ring + sc * nstage * STAGE_B, full_wg = bar_full + sc * MAX_STAGE * 8;
        const int e = lane >> 1, half = lane & 1;
        const uint32_t coef_off = e * 128 + ((half ^ (e & 7)) << 4);
        const int vrot = (e & 3) ^ ((e >> 1) & 3);
        const uint8_t* tab = (const uint8_t*)g_table + half * 16;
        int stage = r;
        uint32_t phase = 1;
        uint32_t ma = sb + SM_META + (g0 * 16 + e) * 8, ida = sb + SM_SID + g0 * 32;
        uint2 m = make_uint2(0u, 0u);
        uint4 tv = make_uint4(0u, 0u, 0u, 0u), ia = tv, ib = tv;
        if (g0 < g1) {
            m  = lds64(ma);
            ia = lds128(ida);
            ib = lds128(ida + 16);
            tv = __ldg((const uint4*)(tab + (m.x & 0xffffu)));
        }
        for (int left = (g1 - g0 + 1) >> 1; left > 0; left--) {
            const uint32_t st = ring_wg + stage * STAGE_B, fb = full_wg + stage * 8;
            uint4 o[4];
            {
                const uint32_t mul[4] = {0x3f803f80u, __byte_perm(m.y, 0, 0x1010), __byte_perm(m.y, 0, 0x3232), __byte_perm(m.x, 0, 0x3232)};
#pragma unroll
                for (int j = 0; j < 4; j++) {
                    const int v = j ^ vrot;
                    const uint32_t lo = (v & 1) ? mul[1] : mul[0], hi = (v & 1) ? mul[3] : mul[2];
                    const uint32_t mm = (v & 2) ? hi : lo;
                    o[j] = make_uint4(hmul2(tv.x, mm), hmul2(tv.y, mm), hmul2(tv.z, mm), hmul2(tv.w, mm));
                }
            }
            ma += 256; ida += 64;
            if (left > 1) m = lds64(ma);
            mbar_wait(fb + EMPTY_OFF, phase);
            uint32_t leader;
            asm volatile("{\n.reg .pred p;\nelect.sync _|p, 0xffffffff;\nselp.u32 %0, 1, 0, p;\n}" : "=r"(leader));
            if (leader) {
                const uint32_t id2[8] = {ia.x, ia.y, ia.z, ia.w, ib.x, ib.y, ib.z, ib.w};
                const uint32_t rows = st + 2048;
                if ((ib.w >> 16) != 0xffffu) {
                    mbar_expect_tx(fb, 16 * 512);
#pragma unroll
                    for (int i = 0; i < 8; i++) {
                        tma_load(rows + (2 * i) * 640, &tmF, (int)(id2[i] & 0xffffu), fb);
                        tma_load(rows + (2 * i + 1) * 640, &tmF, (int)(id2[i] >> 16), fb);
                    }
                } else {
                    int nv = 0;
#pragma unroll
                    for (int i = 0; i < 8; i++) nv += ((id2[i] & 0xffffu) != 0xffffu) + ((id2[i] >> 16) != 0xffffu);
                    mbar_expect_tx(fb, (uint32_t)nv * 512u);
#pragma unroll
                    for (int q = 0; q < 4; q++) {
                        if (4 * q + 4 <= nv) {
                            tma_load(rows + (4 * q) * 640, &tmF, (int)(id2[2 * q] & 0xffffu), fb);
                            tma_load(rows + (4 * q + 1) * 640, &tmF, (int)(id2[2 * q] >> 16), fb);
                            tma_load(rows + (4 * q + 2) * 640, &tmF, (int)(id2[2 * q + 1] & 0xffffu), fb);
                            tma_load(rows + (4 * q + 3) * 640, &tmF, (int)(id2[2 * q + 1] >> 16), fb);
                        } else {
                            if (4 * q < nv)     tma_load(rows + (4 * q) * 640, &tmF, (int)(id2[2 * q] & 0xffffu), fb);
                            if (4 * q + 1 < nv) tma_load(rows + (4 * q + 1) * 640, &tmF, (int)(id2[2 * q] >> 16), fb);
                            if (4 * q + 2 < nv) tma_load(rows + (4 * q + 2) * 640, &tmF, (int)(id2[2 * q + 1] & 0xffffu), fb);
                        }
                    }
                }
            }
            __syncwarp();
            if (left > 1) {
                ia = lds128(ida);
                ib = lds128(ida + 16);
                tv = __ldg((const uint4*)(tab + (m.x & 0xffffu)));
            }
            const uint32_t a = st + coef_off;
#pragma unroll
            for (int j = 0; j < 4; j++) sts128(a ^ ((j ^ vrot) << 5), o[j]);
            fence_async_smem();
            __syncwarp();
            mbar_arrive_elected(fb);
            stage += 2;
            if (stage >= nstage) { stage -= nstage; phase ^= 1; }
        }
    } else if (wgi == 2) {
        uint32_t wA[2][4][4];
#pragma unroll
        for (int mk = 0; mk < 8; mk++) {
            const uint4 q = lds128(sb + SM_HT + (mk * 128 + (tid & 127)) * 16);
            wA[mk >> 2][mk & 3][0] = q.x; wA[mk >> 2][mk & 3][1] = q.y; wA[mk >> 2][mk & 3][2] = q.z; wA[mk >> 2][mk & 3][3] = q.w;
        }
        __syncwarp();
        mbar_arrive_elected(bar_hempty);
        mbar_arrive_elected(bar_hempty + 8);
        const uint32_t lane_off = (uint32_t)node0 * 512u + t * 128 + w * 32 + (g & 1) * 16 + (g >> 1) * 4;
        int nn0 = 0, nn1 = split;
        uint32_t hp0 = 0, hp1 = 0;
        uint32_t rs0 = 0, rs1 = 0;
        if (nn0 < split)  rs0 = __ldg((const uint32_t*)((const uint8_t*)p.sv + (lane_off + (uint32_t)nn0 * 512u)));
        if (nn1 < nnodes) rs1 = __ldg((const uint32_t*)((const uint8_t*)p.sv + (lane_off + (uint32_t)nn1 * 512u)));
        float pr[4][2];
        int pend = -1;
        uint32_t resid_p = 0;
        auto finish = [&]() {
            const bool hi2 = t & 2, hi1 = t & 1, odd = g & 1;
            float ka0 = hi2 ? pr[2][0] : pr[0][0], ka1 = hi2 ? pr[2][1] : pr[0][1];
            float kb0 = hi2 ? pr[3][0] : pr[1][0], kb1 = hi2 ? pr[3][1] : pr[1][1];
            float sa0 = hi2 ? pr[0][0] : pr[2][0], sa1 = hi2 ? pr[0][1] : pr[2][1];
            float sb0 = hi2 ? pr[1][0] : pr[3][0], sb1 = hi2 ? pr[1][1] : pr[3][1];
            ka0 += __shfl_xor_sync(0xffffffffu, sa0, 2); ka1 += __shfl_xor_sync(0xffffffffu, sa1, 2);
            kb0 += __shfl_xor_sync(0xffffffffu, sb0, 2); kb1 += __shfl_xor_sync(0xffffffffu, sb1, 2);
            float k0 = hi1 ? kb0 : ka0, k1 = hi1 ? kb1 : ka1;
            float s0 = hi1 ? ka0 : kb0, s1 = hi1 ? ka1 : kb1;
            k0 += __shfl_xor_sync(0xffffffffu, s0, 1);
            k1 += __shfl_xor_sync(0xffffffffu, s1, 1);
            const float other = __shfl_xor_sync(0xffffffffu, odd ? k0 : k1, 4);
            const float lo = odd ? other : k0, hi = odd ? k1 : other;
            *(uint32_t*)((uint8_t*)p.out + (lane_off + (uint32_t)pend * 512u)) = pack_bf(bf_lo(resid_p) + lo, bf_hi(resid_p) + hi);
            pend = -1;
        };
        auto end_of = [&](int nl, int base) -> int {
            const uint32_t info = lds32(sb + SM_NINFO + nl * 4);
            return (int)(info & 0xffffu) + (int)(info >> 16) - base;
        };
        int e0 = nn0 < split ? end_of(nn0, 0) : 0x7fffffff, e1 = nn1 < nnodes ? end_of(nn1, mid * 16) : 0x7fffffff;
        while (nn0 < split || nn1 < nnodes) {
            const int c = __reduce_max_sync(0xffffffffu, e0 <= e1 ? 0 : 1);
            mbar_wait(bar_hfull + c * 8, c ? hp1 : hp0);
            const uint32_t dht = desc_lo(sb + SM_HT + c * 8192);
            float zs[8], zv[24];
            wg_fence();
            wgmma_n16_first(zs, wA[0][0], dht);
            wgmma_n48_first(zv, wA[1][0], dht + 2);
#pragma unroll
            for (int ks = 1; ks < 4; ks++) {
                wgmma_n16(zs, wA[0][ks], dht + ks * 128);
                wgmma_n48(zv, wA[1][ks], dht + ks * 128 + 2);
            }
            wg_commit();
            float pv[6];
            {
                const uint32_t pa = sb + SM_PV + c * 3072 + (tid & 127) * 8;
                const uint2 a0 = lds64(pa), a1 = lds64(pa + 1024), a2 = lds64(pa + 2048);
                pv[0] = __uint_as_float(a0.x); pv[1] = __uint_as_float(a0.y); pv[2] = __uint_as_float(a1.x);
                pv[3] = __uint_as_float(a1.y); pv[4] = __uint_as_float(a2.x); pv[5] = __uint_as_float(a2.y);
            }
            if (pend >= 0) finish();
            wg_wait0();
            mbar_arrive_elected(bar_hempty + c * 8);
#pragma unroll
            for (int i = 0; i < 12; i++) asm volatile("" : "+r"(wp[i >> 2][i & 3]));
            pr[0][0] = bf_lo(wp[0][0]) * zs[0] + bf_hi(wp[0][0]) * zs[1] + bf_lo(wp[0][2]) * zs[4] + bf_hi(wp[0][2]) * zs[5];
            pr[0][1] = bf_lo(wp[0][1]) * zs[2] + bf_hi(wp[0][1]) * zs[3] + bf_lo(wp[0][3]) * zs[6] + bf_hi(wp[0][3]) * zs[7];
#pragma unroll
            for (int a = 0; a < 3; a++) {
                const float* y = zv + 8 * a;
                pr[a + 1][0] = pv[2 * a] + bf_lo(wp[2][0]) * y[0] + bf_hi(wp[2][0]) * y[1] + bf_lo(wp[2][2]) * y[4] + bf_hi(wp[2][2]) * y[5];
                pr[a + 1][1] = pv[2 * a + 1] + bf_lo(wp[2][1]) * y[2] + bf_hi(wp[2][1]) * y[3] + bf_lo(wp[2][3]) * y[6] + bf_hi(wp[2][3]) * y[7];
            }
            if (c == 0) {
                pend = nn0; resid_p = rs0; hp0 ^= 1;
                e0 = 0x7fffffff;
                if (++nn0 < split) { rs0 = __ldg((const uint32_t*)((const uint8_t*)p.sv + (lane_off + (uint32_t)nn0 * 512u))); e0 = end_of(nn0, 0); }
            } else {
                pend = nn1; resid_p = rs1; hp1 ^= 1;
                e1 = 0x7fffffff;
                if (++nn1 < nnodes) { rs1 = __ldg((const uint32_t*)((const uint8_t*)p.sv + (lane_off + (uint32_t)nn1 * 512u))); e1 = end_of(nn1, mid * 16); }
            }
        }
        if (pend >= 0) finish();
    } else {
        const int wg = wgi;
        uint32_t aoff[4];
        {
            const int e = (lane & 7) + 8 * (lane >> 4), ch = 2 * w + ((lane >> 3) & 1);
#pragma unroll
            for (int b = 0; b < 4; b++) aoff[b] = 2048 + e * 640 + b * 128 + ((ch ^ ((5 * e + b) & 7)) << 4);
        }
        const uint32_t stsm_a = sb + SM_HT + wg * 8192 + (16 * w + (lane & 15)) * 128 + (((lane >> 4) ^ (lane & 7)) << 4);
        const uint32_t pv_a = sb + SM_PV + wg * 3072 + (tid & 127) * 8;
        const uint32_t ring_wg = ring + wg * nstage * STAGE_B;
        const uint32_t full_wg = bar_full + wg * MAX_STAGE * 8;

        float ys[8], yv[24], dQ[3][8];
        uint32_t A0[4][4], A1[4][4];
#pragma unroll
        for (int i = 0; i < 24; i++) yv[i] = 0.f;
#pragma unroll
        for (int i = 0; i < 8; i++) { ys[i] = 0.f; dQ[0][i] = 0.f; dQ[1][i] = 0.f; dQ[2][i] = 0.f; }
        int left = wg == 0 ? mid : (slots >> 4) - mid;
        int fstage = 0;
        uint32_t fphase = 0, fst = ring_wg, fbar = full_wg, hphase = 0;
        uint32_t ninfo_a = sb + SM_NINFO + (wg == 0 ? 0 : split) * 4;
        int gi = 0, G = __reduce_max_sync(0xffffffffu, (int)(lds32(ninfo_a) >> 20));

        auto fetch = [&](uint32_t (&A)[4][4], uint32_t& bd, uint32_t& eb) {
            mbar_wait(fbar, fphase);
#pragma unroll
            for (int b = 0; b < 4; b++) ldsm4t(A[b], fst + aoff[b]);
            bd = desc_lo(fst);
            eb = fbar + EMPTY_OFF;
            fst += STAGE_B; fbar += 8;
            if (++fstage == nstage) { fstage = 0; fphase ^= 1; fst = ring_wg; fbar = full_wg; }
        };
        auto step = [&](uint32_t (&Ac)[4][4], uint32_t bdc, uint32_t ebc, uint32_t (&An)[4][4], uint32_t& bdn, uint32_t& ebn) {
            wg_fence();
            wgmma_n64_p(ys, yv, Ac[0], bdc, gi);
            wgmma_n16_p(dQ[0], Ac[1], bdc, gi);
            wgmma_n16_p(dQ[1], Ac[2], bdc, gi);
            wgmma_n16_p(dQ[2], Ac[3], bdc, gi);
            wg_commit();
            if (--left > 0) fetch(An, bdn, ebn);
            const bool last = ++gi == G;
            uint32_t info_next = 0;
            if (last) { ninfo_a += 4; info_next = lds32(ninfo_a); }
            wg_wait0();
            mbar_arrive_elected(ebc);
            if (last) {
                mbar_wait(bar_hempty + wg * 8, hphase);
                hphase ^= 1;
                stsm4(stsm_a, pack_bf(ys[0], ys[1]), pack_bf(ys[2], ys[3]), pack_bf(ys[4], ys[5]), pack_bf(ys[6], ys[7]));
#pragma unroll
                for (int i = 0; i < 6; i += 2) {
                    stsm4(stsm_a ^ ((i + 2) << 4),
                          pack_bf(yv[4 * i], yv[4 * i + 1]), pack_bf(yv[4 * i + 2], yv[4 * i + 3]),
                          pack_bf(yv[4 * i + 4], yv[4 * i + 5]), pack_bf(yv[4 * i + 6], yv[4 * i + 7]));
                }
#pragma unroll
                for (int i = 0; i < 4; i++) asm volatile("" : "+r"(wp[1][i]));
#pragma unroll
                for (int a = 0; a < 3; a++) {
                    const float* q = dQ[a];
                    const float p0 = bf_lo(wp[1][0]) * q[0] + bf_hi(wp[1][0]) * q[1] + bf_lo(wp[1][2]) * q[4] + bf_hi(wp[1][2]) * q[5];
                    const float p1 = bf_lo(wp[1][1]) * q[2] + bf_hi(wp[1][1]) * q[3] + bf_lo(wp[1][3]) * q[6] + bf_hi(wp[1][3]) * q[7];
                    asm volatile("st.shared.v2.f32 [%0], {%1, %2};" ::"r"(pv_a + a * 1024), "f"(p0), "f"(p1) : "memory");
                }
                fence_async_smem();
                __syncwarp();
                mbar_arrive_elected(bar_hfull + wg * 8);
                G = __reduce_max_sync(0xffffffffu, (int)(info_next >> 20));
                gi = 0;
            }
        };
        if (left > 0) {
            uint32_t bd0, eb0, bd1 = 0, eb1 = 0;
            fetch(A0, bd0, eb0);
            while (true) {
                step(A0, bd0, eb0, A1, bd1, eb1);
                if (left <= 0) break;
                step(A1, bd1, eb1, A0, bd0, eb0);
                if (left <= 0) break;
            }
        }
    }
    STAMP(8);
}

typedef CUresult (*EncodeFn)(CUtensorMap*, CUtensorMapDataType, cuuint32_t, void*, const cuuint64_t*, const cuuint64_t*,
                             const cuuint32_t*, const cuuint32_t*, CUtensorMapInterleave, CUtensorMapSwizzle,
                             CUtensorMapL2promotion, CUtensorMapFloatOOBfill);

void make_map(EncodeFn enc, CUtensorMap* tm, const void* base, uint64_t lines, uint32_t box) {
    cuuint64_t gd[2] = {64, lines};
    cuuint64_t gs[1] = {128};
    cuuint32_t bd[2] = {64, box};
    cuuint32_t es[2] = {1, 1};
    enc(tm, CU_TENSOR_MAP_DATA_TYPE_BFLOAT16, 2, const_cast<void*>(base), gd, gs, bd, es, CU_TENSOR_MAP_INTERLEAVE_NONE,
        CU_TENSOR_MAP_SWIZZLE_128B, CU_TENSOR_MAP_L2_PROMOTION_L2_128B, CU_TENSOR_MAP_FLOAT_OOB_FILL_NONE);
}

}

extern "C" void kernel_launch(void* const* d_in, const int* in_sizes, int n_in, void* d_out, int out_size) {
    (void)n_in; (void)out_size;
    static int n_sm = 0;
    static EncodeFn enc = nullptr;
    static void* f_ptr = nullptr;
    if (n_sm == 0) {
        int dev = 0;
        cudaGetDevice(&dev);
        cudaDeviceGetAttribute(&n_sm, cudaDevAttrMultiProcessorCount, dev);
        cudaFuncSetAttribute(painn_kernel, cudaFuncAttributeMaxDynamicSharedMemorySize, SM_TOTAL);
        void* fn = nullptr;
        cudaDriverEntryPointQueryResult qr;
        cudaGetDriverEntryPoint("cuTensorMapEncodeTiled", &fn, cudaEnableDefault, &qr);
        enc = (EncodeFn)fn;
        cudaGetSymbolAddress(&f_ptr, g_F);
    }
    Params p;
    p.sv    = (const __nv_bfloat16*)d_in[0];
    p.pos   = (const __nv_bfloat16*)d_in[1];
    p.src   = (const int*)d_in[2];
    p.dst   = (const int*)d_in[3];
    p.freqs = (const __nv_bfloat16*)d_in[4];
    p.w1    = (const __nv_bfloat16*)d_in[5];
    p.w2    = (const __nv_bfloat16*)d_in[6];
    p.wr    = (const __nv_bfloat16*)d_in[7];
    p.out   = (__nv_bfloat16*)d_out;
    p.N = in_sizes[1] / 3;
    p.E = in_sizes[2];
    p.ncta = n_sm < MAX_CTA ? n_sm : MAX_CTA;
    p.npc = (p.N + p.ncta - 1) / p.ncta;
    p.npc_magic = (uint32_t)(0x100000000ull / (uint32_t)p.npc) + 1u;
    p.quads_per_cta = ((p.E >> 2) + p.ncta - 1) / p.ncta;
    if (!enc || p.N > MAX_N || p.npc > MAX_NPC || (p.E & 3) || p.quads_per_cta > MAX_ROUNDS * 32) return;

    CUtensorMap tmF, tmSV, tmW1, tmW2;
    make_map(enc, &tmF, f_ptr, (uint64_t)p.N * 4, 4);
    make_map(enc, &tmSV, p.sv, (uint64_t)p.N * 4, 160);
    make_map(enc, &tmW1, p.w1, 64, 64);
    make_map(enc, &tmW2, p.w2, 192, 192);

    cudaLaunchConfig_t cfg = {};
    cfg.gridDim = dim3(p.ncta);
    cfg.blockDim = dim3(NT);
    cfg.dynamicSmemBytes = SM_TOTAL;
    cfg.stream = cudaStreamPerThread;
    cudaLaunchAttribute attr[1];
    attr[0].id = cudaLaunchAttributeCooperative;
    attr[0].val.cooperative = 1;
    cfg.attrs = attr;
    cfg.numAttrs = 1;
    cudaLaunchKernelEx(&cfg, painn_kernel, p, tmF, tmSV, tmW1, tmW2);
}
```

```cpp
#include <cuda_runtime.h>
#include <cuda.h>
#include <cuda_bf16.h>
#include <stdint.h>

namespace {

constexpr int NT        = 512;
constexpr int NCWG      = 2;
constexpr int MAX_N     = 10240;
constexpr int MAX_CTA   = 144;
constexpr int MAX_NPC   = 80;
constexpr int MAX_ROUNDS = 38;
constexpr int REC_CAP   = MAX_ROUNDS * 128;
constexpr int SLOT_CAP  = 6144;
constexpr int MAX_STAGE = 6;
constexpr int STAGE_B   = 12288;

constexpr uint32_t D_MIN_BITS = 0x38D2;
constexpr uint32_t D_MAX_BITS = 0x409C;
constexpr int TAB_ROWS  = (int)(D_MAX_BITS - D_MIN_BITS) + 1;
constexpr int TAB_ZERO  = TAB_ROWS;
constexpr int TAB_BYTES = (TAB_ROWS + 1) * 32;

constexpr int SM_BINCNT = 0;
constexpr int SM_BINOFF = SM_BINCNT + MAX_CTA * 4;
constexpr int SM_NCNT   = SM_BINOFF + MAX_CTA * 4;
constexpr int SM_NINFO  = SM_NCNT + MAX_NPC * 4;
constexpr int SM_ORDER  = SM_NINFO + (MAX_NPC + 1) * 4;
constexpr int SM_CTRL   = SM_ORDER + MAX_NPC + 12;
constexpr int SM_BARS   = SM_CTRL + 64;
constexpr int SM_SID    = 2048 + 256;
constexpr int SM_META   = SM_SID + SLOT_CAP * 2;
constexpr int SM_TOTAL  = 232448;
constexpr int SM_HT     = (SM_TOTAL - 3 * 8192) / 1024 * 1024;
constexpr int SM_PV     = SM_HT + 2 * 8192;
constexpr int SM_RING4  = SM_HT - NCWG * 6 * STAGE_B;
constexpr int SM_RING3  = SM_HT - NCWG * 5 * STAGE_B;
constexpr int SLOT_CAP4 = (SM_RING4 - SM_META) / 8;
constexpr int SM_STAGE2 = SM_RING3 - 0;
constexpr int STAGE_CAP = (SM_HT - SM_RING3) / 16;
constexpr int P1_POS    = 3072;
constexpr int P1_STAGE  = P1_POS + 61440;
constexpr int P1_SV     = (P1_STAGE + REC_CAP * 16 + 1023) / 1024 * 1024;
constexpr int P1_W1     = P1_SV + MAX_NPC * 512;
constexpr int P1_W2     = P1_W1 + 8192;
constexpr int P1_END    = P1_W2 + 24576;
static_assert(SM_BARS + (8 + 2 * NCWG * MAX_STAGE) * 8 <= SM_SID, "misc block");
static_assert(SM_BARS + 256 <= P1_POS, "misc block");
static_assert(P1_END <= SM_TOTAL, "phase 1 overlay");
static_assert(SM_META + SLOT_CAP * 8 <= SM_RING3, "CSR");
static_assert(SM_RING4 % 1024 == 0 && SM_RING3 % 1024 == 0 && SM_HT % 1024 == 0, "alignment");
static_assert(SM_BARS % 8 == 0 && SM_META % 8 == 0 && SM_CTRL % 4 == 0, "alignment");
static_assert(MAX_N * 6 <= 61440, "pos");
static_assert(SM_SID + MAX_NPC * 1024 <= SM_TOTAL, "slow path accumulators");

__device__ __align__(1024) uint4 g_F[MAX_N * 32];
__device__ uint4    g_rec[MAX_CTA * REC_CAP];
__device__ uint32_t g_offs[MAX_CTA * MAX_CTA];
__device__ uint4    g_table[(TAB_BYTES + 15) / 16];
__device__ unsigned g_bar[2];
#define STAMP(k)
#define STAMPT(k, T)
#define ITS(k)

struct Params {
    const __nv_bfloat16* sv;
    const __nv_bfloat16* pos;
    const int*           src;
    const int*           dst;
    const __nv_bfloat16* freqs;
    const __nv_bfloat16* w1;
    const __nv_bfloat16* w2;
    const __nv_bfloat16* wr;
    __nv_bfloat16*       out;
    int N, E, ncta, npc;
    uint32_t npc_magic;
    int quads_per_cta;
};

__device__ __forceinline__ uint32_t smem_u32(const void* p) { return (uint32_t)__cvta_generic_to_shared(p); }
__device__ __forceinline__ float bf_lo(uint32_t v) { return __uint_as_float(v << 16); }
__device__ __forceinline__ float bf_hi(uint32_t v) { return __uint_as_float(v & 0xffff0000u); }
__device__ __forceinline__ float bf_u16(uint16_t v) { return __uint_as_float((uint32_t)v << 16); }
__device__ __forceinline__ uint32_t pack_bf(float lo, float hi) {
    uint32_t r;
    asm("cvt.rn.bf16x2.f32 %0, %1, %2;" : "=r"(r) : "f"(hi), "f"(lo));
    return r;
}
__device__ __forceinline__ float rbf(float x) { return bf_lo(pack_bf(x, 0.f)); }
__device__ __forceinline__ uint32_t hmul2(uint32_t a, uint32_t b) {
    uint32_t r;
    asm("mul.rn.bf16x2 %0, %1, %2;" : "=r"(r) : "r"(a), "r"(b));
    return r;
}
__device__ __forceinline__ uint32_t hsub2(uint32_t a, uint32_t b) {
    uint32_t r;
    asm("sub.rn.bf16x2 %0, %1, %2;" : "=r"(r) : "r"(a), "r"(b));
    return r;
}
__device__ __forceinline__ uint32_t lds32(uint32_t a) { uint32_t v; asm volatile("ld.shared.u32 %0, [%1];" : "=r"(v) : "r"(a)); return v; }
__device__ __forceinline__ uint32_t lds16(uint32_t a) { uint16_t v; asm volatile("ld.shared.u16 %0, [%1];" : "=h"(v) : "r"(a)); return v; }
__device__ __forceinline__ uint2 lds64(uint32_t a) { uint2 v; asm volatile("ld.shared.v2.u32 {%0,%1}, [%2];" : "=r"(v.x), "=r"(v.y) : "r"(a)); return v; }
__device__ __forceinline__ uint4 lds128(uint32_t a) { uint4 v; asm volatile("ld.shared.v4.u32 {%0,%1,%2,%3}, [%4];" : "=r"(v.x), "=r"(v.y), "=r"(v.z), "=r"(v.w) : "r"(a)); return v; }
__device__ __forceinline__ void sts32(uint32_t a, uint32_t v) { asm volatile("st.shared.u32 [%0], %1;" ::"r"(a), "r"(v) : "memory"); }
__device__ __forceinline__ void sts128(uint32_t a, uint4 v) { asm volatile("st.shared.v4.u32 [%0], {%1,%2,%3,%4};" ::"r"(a), "r"(v.x), "r"(v.y), "r"(v.z), "r"(v.w) : "memory"); }
__device__ __forceinline__ void mbar_init(uint32_t bar, int cnt) { asm volatile("mbarrier.init.shared::cta.b64 [%0], %1;" ::"r"(bar), "r"(cnt) : "memory"); }
__device__ __forceinline__ void mbar_expect_tx(uint32_t bar, uint32_t bytes) { asm volatile("mbarrier.arrive.expect_tx.shared::cta.b64 _, [%0], %1;" ::"r"(bar), "r"(bytes) : "memory"); }
__device__ __forceinline__ void mbar_arrive(uint32_t bar) { asm volatile("mbarrier.arrive.shared::cta.b64 _, [%0];" ::"r"(bar) : "memory"); }
__device__ __forceinline__ void mbar_wait(uint32_t bar, uint32_t parity) {
    asm volatile("{\n.reg .pred p;\n.reg .u32 c;\n"
                 "mbarrier.try_wait.parity.shared::cta.b64 p, [%0], %1;\n"
                 "@p bra DONE_%=;\n"
                 "mov.u32 c, 0;\n"
                 "LOOP_%=:\n"
                 "mbarrier.try_wait.parity.shared::cta.b64 p, [%0], %1;\n"
                 "@p bra DONE_%=;\n"
                 "add.u32 c, c, 1;\n"
                 "setp.lt.u32 p, c, 4194304;\n"
                 "@p bra LOOP_%=;\n"
                 "DONE_%=:\n}"
                 ::"r"(bar), "r"(parity) : "memory");
}
__device__ __forceinline__ void mbar_arrive_elected(uint32_t bar) {
    asm volatile("{\n.reg .pred p;\nelect.sync _|p, 0xffffffff;\n@p mbarrier.arrive.shared::cta.b64 _, [%0];\n}" ::"r"(bar) : "memory");
}
__device__ __forceinline__ void bulk_g2s(uint32_t dst, const void* src, uint32_t bytes, uint32_t bar) {
    asm volatile("cp.async.bulk.shared::cluster.global.mbarrier::complete_tx::bytes [%0], [%1], %2, [%3];"
                 ::"r"(dst), "l"(src), "r"(bytes), "r"(bar) : "memory");
}
__device__ __forceinline__ void tma_load(uint32_t dst, const CUtensorMap* tm, int line, uint32_t bar) {
    asm volatile("cp.async.bulk.tensor.2d.shared::cluster.global.mbarrier::complete_tx::bytes [%0], [%1, {%3, %4}], [%2];"
                 ::"r"(dst), "l"(tm), "r"(bar), "r"(0), "r"(line) : "memory");
}
__device__ __forceinline__ void tma_store(const CUtensorMap* tm, int line, uint32_t src) {
    asm volatile("cp.async.bulk.tensor.2d.global.shared::cta.bulk_group [%0, {%2, %3}], [%1];"
                 ::"l"(tm), "r"(src), "r"(0), "r"(line) : "memory");
}
__device__ __forceinline__ void fence_async_smem() { asm volatile("fence.proxy.async.shared::cta;" ::: "memory"); }
__device__ __forceinline__ void named_barrier(int id) { asm volatile("bar.sync %0, 128;" ::"r"(id) : "memory"); }
__device__ __forceinline__ void ldsm4(uint32_t (&r)[4], uint32_t a) {
    asm volatile("ldmatrix.sync.aligned.m8n8.x4.shared.b16 {%0,%1,%2,%3}, [%4];" : "=r"(r[0]), "=r"(r[1]), "=r"(r[2]), "=r"(r[3]) : "r"(a) : "memory");
}
__device__ __forceinline__ void ldsm4t(uint32_t (&r)[4], uint32_t a) {
    asm volatile("ldmatrix.sync.aligned.m8n8.x4.trans.shared.b16 {%0,%1,%2,%3}, [%4];" : "=r"(r[0]), "=r"(r[1]), "=r"(r[2]), "=r"(r[3]) : "r"(a) : "memory");
}
__device__ __forceinline__ void stsm4(uint32_t a, uint32_t r0, uint32_t r1, uint32_t r2, uint32_t r3) {
    asm volatile("stmatrix.sync.aligned.m8n8.x4.shared.b16 [%0], {%1,%2,%3,%4};" ::"r"(a), "r"(r0), "r"(r1), "r"(r2), "r"(r3) : "memory");
}
__device__ __forceinline__ void mma16816(float (&c)[4], const uint32_t (&a)[4], uint32_t b0, uint32_t b1) {
    asm volatile("mma.sync.aligned.m16n8k16.row.col.f32.bf16.bf16.f32 {%0,%1,%2,%3}, {%4,%5,%6,%7}, {%8,%9}, {%0,%1,%2,%3};"
                 : "+f"(c[0]), "+f"(c[1]), "+f"(c[2]), "+f"(c[3])
                 : "r"(a[0]), "r"(a[1]), "r"(a[2]), "r"(a[3]), "r"(b0), "r"(b1));
}

__device__ __forceinline__ uint32_t desc_lo(uint32_t saddr) { return ((saddr & 0x3FFFF) >> 4) | (1u << 16); }
#define DESC_HI "0x40000040"
__device__ __forceinline__ void wg_fence() { asm volatile("wgmma.fence.sync.aligned;" ::: "memory"); }
__device__ __forceinline__ void wg_commit() { asm volatile("wgmma.commit_group.sync.aligned;" ::: "memory"); }
__device__ __forceinline__ void wg_wait0() { asm volatile("wgmma.wait_group.sync.aligned 0;" ::: "memory"); }
__device__ __forceinline__ void wg_wait1() { asm volatile("wgmma.wait_group.sync.aligned 1;" ::: "memory"); }

__device__ __forceinline__ void wgmma_n64_first(float (&d)[8], float (&e)[24], const uint32_t (&a)[4], uint32_t bdesc) {
    asm volatile("{\n.reg .b64 b;\nmov.b64 b, {%36, " DESC_HI "};\n"
                 "wgmma.mma_async.sync.aligned.m64n64k16.f32.bf16.bf16 {%0,%1,%2,%3,%4,%5,%6,%7,%8,%9,%10,%11,%12,%13,%14,%15,%16,%17,%18,%19,%20,%21,%22,%23,%24,%25,%26,%27,%28,%29,%30,%31}, {%32,%33,%34,%35}, b, 0, 1, 1, 1;\n}"
                 : "=f"(d[0]), "=f"(d[1]), "=f"(d[2]), "=f"(d[3]), "=f"(d[4]), "=f"(d[5]), "=f"(d[6]), "=f"(d[7]),
                   "=f"(e[0]), "=f"(e[1]), "=f"(e[2]), "=f"(e[3]), "=f"(e[4]), "=f"(e[5]), "=f"(e[6]), "=f"(e[7]), "=f"(e[8]), "=f"(e[9]), "=f"(e[10]), "=f"(e[11]), "=f"(e[12]), "=f"(e[13]), "=f"(e[14]), "=f"(e[15]), "=f"(e[16]), "=f"(e[17]), "=f"(e[18]), "=f"(e[19]), "=f"(e[20]), "=f"(e[21]), "=f"(e[22]), "=f"(e[23])
                 : "r"(a[0]), "r"(a[1]), "r"(a[2]), "r"(a[3]), "r"(bdesc));
}
__device__ __forceinline__ void wgmma_n64(float (&d)[8], float (&e)[24], const uint32_t (&a)[4], uint32_t bdesc) {
    asm volatile("{\n.reg .b64 b;\nmov.b64 b, {%36, " DESC_HI "};\n"
                 "wgmma.mma_async.sync.aligned.m64n64k16.f32.bf16.bf16 {%0,%1,%2,%3,%4,%5,%6,%7,%8,%9,%10,%11,%12,%13,%14,%15,%16,%17,%18,%19,%20,%21,%22,%23,%24,%25,%26,%27,%28,%29,%30,%31}, {%32,%33,%34,%35}, b, 1, 1, 1, 1;\n}"
                 : "+f"(d[0]), "+f"(d[1]), "+f"(d[2]), "+f"(d[3]), "+f"(d[4]), "+f"(d[5]), "+f"(d[6]), "+f"(d[7]),
                   "+f"(e[0]), "+f"(e[1]), "+f"(e[2]), "+f"(e[3]), "+f"(e[4]), "+f"(e[5]), "+f"(e[6]), "+f"(e[7]), "+f"(e[8]), "+f"(e[9]), "+f"(e[10]), "+f"(e[11]), "+f"(e[12]), "+f"(e[13]), "+f"(e[14]), "+f"(e[15]), "+f"(e[16]), "+f"(e[17]), "+f"(e[18]), "+f"(e[19]), "+f"(e[20]), "+f"(e[21]), "+f"(e[22]), "+f"(e[23])
                 : "r"(a[0]), "r"(a[1]), "r"(a[2]), "r"(a[3]), "r"(bdesc));
}
__device__ __forceinline__ void wgmma_n48_first(float (&e)[24], const uint32_t (&a)[4], uint32_t bdesc) {
    asm volatile("{\n.reg .b64 b;\nmov.b64 b, {%28, " DESC_HI "};\n"
                 "wgmma.mma_async.sync.aligned.m64n48k16.f32.bf16.bf16 {%0,%1,%2,%3,%4,%5,%6,%7,%8,%9,%10,%11,%12,%13,%14,%15,%16,%17,%18,%19,%20,%21,%22,%23}, {%24,%25,%26,%27}, b, 0, 1, 1, 1;\n}"
                 : "=f"(e[0]), "=f"(e[1]), "=f"(e[2]), "=f"(e[3]), "=f"(e[4]), "=f"(e[5]), "=f"(e[6]), "=f"(e[7]), "=f"(e[8]), "=f"(e[9]), "=f"(e[10]), "=f"(e[11]), "=f"(e[12]), "=f"(e[13]), "=f"(e[14]), "=f"(e[15]), "=f"(e[16]), "=f"(e[17]), "=f"(e[18]), "=f"(e[19]), "=f"(e[20]), "=f"(e[21]), "=f"(e[22]), "=f"(e[23])
                 : "r"(a[0]), "r"(a[1]), "r"(a[2]), "r"(a[3]), "r"(bdesc));
}
__device__ __forceinline__ void wgmma_n48(float (&e)[24], const uint32_t (&a)[4], uint32_t bdesc) {
    asm volatile("{\n.reg .b64 b;\nmov.b64 b, {%28, " DESC_HI "};\n"
                 "wgmma.mma_async.sync.aligned.m64n48k16.f32.bf16.bf16 {%0,%1,%2,%3,%4,%5,%6,%7,%8,%9,%10,%11,%12,%13,%14,%15,%16,%17,%18,%19,%20,%21,%22,%23}, {%24,%25,%26,%27}, b, 1, 1, 1, 1;\n}"
                 : "+f"(e[0]), "+f"(e[1]), "+f"(e[2]), "+f"(e[3]), "+f"(e[4]), "+f"(e[5]), "+f"(e[6]), "+f"(e[7]), "+f"(e[8]), "+f"(e[9]), "+f"(e[10]), "+f"(e[11]), "+f"(e[12]), "+f"(e[13]), "+f"(e[14]), "+f"(e[15]), "+f"(e[16]), "+f"(e[17]), "+f"(e[18]), "+f"(e[19]), "+f"(e[20]), "+f"(e[21]), "+f"(e[22]), "+f"(e[23])
                 : "r"(a[0]), "r"(a[1]), "r"(a[2]), "r"(a[3]), "r"(bdesc));
}
__device__ __forceinline__ void wgmma_n16_first(float (&d)[8], const uint32_t (&a)[4], uint32_t bdesc) {
    asm volatile("{\n.reg .b64 b;\nmov.b64 b, {%12, " DESC_HI "};\n"
                 "wgmma.mma_async.sync.aligned.m64n16k16.f32.bf16.bf16 {%0,%1,%2,%3,%4,%5,%6,%7}, {%8,%9,%10,%11}, b, 0, 1, 1, 1;\n}"
                 : "=f"(d[0]), "=f"(d[1]), "=f"(d[2]), "=f"(d[3]), "=f"(d[4]), "=f"(d[5]), "=f"(d[6]), "=f"(d[7])
                 : "r"(a[0]), "r"(a[1]), "r"(a[2]), "r"(a[3]), "r"(bdesc));
}
__device__ __forceinline__ void wgmma_n16(float (&d)[8], const uint32_t (&a)[4], uint32_t bdesc) {
    asm volatile("{\n.reg .b64 b;\nmov.b64 b, {%12, " DESC_HI "};\n"
                 "wgmma.mma_async.sync.aligned.m64n16k16.f32.bf16.bf16 {%0,%1,%2,%3,%4,%5,%6,%7}, {%8,%9,%10,%11}, b, 1, 1, 1, 1;\n}"
                 : "+f"(d[0]), "+f"(d[1]), "+f"(d[2]), "+f"(d[3]), "+f"(d[4]), "+f"(d[5]), "+f"(d[6]), "+f"(d[7])
                 : "r"(a[0]), "r"(a[1]), "r"(a[2]), "r"(a[3]), "r"(bdesc));
}

__device__ __forceinline__ void wgmma_n64_p(float (&d)[8], float (&e)[24], const uint32_t (&a)[4], uint32_t bdesc, int acc) {
    asm volatile("{\n.reg .pred p;\n.reg .b64 b;\nsetp.ne.b32 p, %37, 0;\nmov.b64 b, {%36, " DESC_HI "};\n"
                 "wgmma.mma_async.sync.aligned.m64n64k16.f32.bf16.bf16 {%0,%1,%2,%3,%4,%5,%6,%7,%8,%9,%10,%11,%12,%13,%14,%15,%16,%17,%18,%19,%20,%21,%22,%23,%24,%25,%26,%27,%28,%29,%30,%31}, {%32,%33,%34,%35}, b, p, 1, 1, 1;\n}"
                 : "+f"(d[0]), "+f"(d[1]), "+f"(d[2]), "+f"(d[3]), "+f"(d[4]), "+f"(d[5]), "+f"(d[6]), "+f"(d[7]),
                   "+f"(e[0]), "+f"(e[1]), "+f"(e[2]), "+f"(e[3]), "+f"(e[4]), "+f"(e[5]), "+f"(e[6]), "+f"(e[7]), "+f"(e[8]), "+f"(e[9]), "+f"(e[10]), "+f"(e[11]), "+f"(e[12]), "+f"(e[13]), "+f"(e[14]), "+f"(e[15]), "+f"(e[16]), "+f"(e[17]), "+f"(e[18]), "+f"(e[19]), "+f"(e[20]), "+f"(e[21]), "+f"(e[22]), "+f"(e[23])
                 : "r"(a[0]), "r"(a[1]), "r"(a[2]), "r"(a[3]), "r"(bdesc), "r"(acc));
}
__device__ __forceinline__ void wgmma_n16_p(float (&d)[8], const uint32_t (&a)[4], uint32_t bdesc, int acc) {
    asm volatile("{\n.reg .pred p;\n.reg .b64 b;\nsetp.ne.b32 p, %13, 0;\nmov.b64 b, {%12, " DESC_HI "};\n"
                 "wgmma.mma_async.sync.aligned.m64n16k16.f32.bf16.bf16 {%0,%1,%2,%3,%4,%5,%6,%7}, {%8,%9,%10,%11}, b, p, 1, 1, 1;\n}"
                 : "+f"(d[0]), "+f"(d[1]), "+f"(d[2]), "+f"(d[3]), "+f"(d[4]), "+f"(d[5]), "+f"(d[6]), "+f"(d[7])
                 : "r"(a[0]), "r"(a[1]), "r"(a[2]), "r"(a[3]), "r"(bdesc), "r"(acc));
}

__device__ __forceinline__ uint32_t edge_dist(uint32_t sxy, uint32_t sz, uint32_t dxy, uint32_t dz, uint32_t& rxy, uint32_t& rz) {
    rxy = hsub2(sxy, dxy);
    rz  = hsub2(sz, dz);
    uint32_t qxy = hmul2(rxy, rxy), qz = hmul2(rz, rz);
    float ss = rbf((bf_lo(qxy) + bf_hi(qxy)) + bf_lo(qz));
    float s2 = rbf(ss + 1e-8f);
    float d;
    asm("sqrt.approx.ftz.f32 %0, %1;" : "=f"(d) : "f"(s2));
    return pack_bf(d, 0.f) & 0xffffu;
}

__device__ __forceinline__ void load_pos(uint32_t sm_pos, int i, uint32_t& xy, uint32_t& z) {
    uint32_t a  = (sm_pos + 6u * (uint32_t)i) & ~3u;
    uint32_t w0 = lds32(a), w1 = lds32(a + 4);
    uint32_t sh = (uint32_t)i << 4;
    xy = __funnelshift_r(w0, w1, sh);
    z  = __funnelshift_r(w1, w1, sh);
}

__device__ __noinline__ float radial_value(float d, float f) {
    float arg = rbf(d * f);
    float sn  = rbf(sinf(arg));
    float rb  = rbf(__fdiv_rn(sn, d));
    float c   = rbf(cosf(rbf(__fdiv_rn(rbf(d * 3.14159265358979323846f), 5.0f))));
    float fc  = rbf(0.5f * rbf(c + 1.0f));
    return rb * fc;
}

__global__ void __launch_bounds__(NT, 1)
painn_kernel(const Params p, const __grid_constant__ CUtensorMap tmF, const __grid_constant__ CUtensorMap tmSV,
             const __grid_constant__ CUtensorMap tmW1, const __grid_constant__ CUtensorMap tmW2) {
    extern __shared__ __align__(1024) uint8_t smem[];
    const uint32_t sb   = smem_u32(smem);
    const int tid  = threadIdx.x, lane = tid & 31, warp = __shfl_sync(0xffffffffu, tid >> 5, 0);
    const int cta  = blockIdx.x;
    const int g    = lane >> 2, t = lane & 3;
    int* binCnt = (int*)(smem + SM_BINCNT);
    int* binOff = (int*)(smem + SM_BINOFF);
    int* nCnt   = (int*)(smem + SM_NCNT);
    uint32_t* nInfo = (uint32_t*)(smem + SM_NINFO);
    volatile int* ctrl = (volatile int*)(smem + SM_CTRL);
    const uint32_t bar_pos = sb + SM_BARS, bar_mlp = bar_pos + 8, bar_rec = bar_pos + 16;
    const uint32_t bar_full = bar_pos + 32, bar_empty = bar_full + NCWG * MAX_STAGE * 8;
    const uint32_t bar_hfull = bar_empty + NCWG * MAX_STAGE * 8, bar_hempty = bar_hfull + 16;

    const int node0  = cta * p.npc;
    const int nnodes = max(0, min(p.npc, p.N - node0));

    STAMP(0);
    if (tid == 0) {
        mbar_init(bar_pos, 1);
        asm volatile("fence.mbarrier_init.release.cluster;" ::: "memory");
        uint32_t pos_bytes = (uint32_t)(p.N * 6 + 15) & ~15u;
        mbar_expect_tx(bar_pos, pos_bytes);
        bulk_g2s(sb + P1_POS, p.pos, pos_bytes, bar_pos);
    } else if (tid == 32) {
        mbar_init(bar_mlp, 1);
        asm volatile("fence.mbarrier_init.release.cluster;" ::: "memory");
        mbar_expect_tx(bar_mlp, 2u * 160u * 128u + 8192u + 24576u);
        tma_load(sb + P1_W1, &tmW1, 0, bar_mlp);
        tma_load(sb + P1_SV, &tmSV, node0 * 4, bar_mlp);
        tma_load(sb + P1_W2, &tmW2, 0, bar_mlp);
        tma_load(sb + P1_SV + 160 * 128, &tmSV, node0 * 4 + 160, bar_mlp);
    } else if (tid == 64) {
        mbar_init(bar_rec, 1);
        mbar_init(bar_hfull, 4); mbar_init(bar_hfull + 8, 4); mbar_init(bar_hempty, 4); mbar_init(bar_hempty + 8, 4);
        asm volatile("prefetch.tensormap [%0];" ::"l"(&tmF) : "memory");
    } else if (tid >= 96 && tid < 96 + NCWG * MAX_STAGE) {
        mbar_init(bar_full + 8 * (tid - 96), 2);
        mbar_init(bar_empty + 8 * (tid - 96), 4);
    }
    unsigned bar_seen = 0;
    if (tid == 15 * 32 || tid == 14 * 32)
        asm volatile("ld.relaxed.gpu.global.u32 %0, [%1];" : "=r"(bar_seen) : "l"(&g_bar[tid == 15 * 32 ? 0 : 1]) : "memory");
    const bool mlp_warp = warp >= 6;
    int4 s4[3], d4[3];
    const int q0 = cta * p.quads_per_cta;
    const int qend = min(q0 + p.quads_per_cta, p.E >> 2);
#pragma unroll
    for (int k = 0; k < 3; k++) {
        const int q = q0 + (k < 2 ? warp + 16 * k : 32 + warp) * 32 + lane;
        const bool ok = q < qend && (k < 2 || !mlp_warp);
        s4[k] = ok ? __ldg((const int4*)p.src + q) : make_int4(-1, -1, -1, -1);
        d4[k] = ok ? __ldg((const int4*)p.dst + q) : make_int4(0, 0, 0, 0);
    }
    if (tid < MAX_CTA) binCnt[tid] = 0;
    if (tid < MAX_NPC) nCnt[tid] = 0;
    if (tid < 16) ctrl[tid] = 0;
    if (tid >= 416 && tid < 416 + 48) {
        asm volatile("prefetch.global.L2 [%0];" ::"l"((const uint8_t*)p.wr + (tid - 416) * 128));
    }
    for (int i = P1_STAGE / 16 + tid; i < P1_SV / 16; i += NT) sts128(sb + i * 16, make_uint4(0u, 0u, 0u, 0u));
    __syncthreads();

    if (!mlp_warp) {
        const int rows_per = (TAB_ROWS + 1 + p.ncta - 1) / p.ncta;
        for (int i = tid; i < rows_per * 8; i += 6 * 32) {
            int row = cta * rows_per + (i >> 3), kp = i & 7;
            if (row <= TAB_ROWS) {
                uint32_t val = 0;
                if (row < TAB_ROWS) {
                    float d = __uint_as_float((D_MIN_BITS + row) << 16);
                    uint32_t f2 = __ldg((const uint32_t*)p.freqs + kp);
                    val = pack_bf(radial_value(d, bf_lo(f2)), radial_value(d, bf_hi(f2)));
                }
                ((uint32_t*)g_table)[row * 8 + kp] = val;
            }
        }
    } else {
        const int mt = (warp - 6) >> 1, hf = (warp - 6) & 1;
        if (mt * 16 < nnodes) {
            mbar_wait(bar_mlp, 0);
            STAMPT(10, 6 * 32);
            const int lrow = lane & 15, lch = lane >> 4;
            const uint32_t rowb = sb + P1_SV + (mt * 16 + lrow) * 512;
            const uint32_t key0 = (4 * lrow) & 7;
            float acc[4][4];
#pragma unroll
            for (int i = 0; i < 4; i++) { acc[i][0] = acc[i][1] = acc[i][2] = acc[i][3] = 0.f; }
#pragma unroll
            for (int ks = 0; ks < 4; ks++) {
                uint32_t a[4];
                ldsm4(a, rowb + (((2 * ks + lch) ^ key0) << 4));
                const int kk = 16 * ks + lrow;
#pragma unroll
                for (int nt = 0; nt < 4; nt += 2) {
                    uint32_t b[4];
                    ldsm4t(b, sb + P1_W1 + kk * 128 + (((4 * hf + nt + lch) ^ (kk & 7)) << 4));
                    mma16816(acc[nt], a, b[0], b[1]);
                    mma16816(acc[nt + 1], a, b[2], b[3]);
                }
            }
            uint32_t hp[4][2];
#pragma unroll
            for (int i = 0; i < 4; i++) {
                float h[4];
#pragma unroll
                for (int q = 0; q < 4; q++) {
                    float x = rbf(acc[i][q]);
                    h[q] = __fdividef(x, 1.0f + __expf(-x));
                    acc[i][q] = 0.f;
                }
                hp[i][0] = pack_bf(h[0], h[1]);
                hp[i][1] = pack_bf(h[2], h[3]);
            }
            asm volatile("bar.sync %0, 64;" ::"r"(4 + mt) : "memory");
#pragma unroll
            for (int i = 0; i < 4; i += 2)
                stsm4(rowb + (((4 * hf + i + lch) ^ key0) << 4), hp[i][0], hp[i][1], hp[i + 1][0], hp[i + 1][1]);
            asm volatile("bar.sync %0, 64;" ::"r"(4 + mt) : "memory");
#pragma unroll
            for (int ks = 0; ks < 4; ks++) {
                uint32_t a[4];
                ldsm4(a, rowb + (((2 * ks + lch) ^ key0) << 4));
                const int line = 3 * (16 * ks + lrow) + 1;
#pragma unroll
                for (int nt = 0; nt < 4; nt += 2) {
                    uint32_t b[4];
                    ldsm4t(b, sb + P1_W2 + line * 128 + (((4 * hf + nt + lch) ^ (line & 7)) << 4));
                    mma16816(acc[nt], a, b[0], b[1]);
                    mma16816(acc[nt + 1], a, b[2], b[3]);
                }
            }
            uint32_t vq[2][3][4];
#pragma unroll
            for (int rh = 0; rh < 2; rh++) {
#pragma unroll
                for (int a = 0; a < 3; a++) {
                    const int line = 4 * (mt * 16 + g + 8 * rh) + 1 + a;
#pragma unroll
                    for (int i = 0; i < 4; i++) vq[rh][a][i] = lds32(sb + P1_SV + line * 128 + 4 * t + (((4 * hf + i) ^ (line & 7)) << 4));
                }
            }
#pragma unroll
            for (int rh = 0; rh < 2; rh++) {
#pragma unroll
                for (int a = 0; a < 3; a++) {
                    const int line = 4 * (mt * 16 + g + 8 * rh) + 1 + a;
#pragma unroll
                    for (int i = 0; i < 4; i++)
                        sts32(sb + P1_SV + line * 128 + 4 * t + (((4 * hf + i) ^ (line & 7)) << 4),
                              hmul2(pack_bf(acc[i][2 * rh], acc[i][2 * rh + 1]), vq[rh][a][i]));
                }
            }
            fence_async_smem();
            asm volatile("bar.sync %0, 64;" ::"r"(4 + mt) : "memory");
            if (lane < 8 && mt * 16 + 8 * hf + lane < nnodes)
                tma_store(&tmF, (node0 + mt * 16 + 8 * hf + lane) * 4, sb + P1_SV + (mt * 16 + 8 * hf + lane) * 512);
            asm volatile("cp.async.bulk.commit_group;" ::: "memory");
        }
        STAMPT(11, 6 * 32);
    }
    mbar_wait(bar_pos, 0);
    STAMP(1);

    uint32_t r0[12], r1[12], r2[12], rk[12];
#pragma unroll
    for (int k = 0; k < 3; k++) {
        const int ss[4] = {s4[k].x, s4[k].y, s4[k].z, s4[k].w};
        const int dd[4] = {d4[k].x, d4[k].y, d4[k].z, d4[k].w};
#pragma unroll
        for (int j = 0; j < 4; j++) rk[k * 4 + j] = 0xffffffffu;
        if (ss[0] >= 0) {
#pragma unroll
            for (int j = 0; j < 4; j++) {
                const int e = k * 4 + j;
                const int s = ss[j], d = dd[j];
                uint32_t sxy, sz, dxy, dz, rxy, rz;
                load_pos(sb + P1_POS, s, sxy, sz);
                load_pos(sb + P1_POS, d, dxy, dz);
                uint32_t db = edge_dist(sxy, sz, dxy, dz, rxy, rz);
                float inv;
                asm("rcp.approx.ftz.f32 %0, %1;" : "=f"(inv) : "f"(__uint_as_float(db << 16)));
                uint32_t bin = __umulhi((uint32_t)d, p.npc_magic);
                uint32_t dl  = (uint32_t)d - bin * (uint32_t)p.npc;
                r0[e] = (uint32_t)s | ((db - D_MIN_BITS) << 16);
                r1[e] = pack_bf(bf_lo(rxy) * inv, bf_hi(rxy) * inv);
                r2[e] = __byte_perm(pack_bf(bf_lo(rz) * inv, 0.f), dl, 0x5410);
                if (db <= D_MAX_BITS) rk[e] = (uint32_t)atomicAdd(&binCnt[bin], 1) | (bin << 16);
            }
        }
    }
    STAMP(2);
    STAMPT(12, 6 * 32);
    __syncthreads();
    STAMP(3);
    if (warp == 0) {
        int c[5], s = 0;
#pragma unroll
        for (int i = 0; i < 5; i++) { int b = lane * 5 + i; c[i] = b < p.ncta ? binCnt[b] : 0; s += c[i]; }
        int x = s;
#pragma unroll
        for (int o = 1; o < 32; o <<= 1) { int y = __shfl_up_sync(0xffffffffu, x, o); if (lane >= o) x += y; }
        int off = x - s;
#pragma unroll
        for (int i = 0; i < 5; i++) {
            int b = lane * 5 + i;
            if (b < p.ncta) { binOff[b] = off; g_offs[cta * MAX_CTA + b] = (uint32_t)off | ((uint32_t)c[i] << 16); }
            off += c[i];
        }
        if (lane == 31) ctrl[8] = x;
    }
    __syncthreads();
#pragma unroll
    for (int e = 0; e < 12; e++)
        if (rk[e] != 0xffffffffu) rk[e] = (rk[e] & 0xffffu) + lds32(sb + SM_BINOFF + (rk[e] >> 16) * 4);
#pragma unroll
    for (int e = 0; e < 12; e++)
        if (rk[e] != 0xffffffffu) sts128(sb + P1_STAGE + rk[e] * 16, make_uint4(r0[e], r1[e], r2[e], 0u));
    fence_async_smem();
    __syncthreads();
    if (tid == 0) {
        const uint32_t bytes = (uint32_t)ctrl[8] * 16u;
        if (bytes) asm volatile("cp.async.bulk.global.shared::cta.bulk_group [%0], [%1], %2;"
                                ::"l"(g_rec + (size_t)cta * REC_CAP), "r"(sb + P1_STAGE), "r"(bytes) : "memory");
        asm volatile("cp.async.bulk.commit_group;" ::: "memory");
    }
    if (tid == 32) asm volatile("red.add.release.gpu.global.u32 [%0], 1;" ::"l"(&g_bar[0]) : "memory");
    if (tid == 0 || (mlp_warp && lane < 8)) {
        asm volatile("cp.async.bulk.wait_group 0;" ::: "memory");
        asm volatile("fence.proxy.async;" ::: "memory");
    }

    __syncthreads();
    STAMP(4);
    if (tid == 0) asm volatile("red.add.release.gpu.global.u32 [%0], 1;" ::"l"(&g_bar[1]) : "memory");
    uint32_t wp[3][4];
    if (warp >= 4 && warp < 8) {
        const uint16_t* w2 = (const uint16_t*)p.w2 + 16 * (warp & 3) + g;
#pragma unroll 2
        for (int mk = 0; mk < 8; mk++) {
            uint32_t f[4];
#pragma unroll
            for (int i = 0; i < 4; i++) {
                const uint16_t* q = w2 + (16 * (mk & 3) + 2 * t + 8 * (i >> 1)) * 192 + (mk >> 2) * 128 + 8 * (i & 1);
                f[i] = (uint32_t)__ldg(q) | ((uint32_t)__ldg(q + 192) << 16);
            }
            sts128(sb + SM_HT + (mk * 128 + (tid & 127)) * 16, make_uint4(f[0], f[1], f[2], f[3]));
        }
    }
    if (warp < 12) {
        const uint16_t* wr = (const uint16_t*)p.wr + 16 * (warp & 3) + g;
#pragma unroll
        for (int ty = 0; ty < 3; ty++) {
#pragma unroll
            for (int i = 0; i < 4; i++) {
                const uint16_t* q = wr + (8 * (i >> 1) + 2 * t) * 192 + ty * 64 + 8 * (i & 1);
                wp[ty][i] = (uint32_t)__ldg(q) | ((uint32_t)__ldg(q + 192) << 16);
            }
        }
    }
    if (warp == 15) {
        if (lane == 0) {
            const unsigned target = (bar_seen / (unsigned)p.ncta + 1u) * (unsigned)p.ncta;
            unsigned cur;
            int spins = 0;
            do {
                asm volatile("ld.acquire.gpu.global.u32 %0, [%1];" : "=r"(cur) : "l"(&g_bar[0]) : "memory");
            } while ((int)(cur - target) < 0 && ++spins < (1 << 24));
        }
        __syncwarp();
        uint32_t v[5];
        int s = 0;
#pragma unroll
        for (int i = 0; i < 5; i++) {
            int b = lane * 5 + i;
            v[i] = b < p.ncta ? __ldcg(&g_offs[b * MAX_CTA + cta]) : 0u;
        }
#pragma unroll
        for (int i = 0; i < 5; i++) s += (int)(v[i] >> 16);
        int x = s;
#pragma unroll
        for (int o = 1; o < 32; o <<= 1) { int y = __shfl_up_sync(0xffffffffu, x, o); if (lane >= o) x += y; }
        const int tot = __shfl_sync(0xffffffffu, x, 31);
        int off = x - s;
#pragma unroll
        for (int i = 0; i < 5; i++) {
            int b = lane * 5 + i;
            if (b < p.ncta) { binCnt[b] = (int)v[i]; binOff[b] = off; }
            off += (int)(v[i] >> 16);
        }
        if (lane == 0) {
            ctrl[8] = tot;
            if (tot > STAGE_CAP) ctrl[1] = 1;
            mbar_expect_tx(bar_rec, tot > STAGE_CAP ? 0u : (uint32_t)tot * 16u);
        }
    }
    if (tid == 14 * 32) {
        const unsigned target = (bar_seen / (unsigned)p.ncta + 1u) * (unsigned)p.ncta;
        unsigned cur;
        int spins = 0;
        do {
            asm volatile("ld.acquire.gpu.global.u32 %0, [%1];" : "=r"(cur) : "l"(&g_bar[1]) : "memory");
        } while ((int)(cur - target) < 0 && ++spins < (1 << 24));
    }
    __syncthreads();
    STAMP(5);

    const int total = ctrl[8];
    if (ctrl[1] == 0) {
        const int b = (lane << 4) | warp;
        if (lane < 9 && b < p.ncta) {
            const uint32_t v = (uint32_t)binCnt[b], c = v >> 16;
            if (c) {
                asm volatile("fence.proxy.async;" ::: "memory");
                bulk_g2s(sb + SM_STAGE2 + (uint32_t)binOff[b] * 16u, g_rec + (size_t)b * REC_CAP + (v & 0xffffu), c * 16u, bar_rec);
            }
        }
    }
    mbar_wait(bar_rec, 0);
    STAMP(13);
    constexpr int RPT = 8;
    uint4 rec[RPT];
    const bool okc = ctrl[1] == 0;
#pragma unroll
    for (int k = 0; k < RPT; k++) {
        const int i = tid + k * NT;
        if (okc && i < total) rec[k] = lds128(sb + SM_STAGE2 + i * 16);
    }
#pragma unroll
    for (int k = 0; k < RPT; k++) {
        const int i = tid + k * NT;
        if (okc && i < total) rec[k].w = (uint32_t)atomicAdd(&nCnt[rec[k].z >> 16], 1);
    }
    if (okc) {
        for (int i = tid + RPT * NT; i < total; i += NT) {
            uint32_t dl = lds32(sb + SM_STAGE2 + i * 16 + 8) >> 16;
            sts32(sb + SM_STAGE2 + i * 16 + 12, (uint32_t)atomicAdd(&nCnt[dl], 1));
        }
    }
    __syncthreads();
    if (warp == 0) {
        int c[3], s = 0;
#pragma unroll
        for (int i = 0; i < 3; i++) {
            int b = lane * 3 + i;
            c[i] = b < nnodes ? max(16, (nCnt[b] + 15) & ~15) : 0;
            s += c[i];
        }
        int x = s;
#pragma unroll
        for (int o = 1; o < 32; o <<= 1) { int y = __shfl_up_sync(0xffffffffu, x, o); if (lane >= o) x += y; }
        const int slots = __shfl_sync(0xffffffffu, x, 31);
        int off = x - s, below = 0;
#pragma unroll
        for (int i = 0; i < 3; i++) {
            int b = lane * 3 + i;
            if (b < nnodes) {
                nInfo[b] = (uint32_t)off | ((uint32_t)c[i] << 16);
                below += (2 * off + c[i] < slots);
            }
            off += c[i];
        }
        below = __reduce_add_sync(0xffffffffu, below);
        if (lane == 0) {
            ctrl[2] = below;
            ctrl[4] = slots;
            if (slots > SLOT_CAP) ctrl[1] = 1;
        }
    }
    __syncthreads();
    if (ctrl[1] == 0) {
        uint16_t* sid = (uint16_t*)(smem + SM_SID);
        uint2* meta = (uint2*)(smem + SM_META);
#pragma unroll
        for (int k = 0; k < RPT; k++)
            if (tid + k * NT < total) rec[k].w += lds32(sb + SM_NINFO + (rec[k].z >> 16) * 4) & 0xffffu;
#pragma unroll
        for (int k = 0; k < RPT; k++) {
            if (tid + k * NT < total) {
                const uint4 r = rec[k];
                sid[r.w]  = (uint16_t)((r.x & 0xffffu) << 2);
                meta[r.w] = make_uint2(((r.x >> 16) << 5) | (r.z << 16), r.y);
            }
        }
        for (int i = tid + RPT * NT; i < total; i += NT) {
            uint4 r = lds128(sb + SM_STAGE2 + i * 16);
            int pos = (int)(nInfo[r.z >> 16] & 0xffffu) + (int)r.w;
            sid[pos]  = (uint16_t)((r.x & 0xffffu) << 2);
            meta[pos] = make_uint2(((r.x >> 16) << 5) | (r.z << 16), r.y);
        }
        if (tid >= NT - 128 && tid - (NT - 128) < nnodes) {
            const int b = tid - (NT - 128), split = ctrl[2];
            const int mid = split < nnodes ? (int)(nInfo[split] & 0xffffu) : ctrl[4];
            const int st = b >= split;
            const int mine = (int)(nInfo[b] & 0xffffu) + (int)(nInfo[b] >> 16) - (st ? mid : 0);
            int rank = st ? b - split : b;
            const int o0 = st ? 0 : split, o1 = st ? split : nnodes;
            for (int o = o0; o < o1; o++) {
                const int other = (int)(nInfo[o] & 0xffffu) + (int)(nInfo[o] >> 16) - (st ? 0 : mid);
                rank += st ? (other <= mine) : (other < mine);
            }
            smem[SM_ORDER + rank] = (uint8_t)(b | (st << 7));
        }
        for (int i = tid; i < nnodes * 16; i += NT) {
            int nl = i >> 4, c = nCnt[nl];
            int j = (c & ~15) + (i & 15);
            if (j >= c && (j < 16 || (c & 15))) {
                int pos = (int)(nInfo[nl] & 0xffffu) + j;
                sid[pos]  = 0xffffu;
                meta[pos] = make_uint2((uint32_t)TAB_ZERO << 5, 0u);
            }
        }
    }
    fence_async_smem();
    __syncthreads();
    STAMP(6);

    if (__shfl_sync(0xffffffffu, ctrl[1], 0) != 0) {
        float* acc = (float*)(smem + P1_POS);
        for (int i = tid; i < nnodes * 256; i += NT) acc[i] = 0.f;
        __syncthreads();
        const uint16_t* posu = (const uint16_t*)p.pos;
        const uint32_t* tabg = (const uint32_t*)g_table;
        const uint32_t* Fw = (const uint32_t*)g_F;
        for (int e0 = warp * 32; e0 < p.E; e0 += NT) {
            int e = e0 + lane;
            int s = 0, d = 0;
            uint32_t db = 0xffff, rxy = 0, rz = 0;
            bool act = false;
            if (e < p.E) {
                s = p.src[e]; d = p.dst[e];
                if (d >= node0 && d < node0 + nnodes) {
                    uint32_t sxy = posu[s * 3] | ((uint32_t)posu[s * 3 + 1] << 16), sz = posu[s * 3 + 2];
                    uint32_t dxy = posu[d * 3] | ((uint32_t)posu[d * 3 + 1] << 16), dz = posu[d * 3 + 2];
                    db  = edge_dist(sxy, sz, dxy, dz, rxy, rz);
                    act = db <= D_MAX_BITS;
                }
            }
            unsigned m = __ballot_sync(0xffffffffu, act);
            while (m) {
                int l = __ffs(m) - 1;
                m &= m - 1;
                int es = __shfl_sync(0xffffffffu, s, l), ed = __shfl_sync(0xffffffffu, d, l);
                uint32_t edb = __shfl_sync(0xffffffffu, db, l), exy = __shfl_sync(0xffffffffu, rxy, l), ez = __shfl_sync(0xffffffffu, rz, l);
                float inv = 1.0f / __uint_as_float(edb << 16);
                float rh[3] = {rbf(bf_lo(exy) * inv), rbf(bf_hi(exy) * inv), rbf(bf_lo(ez) * inv)};
                const uint32_t* fr = Fw + (size_t)es * 128 + lane;
                const uint32_t fh = __ldcg(fr);
                const uint32_t q[3] = {__ldcg(fr + 32), __ldcg(fr + 64), __ldcg(fr + 96)};
                float ps0 = 0.f, ps1 = 0.f, pr0 = 0.f, pr1 = 0.f;
                for (int j2 = 0; j2 < 32; j2++) {
                    uint32_t hj = __shfl_sync(0xffffffffu, fh, j2);
                    uint32_t a0 = *(const uint32_t*)(p.w2 + (2 * j2) * 192 + 2 * lane), a1 = *(const uint32_t*)(p.w2 + (2 * j2 + 1) * 192 + 2 * lane);
                    uint32_t b0 = *(const uint32_t*)(p.w2 + (2 * j2) * 192 + 128 + 2 * lane), b1 = *(const uint32_t*)(p.w2 + (2 * j2 + 1) * 192 + 128 + 2 * lane);
                    ps0 += bf_lo(hj) * bf_lo(a0) + bf_hi(hj) * bf_lo(a1);
                    ps1 += bf_lo(hj) * bf_hi(a0) + bf_hi(hj) * bf_hi(a1);
                    pr0 += bf_lo(hj) * bf_lo(b0) + bf_hi(hj) * bf_lo(b1);
                    pr1 += bf_lo(hj) * bf_hi(b0) + bf_hi(hj) * bf_hi(b1);
                }
                float ws0 = 0.f, ws1 = 0.f, wv0 = 0.f, wv1 = 0.f, wr0 = 0.f, wr1 = 0.f;
                for (int k2 = 0; k2 < 8; k2++) {
                    uint32_t rk2 = __ldcg(tabg + (edb - D_MIN_BITS) * 8 + k2);
#pragma unroll
                    for (int h = 0; h < 2; h++) {
                        float rv = h ? bf_hi(rk2) : bf_lo(rk2);
                        const __nv_bfloat16* wrow = p.wr + (2 * k2 + h) * 192 + 2 * lane;
                        uint32_t a = *(const uint32_t*)wrow, b = *(const uint32_t*)(wrow + 64), c = *(const uint32_t*)(wrow + 128);
                        ws0 += rv * bf_lo(a); ws1 += rv * bf_hi(a);
                        wv0 += rv * bf_lo(b); wv1 += rv * bf_hi(b);
                        wr0 += rv * bf_lo(c); wr1 += rv * bf_hi(c);
                    }
                }
                float* a = acc + (ed - node0) * 256 + 2 * lane;
                atomicAdd(a, ps0 * ws0); atomicAdd(a + 1, ps1 * ws1);
#pragma unroll
                for (int c = 0; c < 3; c++) {
                    atomicAdd(a + 64 * (c + 1), wv0 * bf_lo(q[c]) + pr0 * wr0 * rh[c]);
                    atomicAdd(a + 64 * (c + 1) + 1, wv1 * bf_hi(q[c]) + pr1 * wr1 * rh[c]);
                }
            }
        }
        __syncthreads();
        for (int i = tid; i < nnodes * 128; i += NT) {
            uint32_t r = *(const uint32_t*)(p.sv + (size_t)node0 * 256 + 2 * i);
            *(uint32_t*)(p.out + (size_t)node0 * 256 + 2 * i) = pack_bf(bf_lo(r) + acc[2 * i], bf_hi(r) + acc[2 * i + 1]);
        }
        return;
    }

    const int slots = __reduce_max_sync(0xffffffffu, ctrl[4]);
    const int split = __reduce_max_sync(0xffffffffu, ctrl[2]);
    const int nstage = slots <= SLOT_CAP4 ? 6 : 5;
    const uint32_t ring = sb + (nstage == 6 ? SM_RING4 : SM_RING3);
    const int mid = __reduce_max_sync(0xffffffffu, split < nnodes ? (int)(nInfo[split] & 0xffffu) : slots) >> 4;
    const int wgi = warp >> 2, w = warp & 3;
    constexpr uint32_t EMPTY_OFF = NCWG * MAX_STAGE * 8;
    if (wgi == 3) {
        const int sc = w >> 1, r = w & 1;
        const int g0 = (sc == 0 ? 0 : mid) + r, g1 = sc == 0 ? mid : slots >> 4;
        const uint32_t ring_wg = ring + sc * nstage * STAGE_B, full_wg = bar_full + sc * MAX_STAGE * 8;
        const int e = lane >> 1, half = lane & 1;
        const uint32_t coef_off = e * 128 + ((half ^ (e & 7)) << 4);
        const int vrot = (e & 3) ^ ((e >> 1) & 3);
        const uint8_t* tab = (const uint8_t*)g_table + half * 16;
        int stage = r;
        uint32_t phase = 1;
        uint32_t ma = sb + SM_META + (g0 * 16 + e) * 8, ida = sb + SM_SID + g0 * 32;
        uint2 m = make_uint2(0u, 0u);
        uint4 tv = make_uint4(0u, 0u, 0u, 0u), ia = tv, ib = tv;
        if (g0 < g1) {
            m  = lds64(ma);
            ia = lds128(ida);
            ib = lds128(ida + 16);
            tv = __ldg((const uint4*)(tab + (m.x & 0xffffu)));
        }
        for (int left = (g1 - g0 + 1) >> 1; left > 0; left--) {
            const uint32_t st = ring_wg + stage * STAGE_B, fb = full_wg + stage * 8;
            uint4 o[4];
            {
                const uint32_t mul[4] = {0x3f803f80u, __byte_perm(m.y, 0, 0x1010), __byte_perm(m.y, 0, 0x3232), __byte_perm(m.x, 0, 0x3232)};
#pragma unroll
                for (int j = 0; j < 4; j++) {
                    const int v = j ^ vrot;
                    const uint32_t lo = (v & 1) ? mul[1] : mul[0], hi = (v & 1) ? mul[3] : mul[2];
                    const uint32_t mm = (v & 2) ? hi : lo;
                    o[j] = make_uint4(hmul2(tv.x, mm), hmul2(tv.y, mm), hmul2(tv.z, mm), hmul2(tv.w, mm));
                }
            }
            ma += 256; ida += 64;
            if (left > 1) m = lds64(ma);
            mbar_wait(fb + EMPTY_OFF, phase);
            uint32_t leader;
            asm volatile("{\n.reg .pred p;\nelect.sync _|p, 0xffffffff;\nselp.u32 %0, 1, 0, p;\n}" : "=r"(leader));
            if (leader) {
                const uint32_t id2[8] = {ia.x, ia.y, ia.z, ia.w, ib.x, ib.y, ib.z, ib.w};
                const uint32_t rows = st + 2048;
                if ((ib.w >> 16) != 0xffffu) {
                    mbar_expect_tx(fb, 16 * 512);
#pragma unroll
                    for (int i = 0; i < 8; i++) {
                        tma_load(rows + (2 * i) * 640, &tmF, (int)(id2[i] & 0xffffu), fb);
                        tma_load(rows + (2 * i + 1) * 640, &tmF, (int)(id2[i] >> 16), fb);
                    }
                } else {
                    int nv = 0;
#pragma unroll
                    for (int i = 0; i < 8; i++) nv += ((id2[i] & 0xffffu) != 0xffffu) + ((id2[i] >> 16) != 0xffffu);
                    mbar_expect_tx(fb, (uint32_t)nv * 512u);
#pragma unroll
                    for (int q = 0; q < 4; q++) {
                        if (4 * q + 4 <= nv) {
                            tma_load(rows + (4 * q) * 640, &tmF, (int)(id2[2 * q] & 0xffffu), fb);
                            tma_load(rows + (4 * q + 1) * 640, &tmF, (int)(id2[2 * q] >> 16), fb);
                            tma_load(rows + (4 * q + 2) * 640, &tmF, (int)(id2[2 * q + 1] & 0xffffu), fb);
                            tma_load(rows + (4 * q + 3) * 640, &tmF, (int)(id2[2 * q + 1] >> 16), fb);
                        } else {
                            if (4 * q < nv)     tma_load(rows + (4 * q) * 640, &tmF, (int)(id2[2 * q] & 0xffffu), fb);
                            if (4 * q + 1 < nv) tma_load(rows + (4 * q + 1) * 640, &tmF, (int)(id2[2 * q] >> 16), fb);
                            if (4 * q + 2 < nv) tma_load(rows + (4 * q + 2) * 640, &tmF, (int)(id2[2 * q + 1] & 0xffffu), fb);
                        }
                    }
                }
            }
            __syncwarp();
            if (left > 1) {
                ia = lds128(ida);
                ib = lds128(ida + 16);
                tv = __ldg((const uint4*)(tab + (m.x & 0xffffu)));
            }
            const uint32_t a = st + coef_off;
#pragma unroll
            for (int j = 0; j < 4; j++) sts128(a ^ ((j ^ vrot) << 5), o[j]);
            fence_async_smem();
            __syncwarp();
            mbar_arrive_elected(fb);
            stage += 2;
            if (stage >= nstage) { stage -= nstage; phase ^= 1; }
        }
    } else if (wgi == 2) {
        uint32_t wA[2][4][4];
#pragma unroll
        for (int mk = 0; mk < 8; mk++) {
            const uint4 q = lds128(sb + SM_HT + (mk * 128 + (tid & 127)) * 16);
            wA[mk >> 2][mk & 3][0] = q.x; wA[mk >> 2][mk & 3][1] = q.y; wA[mk >> 2][mk & 3][2] = q.z; wA[mk >> 2][mk & 3][3] = q.w;
        }
        __syncwarp();
        mbar_arrive_elected(bar_hempty);
        mbar_arrive_elected(bar_hempty + 8);
        const uint32_t lane_off = (uint32_t)node0 * 512u + t * 128 + w * 32 + (g & 1) * 16 + (g >> 1) * 4;
        uint32_t hpar = 0;
        float zs[8], zv[24], pvv[6], pr[4][2];
        uint32_t residA = 0, residB = 0;
        auto start = [&](int ent) {
            const int c = ent >> 7;
            mbar_wait(bar_hfull + c * 8, (hpar >> c) & 1);
            hpar ^= 1u << c;
            const uint32_t dht = desc_lo(sb + SM_HT + c * 8192);
            wg_fence();
            wgmma_n16_first(zs, wA[0][0], dht);
            wgmma_n48_first(zv, wA[1][0], dht + 2);
#pragma unroll
            for (int ks = 1; ks < 4; ks++) {
                wgmma_n16(zs, wA[0][ks], dht + ks * 128);
                wgmma_n48(zv, wA[1][ks], dht + ks * 128 + 2);
            }
            wg_commit();
        };
        auto side = [&](int ent) {
            const int c = ent >> 7;
            const uint32_t pa = sb + SM_PV + c * 3072 + (tid & 127) * 8;
            const uint2 a0 = lds64(pa), a1 = lds64(pa + 1024), a2 = lds64(pa + 2048);
            pvv[0] = __uint_as_float(a0.x); pvv[1] = __uint_as_float(a0.y); pvv[2] = __uint_as_float(a1.x);
            pvv[3] = __uint_as_float(a1.y); pvv[4] = __uint_as_float(a2.x); pvv[5] = __uint_as_float(a2.y);
            __syncwarp();
            mbar_arrive_elected(bar_hempty + c * 8);
        };
        auto weigh = [&]() {
#pragma unroll
            for (int i = 0; i < 12; i++) asm volatile("" : "+r"(wp[i >> 2][i & 3]));
            pr[0][0] = bf_lo(wp[0][0]) * zs[0] + bf_hi(wp[0][0]) * zs[1] + bf_lo(wp[0][2]) * zs[4] + bf_hi(wp[0][2]) * zs[5];
            pr[0][1] = bf_lo(wp[0][1]) * zs[2] + bf_hi(wp[0][1]) * zs[3] + bf_lo(wp[0][3]) * zs[6] + bf_hi(wp[0][3]) * zs[7];
#pragma unroll
            for (int a = 0; a < 3; a++) {
                const float* y = zv + 8 * a;
                pr[a + 1][0] = pvv[2 * a] + bf_lo(wp[2][0]) * y[0] + bf_hi(wp[2][0]) * y[1] + bf_lo(wp[2][2]) * y[4] + bf_hi(wp[2][2]) * y[5];
                pr[a + 1][1] = pvv[2 * a + 1] + bf_lo(wp[2][1]) * y[2] + bf_hi(wp[2][1]) * y[3] + bf_lo(wp[2][3]) * y[6] + bf_hi(wp[2][3]) * y[7];
            }
        };
        auto finish = [&](int ent, uint32_t resid) {
            const bool hi2 = t & 2, hi1 = t & 1, odd = g & 1;
            float ka0 = hi2 ? pr[2][0] : pr[0][0], ka1 = hi2 ? pr[2][1] : pr[0][1];
            float kb0 = hi2 ? pr[3][0] : pr[1][0], kb1 = hi2 ? pr[3][1] : pr[1][1];
            float sa0 = hi2 ? pr[0][0] : pr[2][0], sa1 = hi2 ? pr[0][1] : pr[2][1];
            float sb0 = hi2 ? pr[1][0] : pr[3][0], sb1 = hi2 ? pr[1][1] : pr[3][1];
            ka0 += __shfl_xor_sync(0xffffffffu, sa0, 2); ka1 += __shfl_xor_sync(0xffffffffu, sa1, 2);
            kb0 += __shfl_xor_sync(0xffffffffu, sb0, 2); kb1 += __shfl_xor_sync(0xffffffffu, sb1, 2);
            float k0 = hi1 ? kb0 : ka0, k1 = hi1 ? kb1 : ka1;
            float s0 = hi1 ? ka0 : kb0, s1 = hi1 ? ka1 : kb1;
            k0 += __shfl_xor_sync(0xffffffffu, s0, 1);
            k1 += __shfl_xor_sync(0xffffffffu, s1, 1);
            const float other = __shfl_xor_sync(0xffffffffu, odd ? k0 : k1, 4);
            const float lo = odd ? other : k0, hi = odd ? k1 : other;
            *(uint32_t*)((uint8_t*)p.out + (lane_off + (uint32_t)(ent & 127) * 512u)) = pack_bf(bf_lo(resid) + lo, bf_hi(resid) + hi);
        };
        auto entry = [&](int i) -> int { return __reduce_max_sync(0xffffffffu, (int)smem[SM_ORDER + i]); };
        auto load_resid = [&](int ent) -> uint32_t { return __ldg((const uint32_t*)((const uint8_t*)p.sv + (lane_off + (uint32_t)(ent & 127) * 512u))); };
        if (nnodes > 0) {
            int i = 0, cur = entry(0), nxt = entry(1);
            residA = load_resid(cur);
            start(cur);
            while (true) {
                if (i + 1 < nnodes) residB = load_resid(nxt);
                wg_wait0();
                side(cur);
                weigh();
                if (i + 1 < nnodes) start(nxt);
                finish(cur, residA);
                if (++i >= nnodes) break;
                cur = nxt; nxt = entry(i + 1);
                if (i + 1 < nnodes) residA = load_resid(nxt);
                wg_wait0();
                side(cur);
                weigh();
                if (i + 1 < nnodes) start(nxt);
                finish(cur, residB);
                if (++i >= nnodes) break;
                cur = nxt; nxt = entry(i + 1);
            }
        }
    } else {
        const int wg = wgi;
        uint32_t aoff[4];
        {
            const int e = (lane & 7) + 8 * (lane >> 4), ch = 2 * w + ((lane >> 3) & 1);
#pragma unroll
            for (int b = 0; b < 4; b++) aoff[b] = 2048 + e * 640 + b * 128 + ((ch ^ ((5 * e + b) & 7)) << 4);
        }
        const uint32_t stsm_a = sb + SM_HT + wg * 8192 + (16 * w + (lane & 15)) * 128 + (((lane >> 4) ^ (lane & 7)) << 4);
        const uint32_t pv_a = sb + SM_PV + wg * 3072 + (tid & 127) * 8;
        const uint32_t ring_wg = ring + wg * nstage * STAGE_B;
        const uint32_t full_wg = bar_full + wg * MAX_STAGE * 8;

        float ys[8], yv[24], dQ[3][8];
        uint32_t A0[4][4], A1[4][4];
#pragma unroll
        for (int i = 0; i < 24; i++) yv[i] = 0.f;
#pragma unroll
        for (int i = 0; i < 8; i++) { ys[i] = 0.f; dQ[0][i] = 0.f; dQ[1][i] = 0.f; dQ[2][i] = 0.f; }
        int left = wg == 0 ? mid : (slots >> 4) - mid;
        int fstage = 0;
        uint32_t fphase = 0, fst = ring_wg, fbar = full_wg, hphase = 0;
        uint32_t ninfo_a = sb + SM_NINFO + (wg == 0 ? 0 : split) * 4;
        int gi = 0, G = __reduce_max_sync(0xffffffffu, (int)(lds32(ninfo_a) >> 20));

        auto fetch = [&](uint32_t (&A)[4][4], uint32_t& bd, uint32_t& eb) {
            mbar_wait(fbar, fphase);
#pragma unroll
            for (int b = 0; b < 4; b++) ldsm4t(A[b], fst + aoff[b]);
            bd = desc_lo(fst);
            eb = fbar + EMPTY_OFF;
            fst += STAGE_B; fbar += 8;
            if (++fstage == nstage) { fstage = 0; fphase ^= 1; fst = ring_wg; fbar = full_wg; }
        };
        auto step = [&](uint32_t (&Ac)[4][4], uint32_t bdc, uint32_t ebc, uint32_t (&An)[4][4], uint32_t& bdn, uint32_t& ebn) {
            wg_fence();
            wgmma_n64_p(ys, yv, Ac[0], bdc, gi);
            wgmma_n16_p(dQ[0], Ac[1], bdc, gi);
            wgmma_n16_p(dQ[1], Ac[2], bdc, gi);
            wgmma_n16_p(dQ[2], Ac[3], bdc, gi);
            wg_commit();
            if (--left > 0) fetch(An, bdn, ebn);
            const bool last = ++gi == G;
            uint32_t info_next = 0;
            if (last) { ninfo_a += 4; info_next = lds32(ninfo_a); }
            wg_wait0();
            mbar_arrive_elected(ebc);
            if (last) {
                mbar_wait(bar_hempty + wg * 8, hphase);
                hphase ^= 1;
                stsm4(stsm_a, pack_bf(ys[0], ys[1]), pack_bf(ys[2], ys[3]), pack_bf(ys[4], ys[5]), pack_bf(ys[6], ys[7]));
#pragma unroll
                for (int i = 0; i < 6; i += 2) {
                    stsm4(stsm_a ^ ((i + 2) << 4),
                          pack_bf(yv[4 * i], yv[4 * i + 1]), pack_bf(yv[4 * i + 2], yv[4 * i + 3]),
                          pack_bf(yv[4 * i + 4], yv[4 * i + 5]), pack_bf(yv[4 * i + 6], yv[4 * i + 7]));
                }
#pragma unroll
                for (int i = 0; i < 4; i++) asm volatile("" : "+r"(wp[1][i]));
#pragma unroll
                for (int a = 0; a < 3; a++) {
                    const float* q = dQ[a];
                    const float p0 = bf_lo(wp[1][0]) * q[0] + bf_hi(wp[1][0]) * q[1] + bf_lo(wp[1][2]) * q[4] + bf_hi(wp[1][2]) * q[5];
                    const float p1 = bf_lo(wp[1][1]) * q[2] + bf_hi(wp[1][1]) * q[3] + bf_lo(wp[1][3]) * q[6] + bf_hi(wp[1][3]) * q[7];
                    asm volatile("st.shared.v2.f32 [%0], {%1, %2};" ::"r"(pv_a + a * 1024), "f"(p0), "f"(p1) : "memory");
                }
                fence_async_smem();
                __syncwarp();
                mbar_arrive_elected(bar_hfull + wg * 8);
                G = __reduce_max_sync(0xffffffffu, (int)(info_next >> 20));
                gi = 0;
            }
        };
        if (left > 0) {
            uint32_t bd0, eb0, bd1 = 0, eb1 = 0;
            fetch(A0, bd0, eb0);
            while (true) {
                step(A0, bd0, eb0, A1, bd1, eb1);
                if (left <= 0) break;
                step(A1, bd1, eb1, A0, bd0, eb0);
                if (left <= 0) break;
            }
        }
    }
    STAMP(8);
}

typedef CUresult (*EncodeFn)(CUtensorMap*, CUtensorMapDataType, cuuint32_t, void*, const cuuint64_t*, const cuuint64_t*,
                             const cuuint32_t*, const cuuint32_t*, CUtensorMapInterleave, CUtensorMapSwizzle,
                             CUtensorMapL2promotion, CUtensorMapFloatOOBfill);

void make_map(EncodeFn enc, CUtensorMap* tm, const void* base, uint64_t lines, uint32_t box) {
    cuuint64_t gd[2] = {64, lines};
    cuuint64_t gs[1] = {128};
    cuuint32_t bd[2] = {64, box};
    cuuint32_t es[2] = {1, 1};
    enc(tm, CU_TENSOR_MAP_DATA_TYPE_BFLOAT16, 2, const_cast<void*>(base), gd, gs, bd, es, CU_TENSOR_MAP_INTERLEAVE_NONE,
        CU_TENSOR_MAP_SWIZZLE_128B, CU_TENSOR_MAP_L2_PROMOTION_L2_128B, CU_TENSOR_MAP_FLOAT_OOB_FILL_NONE);
}

}

extern "C" void kernel_launch(void* const* d_in, const int* in_sizes, int n_in, void* d_out, int out_size) {
    (void)n_in; (void)out_size;
    static int n_sm = 0;
    static EncodeFn enc = nullptr;
    static void* f_ptr = nullptr;
    if (n_sm == 0) {
        int dev = 0;
        cudaGetDevice(&dev);
        cudaDeviceGetAttribute(&n_sm, cudaDevAttrMultiProcessorCount, dev);
        cudaFuncSetAttribute(painn_kernel, cudaFuncAttributeMaxDynamicSharedMemorySize, SM_TOTAL);
        void* fn = nullptr;
        cudaDriverEntryPointQueryResult qr;
        cudaGetDriverEntryPoint("cuTensorMapEncodeTiled", &fn, cudaEnableDefault, &qr);
        enc = (EncodeFn)fn;
        cudaGetSymbolAddress(&f_ptr, g_F);
    }
    Params p;
    p.sv    = (const __nv_bfloat16*)d_in[0];
    p.pos   = (const __nv_bfloat16*)d_in[1];
    p.src   = (const int*)d_in[2];
    p.dst   = (const int*)d_in[3];
    p.freqs = (const __nv_bfloat16*)d_in[4];
    p.w1    = (const __nv_bfloat16*)d_in[5];
    p.w2    = (const __nv_bfloat16*)d_in[6];
    p.wr    = (const __nv_bfloat16*)d_in[7];
    p.out   = (__nv_bfloat16*)d_out;
    p.N = in_sizes[1] / 3;
    p.E = in_sizes[2];
    p.ncta = n_sm < MAX_CTA ? n_sm : MAX_CTA;
    p.npc = (p.N + p.ncta - 1) / p.ncta;
    p.npc_magic = (uint32_t)(0x100000000ull / (uint32_t)p.npc) + 1u;
    p.quads_per_cta = ((p.E >> 2) + p.ncta - 1) / p.ncta;
    if (!enc || p.N > MAX_N || p.npc > MAX_NPC || (p.E & 3) || p.quads_per_cta > MAX_ROUNDS * 32) return;

    CUtensorMap tmF, tmSV, tmW1, tmW2;
    make_map(enc, &tmF, f_ptr, (uint64_t)p.N * 4, 4);
    make_map(enc, &tmSV, p.sv, (uint64_t)p.N * 4, 160);
    make_map(enc, &tmW1, p.w1, 64, 64);
    make_map(enc, &tmW2, p.w2, 192, 192);

    cudaLaunchConfig_t cfg = {};
    cfg.gridDim = dim3(p.ncta);
    cfg.blockDim = dim3(NT);
    cfg.dynamicSmemBytes = SM_TOTAL;
    cfg.stream = cudaStreamPerThread;
    cudaLaunchAttribute attr[1];
    attr[0].id = cudaLaunchAttributeCooperative;
    attr[0].val.cooperative = 1;
    cfg.attrs = attr;
    cfg.numAttrs = 1;
    cudaLaunchKernelEx(&cfg, painn_kernel, p, tmF, tmSV, tmW1, tmW2);
}
```

```cpp
#include <cuda_runtime.h>
#include <cuda.h>
#include <cuda_bf16.h>
#include <stdint.h>

namespace {

constexpr int NT        = 512;
constexpr int NCWG      = 2;
constexpr int MAX_N     = 10240;
constexpr int MAX_CTA   = 144;
constexpr int MAX_NPC   = 80;
constexpr int MAX_ROUNDS = 38;
constexpr int REC_CAP   = MAX_ROUNDS * 128;
constexpr int SEG_W     = 72;
constexpr int SLOT_CAP  = 6144;
constexpr int MAX_STAGE = 6;
constexpr int STAGE_B   = 12288;

constexpr uint32_t D_MIN_BITS = 0x38D2;
constexpr uint32_t D_MAX_BITS = 0x409C;
constexpr int TAB_ROWS  = (int)(D_MAX_BITS - D_MIN_BITS) + 1;
constexpr int TAB_ZERO  = TAB_ROWS;
constexpr int TAB_BYTES = (TAB_ROWS + 1) * 32;

constexpr int SM_BINCNT = 0;
constexpr int SM_BINOFF = SM_BINCNT + MAX_CTA * 4;
constexpr int SM_NCNT   = SM_BINOFF + MAX_CTA * 4;
constexpr int SM_NINFO  = SM_NCNT + MAX_NPC * 4;
constexpr int SM_ORDER  = SM_NINFO + (MAX_NPC + 1) * 4;
constexpr int SM_CTRL   = SM_ORDER + MAX_NPC + 12;
constexpr int SM_BARS   = SM_CTRL + 64;
constexpr int SM_SID    = 2048 + 256;
constexpr int SM_META   = SM_SID + SLOT_CAP * 2;
constexpr int SM_TOTAL  = 232448;
constexpr int SM_HT     = (SM_TOTAL - 3 * 8192) / 1024 * 1024;
constexpr int SM_PV     = SM_HT + 2 * 8192;
constexpr int SM_RING4  = SM_HT - NCWG * 6 * STAGE_B;
constexpr int SM_RING3  = SM_HT - NCWG * 5 * STAGE_B;
constexpr int SLOT_CAP4 = (SM_RING4 - SM_META) / 8;
constexpr int P1_POS    = 3072;
constexpr int P1_SEG    = P1_POS + 61440;
constexpr int P1_REC    = P1_SEG + MAX_CTA * SEG_W * 4;
constexpr int P1_SV     = 142336;
constexpr int P1_W1     = P1_SV + 4 * MAX_NPC * 128;
constexpr int P1_W2     = P1_W1 + 8192;
constexpr int P1_END    = P1_W2 + 24576;
constexpr int STAGE_CAP = (SM_HT - P1_REC) / 16;
static_assert(SM_BARS + (8 + 2 * NCWG * MAX_STAGE) * 8 <= SM_SID, "misc block");
static_assert(SM_BARS + 256 <= P1_POS, "misc block");
static_assert(P1_END <= SM_TOTAL && P1_SV % 1024 == 0 && P1_REC <= P1_SV && P1_REC % 16 == 0, "phase 1 overlay");
static_assert(SM_META + SLOT_CAP * 8 <= SM_RING3, "CSR");
static_assert(SM_RING4 % 1024 == 0 && SM_RING3 % 1024 == 0 && SM_HT % 1024 == 0, "alignment");
static_assert(SM_BARS % 8 == 0 && SM_META % 8 == 0 && SM_CTRL % 4 == 0, "alignment");
static_assert(MAX_N * 6 <= 61440, "pos");
static_assert(SM_SID + MAX_NPC * 1024 <= SM_TOTAL, "slow path accumulators");

__device__ __align__(1024) uint4 g_F[MAX_N * 32];
__device__ __align__(128) uint32_t g_seg[MAX_CTA * MAX_CTA * SEG_W];
__device__ uint4    g_table[(TAB_BYTES + 15) / 16];
__device__ unsigned g_bar;
#define STAMP(k)
#define STAMPT(k, T)
#define ITS(k)

struct Params {
    const __nv_bfloat16* sv;
    const __nv_bfloat16* pos;
    const int*           src;
    const int*           dst;
    const __nv_bfloat16* freqs;
    const __nv_bfloat16* w1;
    const __nv_bfloat16* w2;
    const __nv_bfloat16* wr;
    __nv_bfloat16*       out;
    int N, E, ncta, npc;
    uint32_t npc_magic;
    int quads_per_cta;
};

__device__ __forceinline__ uint32_t smem_u32(const void* p) { return (uint32_t)__cvta_generic_to_shared(p); }
__device__ __forceinline__ float bf_lo(uint32_t v) { return __uint_as_float(v << 16); }
__device__ __forceinline__ float bf_hi(uint32_t v) { return __uint_as_float(v & 0xffff0000u); }
__device__ __forceinline__ float bf_u16(uint16_t v) { return __uint_as_float((uint32_t)v << 16); }
__device__ __forceinline__ uint32_t pack_bf(float lo, float hi) {
    uint32_t r;
    asm("cvt.rn.bf16x2.f32 %0, %1, %2;" : "=r"(r) : "f"(hi), "f"(lo));
    return r;
}
__device__ __forceinline__ float rbf(float x) { return bf_lo(pack_bf(x, 0.f)); }
__device__ __forceinline__ uint32_t hmul2(uint32_t a, uint32_t b) {
    uint32_t r;
    asm("mul.rn.bf16x2 %0, %1, %2;" : "=r"(r) : "r"(a), "r"(b));
    return r;
}
__device__ __forceinline__ uint32_t hsub2(uint32_t a, uint32_t b) {
    uint32_t r;
    asm("sub.rn.bf16x2 %0, %1, %2;" : "=r"(r) : "r"(a), "r"(b));
    return r;
}
__device__ __forceinline__ uint32_t lds32(uint32_t a) { uint32_t v; asm volatile("ld.shared.u32 %0, [%1];" : "=r"(v) : "r"(a)); return v; }
__device__ __forceinline__ uint32_t lds16(uint32_t a) { uint16_t v; asm volatile("ld.shared.u16 %0, [%1];" : "=h"(v) : "r"(a)); return v; }
__device__ __forceinline__ uint2 lds64(uint32_t a) { uint2 v; asm volatile("ld.shared.v2.u32 {%0,%1}, [%2];" : "=r"(v.x), "=r"(v.y) : "r"(a)); return v; }
__device__ __forceinline__ uint4 lds128(uint32_t a) { uint4 v; asm volatile("ld.shared.v4.u32 {%0,%1,%2,%3}, [%4];" : "=r"(v.x), "=r"(v.y), "=r"(v.z), "=r"(v.w) : "r"(a)); return v; }
__device__ __forceinline__ void sts32(uint32_t a, uint32_t v) { asm volatile("st.shared.u32 [%0], %1;" ::"r"(a), "r"(v) : "memory"); }
__device__ __forceinline__ void sts128(uint32_t a, uint4 v) { asm volatile("st.shared.v4.u32 [%0], {%1,%2,%3,%4};" ::"r"(a), "r"(v.x), "r"(v.y), "r"(v.z), "r"(v.w) : "memory"); }
__device__ __forceinline__ void mbar_init(uint32_t bar, int cnt) { asm volatile("mbarrier.init.shared::cta.b64 [%0], %1;" ::"r"(bar), "r"(cnt) : "memory"); }
__device__ __forceinline__ void mbar_expect_tx(uint32_t bar, uint32_t bytes) { asm volatile("mbarrier.arrive.expect_tx.shared::cta.b64 _, [%0], %1;" ::"r"(bar), "r"(bytes) : "memory"); }
__device__ __forceinline__ void mbar_arrive(uint32_t bar) { asm volatile("mbarrier.arrive.shared::cta.b64 _, [%0];" ::"r"(bar) : "memory"); }
__device__ __forceinline__ void mbar_wait(uint32_t bar, uint32_t parity) {
    asm volatile("{\n.reg .pred p;\n.reg .u32 c;\n"
                 "mbarrier.try_wait.parity.shared::cta.b64 p, [%0], %1;\n"
                 "@p bra DONE_%=;\n"
                 "mov.u32 c, 0;\n"
                 "LOOP_%=:\n"
                 "mbarrier.try_wait.parity.shared::cta.b64 p, [%0], %1;\n"
                 "@p bra DONE_%=;\n"
                 "add.u32 c, c, 1;\n"
                 "setp.lt.u32 p, c, 4194304;\n"
                 "@p bra LOOP_%=;\n"
                 "DONE_%=:\n}"
                 ::"r"(bar), "r"(parity) : "memory");
}
__device__ __forceinline__ void mbar_arrive_elected(uint32_t bar) {
    asm volatile("{\n.reg .pred p;\nelect.sync _|p, 0xffffffff;\n@p mbarrier.arrive.shared::cta.b64 _, [%0];\n}" ::"r"(bar) : "memory");
}
__device__ __forceinline__ void bulk_g2s(uint32_t dst, const void* src, uint32_t bytes, uint32_t bar) {
    asm volatile("cp.async.bulk.shared::cluster.global.mbarrier::complete_tx::bytes [%0], [%1], %2, [%3];"
                 ::"r"(dst), "l"(src), "r"(bytes), "r"(bar) : "memory");
}
__device__ __forceinline__ void tma_load(uint32_t dst, const CUtensorMap* tm, int line, uint32_t bar) {
    asm volatile("cp.async.bulk.tensor.2d.shared::cluster.global.mbarrier::complete_tx::bytes [%0], [%1, {%3, %4}], [%2];"
                 ::"r"(dst), "l"(tm), "r"(bar), "r"(0), "r"(line) : "memory");
}
__device__ __forceinline__ void tma_load3(uint32_t dst, const CUtensorMap* tm, int comp, int node, uint32_t bar) {
    asm volatile("cp.async.bulk.tensor.3d.shared::cluster.global.mbarrier::complete_tx::bytes [%0], [%1, {%3, %4, %5}], [%2];"
                 ::"r"(dst), "l"(tm), "r"(bar), "r"(0), "r"(comp), "r"(node) : "memory");
}
__device__ __forceinline__ void tma_store3(const CUtensorMap* tm, int comp, int node, uint32_t src) {
    asm volatile("cp.async.bulk.tensor.3d.global.shared::cta.bulk_group [%0, {%2, %3, %4}], [%1];"
                 ::"l"(tm), "r"(src), "r"(0), "r"(comp), "r"(node) : "memory");
}
__device__ __forceinline__ void fence_async_smem() { asm volatile("fence.proxy.async.shared::cta;" ::: "memory"); }
__device__ __forceinline__ void named_barrier(int id) { asm volatile("bar.sync %0, 128;" ::"r"(id) : "memory"); }
__device__ __forceinline__ void ldsm4(uint32_t (&r)[4], uint32_t a) {
    asm volatile("ldmatrix.sync.aligned.m8n8.x4.shared.b16 {%0,%1,%2,%3}, [%4];" : "=r"(r[0]), "=r"(r[1]), "=r"(r[2]), "=r"(r[3]) : "r"(a) : "memory");
}
__device__ __forceinline__ void ldsm4t(uint32_t (&r)[4], uint32_t a) {
    asm volatile("ldmatrix.sync.aligned.m8n8.x4.trans.shared.b16 {%0,%1,%2,%3}, [%4];" : "=r"(r[0]), "=r"(r[1]), "=r"(r[2]), "=r"(r[3]) : "r"(a) : "memory");
}
__device__ __forceinline__ void stsm4(uint32_t a, uint32_t r0, uint32_t r1, uint32_t r2, uint32_t r3) {
    asm volatile("stmatrix.sync.aligned.m8n8.x4.shared.b16 [%0], {%1,%2,%3,%4};" ::"r"(a), "r"(r0), "r"(r1), "r"(r2), "r"(r3) : "memory");
}
__device__ __forceinline__ void mma16816(float (&c)[4], const uint32_t (&a)[4], uint32_t b0, uint32_t b1) {
    asm volatile("mma.sync.aligned.m16n8k16.row.col.f32.bf16.bf16.f32 {%0,%1,%2,%3}, {%4,%5,%6,%7}, {%8,%9}, {%0,%1,%2,%3};"
                 : "+f"(c[0]), "+f"(c[1]), "+f"(c[2]), "+f"(c[3])
                 : "r"(a[0]), "r"(a[1]), "r"(a[2]), "r"(a[3]), "r"(b0), "r"(b1));
}

__device__ __forceinline__ uint32_t desc_lo(uint32_t saddr) { return ((saddr & 0x3FFFF) >> 4) | (1u << 16); }
#define DESC_HI "0x40000040"
__device__ __forceinline__ void wg_fence() { asm volatile("wgmma.fence.sync.aligned;" ::: "memory"); }
__device__ __forceinline__ void wg_commit() { asm volatile("wgmma.commit_group.sync.aligned;" ::: "memory"); }
__device__ __forceinline__ void wg_wait0() { asm volatile("wgmma.wait_group.sync.aligned 0;" ::: "memory"); }
__device__ __forceinline__ void wg_wait1() { asm volatile("wgmma.wait_group.sync.aligned 1;" ::: "memory"); }

__device__ __forceinline__ void wgmma_n64_first(float (&d)[8], float (&e)[24], const uint32_t (&a)[4], uint32_t bdesc) {
    asm volatile("{\n.reg .b64 b;\nmov.b64 b, {%36, " DESC_HI "};\n"
                 "wgmma.mma_async.sync.aligned.m64n64k16.f32.bf16.bf16 {%0,%1,%2,%3,%4,%5,%6,%7,%8,%9,%10,%11,%12,%13,%14,%15,%16,%17,%18,%19,%20,%21,%22,%23,%24,%25,%26,%27,%28,%29,%30,%31}, {%32,%33,%34,%35}, b, 0, 1, 1, 1;\n}"
                 : "=f"(d[0]), "=f"(d[1]), "=f"(d[2]), "=f"(d[3]), "=f"(d[4]), "=f"(d[5]), "=f"(d[6]), "=f"(d[7]),
                   "=f"(e[0]), "=f"(e[1]), "=f"(e[2]), "=f"(e[3]), "=f"(e[4]), "=f"(e[5]), "=f"(e[6]), "=f"(e[7]), "=f"(e[8]), "=f"(e[9]), "=f"(e[10]), "=f"(e[11]), "=f"(e[12]), "=f"(e[13]), "=f"(e[14]), "=f"(e[15]), "=f"(e[16]), "=f"(e[17]), "=f"(e[18]), "=f"(e[19]), "=f"(e[20]), "=f"(e[21]), "=f"(e[22]), "=f"(e[23])
                 : "r"(a[0]), "r"(a[1]), "r"(a[2]), "r"(a[3]), "r"(bdesc));
}
__device__ __forceinline__ void wgmma_n64(float (&d)[8], float (&e)[24], const uint32_t (&a)[4], uint32_t bdesc) {
    asm volatile("{\n.reg .b64 b;\nmov.b64 b, {%36, " DESC_HI "};\n"
                 "wgmma.mma_async.sync.aligned.m64n64k16.f32.bf16.bf16 {%0,%1,%2,%3,%4,%5,%6,%7,%8,%9,%10,%11,%12,%13,%14,%15,%16,%17,%18,%19,%20,%21,%22,%23,%24,%25,%26,%27,%28,%29,%30,%31}, {%32,%33,%34,%35}, b, 1, 1, 1, 1;\n}"
                 : "+f"(d[0]), "+f"(d[1]), "+f"(d[2]), "+f"(d[3]), "+f"(d[4]), "+f"(d[5]), "+f"(d[6]), "+f"(d[7]),
                   "+f"(e[0]), "+f"(e[1]), "+f"(e[2]), "+f"(e[3]), "+f"(e[4]), "+f"(e[5]), "+f"(e[6]), "+f"(e[7]), "+f"(e[8]), "+f"(e[9]), "+f"(e[10]), "+f"(e[11]), "+f"(e[12]), "+f"(e[13]), "+f"(e[14]), "+f"(e[15]), "+f"(e[16]), "+f"(e[17]), "+f"(e[18]), "+f"(e[19]), "+f"(e[20]), "+f"(e[21]), "+f"(e[22]), "+f"(e[23])
                 : "r"(a[0]), "r"(a[1]), "r"(a[2]), "r"(a[3]), "r"(bdesc));
}
__device__ __forceinline__ void wgmma_n48_first(float (&e)[24], const uint32_t (&a)[4], uint32_t bdesc) {
    asm volatile("{\n.reg .b64 b;\nmov.b64 b, {%28, " DESC_HI "};\n"
                 "wgmma.mma_async.sync.aligned.m64n48k16.f32.bf16.bf16 {%0,%1,%2,%3,%4,%5,%6,%7,%8,%9,%10,%11,%12,%13,%14,%15,%16,%17,%18,%19,%20,%21,%22,%23}, {%24,%25,%26,%27}, b, 0, 1, 1, 1;\n}"
                 : "=f"(e[0]), "=f"(e[1]), "=f"(e[2]), "=f"(e[3]), "=f"(e[4]), "=f"(e[5]), "=f"(e[6]), "=f"(e[7]), "=f"(e[8]), "=f"(e[9]), "=f"(e[10]), "=f"(e[11]), "=f"(e[12]), "=f"(e[13]), "=f"(e[14]), "=f"(e[15]), "=f"(e[16]), "=f"(e[17]), "=f"(e[18]), "=f"(e[19]), "=f"(e[20]), "=f"(e[21]), "=f"(e[22]), "=f"(e[23])
                 : "r"(a[0]), "r"(a[1]), "r"(a[2]), "r"(a[3]), "r"(bdesc));
}
__device__ __forceinline__ void wgmma_n48(float (&e)[24], const uint32_t (&a)[4], uint32_t bdesc) {
    asm volatile("{\n.reg .b64 b;\nmov.b64 b, {%28, " DESC_HI "};\n"
                 "wgmma.mma_async.sync.aligned.m64n48k16.f32.bf16.bf16 {%0,%1,%2,%3,%4,%5,%6,%7,%8,%9,%10,%11,%12,%13,%14,%15,%16,%17,%18,%19,%20,%21,%22,%23}, {%24,%25,%26,%27}, b, 1, 1, 1, 1;\n}"
                 : "+f"(e[0]), "+f"(e[1]), "+f"(e[2]), "+f"(e[3]), "+f"(e[4]), "+f"(e[5]), "+f"(e[6]), "+f"(e[7]), "+f"(e[8]), "+f"(e[9]), "+f"(e[10]), "+f"(e[11]), "+f"(e[12]), "+f"(e[13]), "+f"(e[14]), "+f"(e[15]), "+f"(e[16]), "+f"(e[17]), "+f"(e[18]), "+f"(e[19]), "+f"(e[20]), "+f"(e[21]), "+f"(e[22]), "+f"(e[23])
                 : "r"(a[0]), "r"(a[1]), "r"(a[2]), "r"(a[3]), "r"(bdesc));
}
__device__ __forceinline__ void wgmma_n16_first(float (&d)[8], const uint32_t (&a)[4], uint32_t bdesc) {
    asm volatile("{\n.reg .b64 b;\nmov.b64 b, {%12, " DESC_HI "};\n"
                 "wgmma.mma_async.sync.aligned.m64n16k16.f32.bf16.bf16 {%0,%1,%2,%3,%4,%5,%6,%7}, {%8,%9,%10,%11}, b, 0, 1, 1, 1;\n}"
                 : "=f"(d[0]), "=f"(d[1]), "=f"(d[2]), "=f"(d[3]), "=f"(d[4]), "=f"(d[5]), "=f"(d[6]), "=f"(d[7])
                 : "r"(a[0]), "r"(a[1]), "r"(a[2]), "r"(a[3]), "r"(bdesc));
}
__device__ __forceinline__ void wgmma_n16(float (&d)[8], const uint32_t (&a)[4], uint32_t bdesc) {
    asm volatile("{\n.reg .b64 b;\nmov.b64 b, {%12, " DESC_HI "};\n"
                 "wgmma.mma_async.sync.aligned.m64n16k16.f32.bf16.bf16 {%0,%1,%2,%3,%4,%5,%6,%7}, {%8,%9,%10,%11}, b, 1, 1, 1, 1;\n}"
                 : "+f"(d[0]), "+f"(d[1]), "+f"(d[2]), "+f"(d[3]), "+f"(d[4]), "+f"(d[5]), "+f"(d[6]), "+f"(d[7])
                 : "r"(a[0]), "r"(a[1]), "r"(a[2]), "r"(a[3]), "r"(bdesc));
}

__device__ __forceinline__ void wgmma_n64_p(float (&d)[8], float (&e)[24], const uint32_t (&a)[4], uint32_t bdesc, int acc) {
    asm volatile("{\n.reg .pred p;\n.reg .b64 b;\nsetp.ne.b32 p, %37, 0;\nmov.b64 b, {%36, " DESC_HI "};\n"
                 "wgmma.mma_async.sync.aligned.m64n64k16.f32.bf16.bf16 {%0,%1,%2,%3,%4,%5,%6,%7,%8,%9,%10,%11,%12,%13,%14,%15,%16,%17,%18,%19,%20,%21,%22,%23,%24,%25,%26,%27,%28,%29,%30,%31}, {%32,%33,%34,%35}, b, p, 1, 1, 1;\n}"
                 : "+f"(d[0]), "+f"(d[1]), "+f"(d[2]), "+f"(d[3]), "+f"(d[4]), "+f"(d[5]), "+f"(d[6]), "+f"(d[7]),
                   "+f"(e[0]), "+f"(e[1]), "+f"(e[2]), "+f"(e[3]), "+f"(e[4]), "+f"(e[5]), "+f"(e[6]), "+f"(e[7]), "+f"(e[8]), "+f"(e[9]), "+f"(e[10]), "+f"(e[11]), "+f"(e[12]), "+f"(e[13]), "+f"(e[14]), "+f"(e[15]), "+f"(e[16]), "+f"(e[17]), "+f"(e[18]), "+f"(e[19]), "+f"(e[20]), "+f"(e[21]), "+f"(e[22]), "+f"(e[23])
                 : "r"(a[0]), "r"(a[1]), "r"(a[2]), "r"(a[3]), "r"(bdesc), "r"(acc));
}
__device__ __forceinline__ void wgmma_n16_p(float (&d)[8], const uint32_t (&a)[4], uint32_t bdesc, int acc) {
    asm volatile("{\n.reg .pred p;\n.reg .b64 b;\nsetp.ne.b32 p, %13, 0;\nmov.b64 b, {%12, " DESC_HI "};\n"
                 "wgmma.mma_async.sync.aligned.m64n16k16.f32.bf16.bf16 {%0,%1,%2,%3,%4,%5,%6,%7}, {%8,%9,%10,%11}, b, p, 1, 1, 1;\n}"
                 : "+f"(d[0]), "+f"(d[1]), "+f"(d[2]), "+f"(d[3]), "+f"(d[4]), "+f"(d[5]), "+f"(d[6]), "+f"(d[7])
                 : "r"(a[0]), "r"(a[1]), "r"(a[2]), "r"(a[3]), "r"(bdesc), "r"(acc));
}

__device__ __forceinline__ uint32_t edge_dist(uint32_t sxy, uint32_t sz, uint32_t dxy, uint32_t dz, uint32_t& rxy, uint32_t& rz) {
    rxy = hsub2(sxy, dxy);
    rz  = hsub2(sz, dz);
    uint32_t qxy = hmul2(rxy, rxy), qz = hmul2(rz, rz);
    float ss = rbf((bf_lo(qxy) + bf_hi(qxy)) + bf_lo(qz));
    float s2 = rbf(ss + 1e-8f);
    float d;
    asm("sqrt.approx.ftz.f32 %0, %1;" : "=f"(d) : "f"(s2));
    return pack_bf(d, 0.f) & 0xffffu;
}

__device__ __forceinline__ void load_pos(uint32_t sm_pos, int i, uint32_t& xy, uint32_t& z) {
    uint32_t a  = (sm_pos + 6u * (uint32_t)i) & ~3u;
    uint32_t w0 = lds32(a), w1 = lds32(a + 4);
    uint32_t sh = (uint32_t)i << 4;
    xy = __funnelshift_r(w0, w1, sh);
    z  = __funnelshift_r(w1, w1, sh);
}

__device__ __noinline__ float radial_value(float d, float f) {
    float arg = rbf(d * f);
    float sn  = rbf(sinf(arg));
    float rb  = rbf(__fdiv_rn(sn, d));
    float c   = rbf(cosf(rbf(__fdiv_rn(rbf(d * 3.14159265358979323846f), 5.0f))));
    float fc  = rbf(0.5f * rbf(c + 1.0f));
    return rb * fc;
}

__global__ void __launch_bounds__(NT, 1)
painn_kernel(const Params p, const __grid_constant__ CUtensorMap tmF, const __grid_constant__ CUtensorMap tmFs,
             const __grid_constant__ CUtensorMap tmSV, const __grid_constant__ CUtensorMap tmW1, const __grid_constant__ CUtensorMap tmW2) {
    extern __shared__ __align__(1024) uint8_t smem[];
    const uint32_t sb   = smem_u32(smem);
    const int tid  = threadIdx.x, lane = tid & 31, warp = __shfl_sync(0xffffffffu, tid >> 5, 0);
    const int cta  = blockIdx.x;
    const int g    = lane >> 2, t = lane & 3;
    int* binCnt = (int*)(smem + SM_BINCNT);
    int* binOff = (int*)(smem + SM_BINOFF);
    int* nCnt   = (int*)(smem + SM_NCNT);
    uint32_t* nInfo = (uint32_t*)(smem + SM_NINFO);
    volatile int* ctrl = (volatile int*)(smem + SM_CTRL);
    const uint32_t bar_pos = sb + SM_BARS, bar_mlp = bar_pos + 8, bar_rec = bar_pos + 16;
    const uint32_t bar_full = bar_pos + 32, bar_empty = bar_full + NCWG * MAX_STAGE * 8;
    const uint32_t bar_hfull = bar_empty + NCWG * MAX_STAGE * 8, bar_hempty = bar_hfull + 16;

    const int node0  = cta * p.npc;
    const int nnodes = max(0, min(p.npc, p.N - node0));

    STAMP(0);
    if (tid == 0) {
        mbar_init(bar_mlp, 1);
        asm volatile("fence.mbarrier_init.release.cluster;" ::: "memory");
        mbar_expect_tx(bar_mlp, 4u * MAX_NPC * 128u + 8192u + 24576u);
        tma_load(sb + P1_W1, &tmW1, 0, bar_mlp);
        tma_load3(sb + P1_SV, &tmSV, 0, node0, bar_mlp);
        tma_load(sb + P1_W2, &tmW2, 0, bar_mlp);
#pragma unroll
        for (int b = 1; b < 4; b++) tma_load3(sb + P1_SV + b * (MAX_NPC * 128), &tmSV, b, node0, bar_mlp);
    } else if (tid == 32) {
        mbar_init(bar_pos, 1);
        asm volatile("fence.mbarrier_init.release.cluster;" ::: "memory");
        uint32_t pos_bytes = (uint32_t)(p.N * 6 + 15) & ~15u;
        mbar_expect_tx(bar_pos, pos_bytes);
        bulk_g2s(sb + P1_POS, p.pos, pos_bytes, bar_pos);
    } else if (tid == 64) {
        mbar_init(bar_rec, 1);
        mbar_init(bar_hfull, 4); mbar_init(bar_hfull + 8, 4); mbar_init(bar_hempty, 4); mbar_init(bar_hempty + 8, 4);
        asm volatile("prefetch.tensormap [%0];" ::"l"(&tmF) : "memory");
        asm volatile("prefetch.tensormap [%0];" ::"l"(&tmFs) : "memory");
    } else if (tid >= 96 && tid < 96 + NCWG * MAX_STAGE) {
        mbar_init(bar_full + 8 * (tid - 96), 2);
        mbar_init(bar_empty + 8 * (tid - 96), 4);
    }
    unsigned bar_seen = 0;
    if (tid == 15 * 32) asm volatile("ld.relaxed.gpu.global.u32 %0, [%1];" : "=r"(bar_seen) : "l"(&g_bar) : "memory");
    const bool mlp_warp = warp >= 6;
    int4 s4[3], d4[3];
    const int q0 = cta * p.quads_per_cta;
    const int qend = min(q0 + p.quads_per_cta, p.E >> 2);
#pragma unroll
    for (int k = 0; k < 3; k++) {
        const int q = q0 + (k < 2 ? warp + 16 * k : 32 + warp) * 32 + lane;
        const bool ok = q < qend && (k < 2 || !mlp_warp);
        s4[k] = ok ? __ldg((const int4*)p.src + q) : make_int4(-1, -1, -1, -1);
        d4[k] = ok ? __ldg((const int4*)p.dst + q) : make_int4(0, 0, 0, 0);
    }
    if (tid < MAX_CTA) binCnt[tid] = 0;
    if (tid < MAX_NPC) nCnt[tid] = 0;
    if (tid < 16) ctrl[tid] = 0;
    if (tid >= 416 && tid < 416 + 48) {
        asm volatile("prefetch.global.L2 [%0];" ::"l"((const uint8_t*)p.wr + (tid - 416) * 128));
    }
    for (int i = P1_SEG / 16 + tid; i < P1_SV / 16; i += NT) sts128(sb + i * 16, make_uint4(0u, 0u, 0u, 0u));
    __syncthreads();

#pragma unroll
    for (int k = 0; k < 3; k++) {
        const int ss[4] = {s4[k].x, s4[k].y, s4[k].z, s4[k].w};
        const int dd[4] = {d4[k].x, d4[k].y, d4[k].z, d4[k].w};
        if (ss[0] >= 0) {
            uint32_t bin[4], rank[4];
#pragma unroll
            for (int j = 0; j < 4; j++) {
                bin[j]  = __umulhi((uint32_t)dd[j], p.npc_magic);
                rank[j] = (uint32_t)atomicAdd(&binCnt[bin[j]], 1);
            }
#pragma unroll
            for (int j = 0; j < 4; j++)
                if (rank[j] < SEG_W - 1)
                    sts32(sb + P1_SEG + (bin[j] * SEG_W + 1 + rank[j]) * 4, (uint32_t)ss[j] | (((uint32_t)dd[j] - bin[j] * (uint32_t)p.npc) << 16));
        }
    }
    STAMP(1);

    if (!mlp_warp) {
        const int rows_per = (TAB_ROWS + 1 + p.ncta - 1) / p.ncta;
        for (int i = tid; i < rows_per * 8; i += 6 * 32) {
            int row = cta * rows_per + (i >> 3), kp = i & 7;
            if (row <= TAB_ROWS) {
                uint32_t val = 0;
                if (row < TAB_ROWS) {
                    float d = __uint_as_float((D_MIN_BITS + row) << 16);
                    uint32_t f2 = __ldg((const uint32_t*)p.freqs + kp);
                    val = pack_bf(radial_value(d, bf_lo(f2)), radial_value(d, bf_hi(f2)));
                }
                ((uint32_t*)g_table)[row * 8 + kp] = val;
            }
        }
    } else {
        const int mt = (warp - 6) >> 1, hf = (warp - 6) & 1;
        if (mt * 16 < nnodes) {
            mbar_wait(bar_mlp, 0);
            STAMPT(10, 6 * 32);
            const int lrow = lane & 15, lch = lane >> 4;
            const uint32_t rowb = sb + P1_SV + (mt * 16 + lrow) * 128;
            const uint32_t key0 = lrow & 7;
            float acc[4][4];
#pragma unroll
            for (int i = 0; i < 4; i++) { acc[i][0] = acc[i][1] = acc[i][2] = acc[i][3] = 0.f; }
#pragma unroll
            for (int ks = 0; ks < 4; ks++) {
                uint32_t a[4];
                ldsm4(a, rowb + (((2 * ks + lch) ^ key0) << 4));
                const int kk = 16 * ks + lrow;
#pragma unroll
                for (int nt = 0; nt < 4; nt += 2) {
                    uint32_t b[4];
                    ldsm4t(b, sb + P1_W1 + kk * 128 + (((4 * hf + nt + lch) ^ (kk & 7)) << 4));
                    mma16816(acc[nt], a, b[0], b[1]);
                    mma16816(acc[nt + 1], a, b[2], b[3]);
                }
            }
            uint32_t hp[4][2];
#pragma unroll
            for (int i = 0; i < 4; i++) {
                float h[4];
#pragma unroll
                for (int q = 0; q < 4; q++) {
                    float x = rbf(acc[i][q]);
                    h[q] = __fdividef(x, 1.0f + __expf(-x));
                    acc[i][q] = 0.f;
                }
                hp[i][0] = pack_bf(h[0], h[1]);
                hp[i][1] = pack_bf(h[2], h[3]);
            }
            asm volatile("bar.sync %0, 64;" ::"r"(4 + mt) : "memory");
#pragma unroll
            for (int i = 0; i < 4; i += 2)
                stsm4(rowb + (((4 * hf + i + lch) ^ key0) << 4), hp[i][0], hp[i][1], hp[i + 1][0], hp[i + 1][1]);
            asm volatile("bar.sync %0, 64;" ::"r"(4 + mt) : "memory");
#pragma unroll
            for (int ks = 0; ks < 4; ks++) {
                uint32_t a[4];
                ldsm4(a, rowb + (((2 * ks + lch) ^ key0) << 4));
                const int line = 3 * (16 * ks + lrow) + 1;
#pragma unroll
                for (int nt = 0; nt < 4; nt += 2) {
                    uint32_t b[4];
                    ldsm4t(b, sb + P1_W2 + line * 128 + (((4 * hf + nt + lch) ^ (line & 7)) << 4));
                    mma16816(acc[nt], a, b[0], b[1]);
                    mma16816(acc[nt + 1], a, b[2], b[3]);
                }
            }
            uint32_t vq[2][3][4];
            const uint32_t vb = sb + P1_SV + (mt * 16 + g) * 128 + 4 * t;
#pragma unroll
            for (int rh = 0; rh < 2; rh++)
#pragma unroll
                for (int a = 0; a < 3; a++)
#pragma unroll
                    for (int i = 0; i < 4; i++) vq[rh][a][i] = lds32(vb + (a + 1) * (MAX_NPC * 128) + rh * 1024 + (((4 * hf + i) ^ g) << 4));
#pragma unroll
            for (int rh = 0; rh < 2; rh++)
#pragma unroll
                for (int a = 0; a < 3; a++)
#pragma unroll
                    for (int i = 0; i < 4; i++)
                        sts32(vb + (a + 1) * (MAX_NPC * 128) + rh * 1024 + (((4 * hf + i) ^ g) << 4),
                              hmul2(pack_bf(acc[i][2 * rh], acc[i][2 * rh + 1]), vq[rh][a][i]));
            fence_async_smem();
            asm volatile("bar.sync %0, 64;" ::"r"(4 + mt) : "memory");
            {
                const int r4 = mt * 16 + 8 * hf + 4 * (lane >> 2), comp = lane & 3;
                if (lane < 8 && r4 < nnodes) tma_store3(&tmFs, comp, node0 + r4, sb + P1_SV + comp * (MAX_NPC * 128) + r4 * 128);
            }
            asm volatile("cp.async.bulk.commit_group;" ::: "memory");
        }
        STAMPT(11, 6 * 32);
    }
    STAMP(2);
    __syncthreads();
    STAMP(3);
    if (tid < p.ncta) sts32(sb + P1_SEG + tid * SEG_W * 4, (uint32_t)binCnt[tid]);
    fence_async_smem();
    __syncthreads();
    if (tid == 0) {
        asm volatile("cp.async.bulk.global.shared::cta.bulk_group [%0], [%1], %2;"
                     ::"l"(g_seg + (size_t)cta * MAX_CTA * SEG_W), "r"(sb + P1_SEG), "r"((uint32_t)p.ncta * SEG_W * 4u) : "memory");
        asm volatile("cp.async.bulk.commit_group;" ::: "memory");
    }
    if (tid == 0 || (mlp_warp && lane < 8)) {
        asm volatile("cp.async.bulk.wait_group 0;" ::: "memory");
        asm volatile("fence.proxy.async;" ::: "memory");
    }

    __syncthreads();
    STAMP(4);
    if (tid == 0) asm volatile("red.add.release.gpu.global.u32 [%0], 1;" ::"l"(&g_bar) : "memory");
    uint32_t wp[3][4];
    if (warp >= 4 && warp < 8) {
        const uint16_t* w2 = (const uint16_t*)p.w2 + 16 * (warp & 3) + g;
#pragma unroll 2
        for (int mk = 0; mk < 8; mk++) {
            uint32_t f[4];
#pragma unroll
            for (int i = 0; i < 4; i++) {
                const uint16_t* q = w2 + (16 * (mk & 3) + 2 * t + 8 * (i >> 1)) * 192 + (mk >> 2) * 128 + 8 * (i & 1);
                f[i] = (uint32_t)__ldg(q) | ((uint32_t)__ldg(q + 192) << 16);
            }
            sts128(sb + SM_HT + (mk * 128 + (tid & 127)) * 16, make_uint4(f[0], f[1], f[2], f[3]));
        }
    }
    if (warp < 12) {
        const uint16_t* wr = (const uint16_t*)p.wr + 16 * (warp & 3) + g;
#pragma unroll
        for (int ty = 0; ty < 3; ty++) {
#pragma unroll
            for (int i = 0; i < 4; i++) {
                const uint16_t* q = wr + (8 * (i >> 1) + 2 * t) * 192 + ty * 64 + 8 * (i & 1);
                wp[ty][i] = (uint32_t)__ldg(q) | ((uint32_t)__ldg(q + 192) << 16);
            }
        }
    }
    if (tid == 15 * 32) {
        const unsigned target = (bar_seen / (unsigned)p.ncta + 1u) * (unsigned)p.ncta;
        unsigned cur;
        int spins = 0;
        do {
            asm volatile("ld.acquire.gpu.global.u32 %0, [%1];" : "=r"(cur) : "l"(&g_bar) : "memory");
        } while ((int)(cur - target) < 0 && ++spins < (1 << 24));
        mbar_expect_tx(bar_rec, (uint32_t)p.ncta * SEG_W * 4u);
    }
    __syncthreads();
    STAMP(5);

    {
        const int b = (lane << 4) | warp;
        if (lane < 9 && b < p.ncta) {
            asm volatile("fence.proxy.async;" ::: "memory");
            bulk_g2s(sb + P1_SEG + b * SEG_W * 4, g_seg + ((size_t)b * MAX_CTA + cta) * SEG_W, SEG_W * 4, bar_rec);
        }
    }
    mbar_wait(bar_pos, 0);
    mbar_wait(bar_rec, 0);
    STAMP(13);
    for (int b = 2 * warp + (lane >> 4); b < ((p.ncta + 1) & ~1); b += 32) {
        const uint32_t seg = sb + P1_SEG + b * SEG_W * 4;
        const int cnt = b < p.ncta ? (int)lds32(seg) : 0;
        if (cnt > SEG_W - 1) ctrl[1] = 1;
        const int n = min(cnt, SEG_W - 1), nmax = max(n, __shfl_xor_sync(0xffffffffu, n, 16));
        for (int j = lane & 15; j - (lane & 15) < nmax; j += 16) {
            bool act = false;
            uint4 rec = make_uint4(0u, 0u, 0u, 0u);
            if (j < n) {
                const uint32_t wd = lds32(seg + 4 + j * 4);
                const uint32_t s = wd & 0xffffu, dl = wd >> 16;
                uint32_t sxy, sz, dxy, dz, rxy, rz;
                load_pos(sb + P1_POS, (int)s, sxy, sz);
                load_pos(sb + P1_POS, node0 + (int)dl, dxy, dz);
                const uint32_t db = edge_dist(sxy, sz, dxy, dz, rxy, rz);
                act = db <= D_MAX_BITS;
                if (act) {
                    float inv;
                    asm("rcp.approx.ftz.f32 %0, %1;" : "=f"(inv) : "f"(__uint_as_float(db << 16)));
                    rec.x = s | ((db - D_MIN_BITS) << 16);
                    rec.y = pack_bf(bf_lo(rxy) * inv, bf_hi(rxy) * inv);
                    rec.z = __byte_perm(pack_bf(bf_lo(rz) * inv, 0.f), dl, 0x5410);
                    rec.w = (uint32_t)atomicAdd(&nCnt[dl], 1);
                }
            }
            const unsigned am = __ballot_sync(0xffffffffu, act);
            int base = 0;
            if (lane == 0 && am) base = atomicAdd((int*)&ctrl[8], __popc(am));
            base = __shfl_sync(0xffffffffu, base, 0) + __popc(am & ((1u << lane) - 1u));
            if (act) {
                if (base < STAGE_CAP) sts128(sb + P1_REC + base * 16, rec);
            }
        }
    }
    __syncthreads();
    const int total = ctrl[8];
    if (tid == 0 && total > STAGE_CAP) ctrl[1] = 1;
    if (warp == 0) {
        int c[3], s = 0;
#pragma unroll
        for (int i = 0; i < 3; i++) {
            int b = lane * 3 + i;
            c[i] = b < nnodes ? max(16, (nCnt[b] + 15) & ~15) : 0;
            s += c[i];
        }
        int x = s;
#pragma unroll
        for (int o = 1; o < 32; o <<= 1) { int y = __shfl_up_sync(0xffffffffu, x, o); if (lane >= o) x += y; }
        const int slots = __shfl_sync(0xffffffffu, x, 31);
        int off = x - s, below = 0;
#pragma unroll
        for (int i = 0; i < 3; i++) {
            int b = lane * 3 + i;
            if (b < nnodes) {
                nInfo[b] = (uint32_t)off | ((uint32_t)c[i] << 16);
                below += (2 * off + c[i] < slots);
            }
            off += c[i];
        }
        below = __reduce_add_sync(0xffffffffu, below);
        if (lane == 0) {
            ctrl[2] = below;
            ctrl[4] = slots;
            if (slots > SLOT_CAP) ctrl[1] = 1;
        }
    }
    __syncthreads();
    if (ctrl[1] == 0) {
        uint16_t* sid = (uint16_t*)(smem + SM_SID);
        uint2* meta = (uint2*)(smem + SM_META);
        for (int i = tid; i < total; i += 2 * NT) {
            const bool two = i + NT < total;
            const uint4 r = lds128(sb + P1_REC + i * 16);
            const uint4 q = two ? lds128(sb + P1_REC + (i + NT) * 16) : r;
            const int pos = (int)(lds32(sb + SM_NINFO + (r.z >> 16) * 4) & 0xffffu) + (int)r.w;
            const int pos2 = (int)(lds32(sb + SM_NINFO + (q.z >> 16) * 4) & 0xffffu) + (int)q.w;
            sid[pos]  = (uint16_t)((r.x & 0xffffu) << 2);
            meta[pos] = make_uint2(((r.x >> 16) << 5) | (r.z << 16), r.y);
            if (two) {
                sid[pos2]  = (uint16_t)((q.x & 0xffffu) << 2);
                meta[pos2] = make_uint2(((q.x >> 16) << 5) | (q.z << 16), q.y);
            }
        }
        if (tid >= NT - 128 && tid - (NT - 128) < nnodes) {
            const int b = tid - (NT - 128), split = ctrl[2];
            const int mid = split < nnodes ? (int)(nInfo[split] & 0xffffu) : ctrl[4];
            const int st = b >= split;
            const int mine = (int)(nInfo[b] & 0xffffu) + (int)(nInfo[b] >> 16) - (st ? mid : 0);
            int rank = st ? b - split : b;
            const int o0 = st ? 0 : split, o1 = st ? split : nnodes;
            for (int o = o0; o < o1; o++) {
                const int other = (int)(nInfo[o] & 0xffffu) + (int)(nInfo[o] >> 16) - (st ? 0 : mid);
                rank += st ? (other <= mine) : (other < mine);
            }
            smem[SM_ORDER + rank] = (uint8_t)(b | (st << 7));
        }
        for (int i = tid; i < nnodes * 16; i += NT) {
            int nl = i >> 4, c = nCnt[nl];
            int j = (c & ~15) + (i & 15);
            if (j >= c && (j < 16 || (c & 15))) {
                int pos = (int)(nInfo[nl] & 0xffffu) + j;
                sid[pos]  = 0xffffu;
                meta[pos] = make_uint2((uint32_t)TAB_ZERO << 5, 0u);
            }
        }
    }
    fence_async_smem();
    __syncthreads();
    STAMP(6);

    if (__shfl_sync(0xffffffffu, ctrl[1], 0) != 0) {
        float* acc = (float*)(smem + P1_POS);
        for (int i = tid; i < nnodes * 256; i += NT) acc[i] = 0.f;
        __syncthreads();
        const uint16_t* posu = (const uint16_t*)p.pos;
        const uint32_t* tabg = (const uint32_t*)g_table;
        const uint32_t* Fw = (const uint32_t*)g_F;
        for (int e0 = warp * 32; e0 < p.E; e0 += NT) {
            int e = e0 + lane;
            int s = 0, d = 0;
            uint32_t db = 0xffff, rxy = 0, rz = 0;
            bool act = false;
            if (e < p.E) {
                s = p.src[e]; d = p.dst[e];
                if (d >= node0 && d < node0 + nnodes) {
                    uint32_t sxy = posu[s * 3] | ((uint32_t)posu[s * 3 + 1] << 16), sz = posu[s * 3 + 2];
                    uint32_t dxy = posu[d * 3] | ((uint32_t)posu[d * 3 + 1] << 16), dz = posu[d * 3 + 2];
                    db  = edge_dist(sxy, sz, dxy, dz, rxy, rz);
                    act = db <= D_MAX_BITS;
                }
            }
            unsigned m = __ballot_sync(0xffffffffu, act);
            while (m) {
                int l = __ffs(m) - 1;
                m &= m - 1;
                int es = __shfl_sync(0xffffffffu, s, l), ed = __shfl_sync(0xffffffffu, d, l);
                uint32_t edb = __shfl_sync(0xffffffffu, db, l), exy = __shfl_sync(0xffffffffu, rxy, l), ez = __shfl_sync(0xffffffffu, rz, l);
                float inv = 1.0f / __uint_as_float(edb << 16);
                float rh[3] = {rbf(bf_lo(exy) * inv), rbf(bf_hi(exy) * inv), rbf(bf_lo(ez) * inv)};
                const uint32_t* fr = Fw + (size_t)es * 128 + lane;
                const uint32_t fh = __ldcg(fr);
                const uint32_t q[3] = {__ldcg(fr + 32), __ldcg(fr + 64), __ldcg(fr + 96)};
                float ps0 = 0.f, ps1 = 0.f, pr0 = 0.f, pr1 = 0.f;
                for (int j2 = 0; j2 < 32; j2++) {
                    uint32_t hj = __shfl_sync(0xffffffffu, fh, j2);
                    uint32_t a0 = *(const uint32_t*)(p.w2 + (2 * j2) * 192 + 2 * lane), a1 = *(const uint32_t*)(p.w2 + (2 * j2 + 1) * 192 + 2 * lane);
                    uint32_t b0 = *(const uint32_t*)(p.w2 + (2 * j2) * 192 + 128 + 2 * lane), b1 = *(const uint32_t*)(p.w2 + (2 * j2 + 1) * 192 + 128 + 2 * lane);
                    ps0 += bf_lo(hj) * bf_lo(a0) + bf_hi(hj) * bf_lo(a1);
                    ps1 += bf_lo(hj) * bf_hi(a0) + bf_hi(hj) * bf_hi(a1);
                    pr0 += bf_lo(hj) * bf_lo(b0) + bf_hi(hj) * bf_lo(b1);
                    pr1 += bf_lo(hj) * bf_hi(b0) + bf_hi(hj) * bf_hi(b1);
                }
                float ws0 = 0.f, ws1 = 0.f, wv0 = 0.f, wv1 = 0.f, wr0 = 0.f, wr1 = 0.f;
                for (int k2 = 0; k2 < 8; k2++) {
                    uint32_t rk2 = __ldcg(tabg + (edb - D_MIN_BITS) * 8 + k2);
#pragma unroll
                    for (int h = 0; h < 2; h++) {
                        float rv = h ? bf_hi(rk2) : bf_lo(rk2);
                        const __nv_bfloat16* wrow = p.wr + (2 * k2 + h) * 192 + 2 * lane;
                        uint32_t a = *(const uint32_t*)wrow, b = *(const uint32_t*)(wrow + 64), c = *(const uint32_t*)(wrow + 128);
                        ws0 += rv * bf_lo(a); ws1 += rv * bf_hi(a);
                        wv0 += rv * bf_lo(b); wv1 += rv * bf_hi(b);
                        wr0 += rv * bf_lo(c); wr1 += rv * bf_hi(c);
                    }
                }
                float* a = acc + (ed - node0) * 256 + 2 * lane;
                atomicAdd(a, ps0 * ws0); atomicAdd(a + 1, ps1 * ws1);
#pragma unroll
                for (int c = 0; c < 3; c++) {
                    atomicAdd(a + 64 * (c + 1), wv0 * bf_lo(q[c]) + pr0 * wr0 * rh[c]);
                    atomicAdd(a + 64 * (c + 1) + 1, wv1 * bf_hi(q[c]) + pr1 * wr1 * rh[c]);
                }
            }
        }
        __syncthreads();
        for (int i = tid; i < nnodes * 128; i += NT) {
            uint32_t r = *(const uint32_t*)(p.sv + (size_t)node0 * 256 + 2 * i);
            *(uint32_t*)(p.out + (size_t)node0 * 256 + 2 * i) = pack_bf(bf_lo(r) + acc[2 * i], bf_hi(r) + acc[2 * i + 1]);
        }
        return;
    }

    const int slots = __reduce_max_sync(0xffffffffu, ctrl[4]);
    const int split = __reduce_max_sync(0xffffffffu, ctrl[2]);
    const int nstage = slots <= SLOT_CAP4 ? 6 : 5;
    const uint32_t ring = sb + (nstage == 6 ? SM_RING4 : SM_RING3);
    const int mid = __reduce_max_sync(0xffffffffu, split < nnodes ? (int)(nInfo[split] & 0xffffu) : slots) >> 4;
    const int wgi = warp >> 2, w = warp & 3;
    constexpr uint32_t EMPTY_OFF = NCWG * MAX_STAGE * 8;
    if (wgi == 3) {
        const int sc = w >> 1, r = w & 1;
        const int g0 = (sc == 0 ? 0 : mid) + r, g1 = sc == 0 ? mid : slots >> 4;
        const uint32_t ring_wg = ring + sc * nstage * STAGE_B, full_wg = bar_full + sc * MAX_STAGE * 8;
        const int e = lane >> 1, half = lane & 1;
        const uint32_t coef_off = e * 128 + ((half ^ (e & 7)) << 4);
        const int vrot = (e & 3) ^ ((e >> 1) & 3);
        const uint8_t* tab = (const uint8_t*)g_table + half * 16;
        int stage = r;
        uint32_t phase = 1;
        uint32_t ma = sb + SM_META + (g0 * 16 + e) * 8, ida = sb + SM_SID + g0 * 32;
        uint2 m = make_uint2(0u, 0u);
        uint4 tv = make_uint4(0u, 0u, 0u, 0u), ia = tv, ib = tv;
        if (g0 < g1) {
            m  = lds64(ma);
            ia = lds128(ida);
            ib = lds128(ida + 16);
            tv = __ldg((const uint4*)(tab + (m.x & 0xffffu)));
        }
        for (int left = (g1 - g0 + 1) >> 1; left > 0; left--) {
            const uint32_t st = ring_wg + stage * STAGE_B, fb = full_wg + stage * 8;
            uint4 o[4];
            {
                const uint32_t mul[4] = {0x3f803f80u, __byte_perm(m.y, 0, 0x1010), __byte_perm(m.y, 0, 0x3232), __byte_perm(m.x, 0, 0x3232)};
#pragma unroll
                for (int j = 0; j < 4; j++) {
                    const int v = j ^ vrot;
                    const uint32_t lo = (v & 1) ? mul[1] : mul[0], hi = (v & 1) ? mul[3] : mul[2];
                    const uint32_t mm = (v & 2) ? hi : lo;
                    o[j] = make_uint4(hmul2(tv.x, mm), hmul2(tv.y, mm), hmul2(tv.z, mm), hmul2(tv.w, mm));
                }
            }
            ma += 256; ida += 64;
            if (left > 1) m = lds64(ma);
            mbar_wait(fb + EMPTY_OFF, phase);
            uint32_t leader;
            asm volatile("{\n.reg .pred p;\nelect.sync _|p, 0xffffffff;\nselp.u32 %0, 1, 0, p;\n}" : "=r"(leader));
            if (leader) {
                const uint32_t id2[8] = {ia.x, ia.y, ia.z, ia.w, ib.x, ib.y, ib.z, ib.w};
                const uint32_t rows = st + 2048;
                if ((ib.w >> 16) != 0xffffu) {
                    mbar_expect_tx(fb, 16 * 512);
#pragma unroll
                    for (int i = 0; i < 8; i++) {
                        tma_load(rows + (2 * i) * 640, &tmF, (int)(id2[i] & 0xffffu), fb);
                        tma_load(rows + (2 * i + 1) * 640, &tmF, (int)(id2[i] >> 16), fb);
                    }
                } else {
                    int nv = 0;
#pragma unroll
                    for (int i = 0; i < 8; i++) nv += ((id2[i] & 0xffffu) != 0xffffu) + ((id2[i] >> 16) != 0xffffu);
                    mbar_expect_tx(fb, (uint32_t)nv * 512u);
#pragma unroll
                    for (int q = 0; q < 4; q++) {
                        if (4 * q + 4 <= nv) {
                            tma_load(rows + (4 * q) * 640, &tmF, (int)(id2[2 * q] & 0xffffu), fb);
                            tma_load(rows + (4 * q + 1) * 640, &tmF, (int)(id2[2 * q] >> 16), fb);
                            tma_load(rows + (4 * q + 2) * 640, &tmF, (int)(id2[2 * q + 1] & 0xffffu), fb);
                            tma_load(rows + (4 * q + 3) * 640, &tmF, (int)(id2[2 * q + 1] >> 16), fb);
                        } else {
                            if (4 * q < nv)     tma_load(rows + (4 * q) * 640, &tmF, (int)(id2[2 * q] & 0xffffu), fb);
                            if (4 * q + 1 < nv) tma_load(rows + (4 * q + 1) * 640, &tmF, (int)(id2[2 * q] >> 16), fb);
                            if (4 * q + 2 < nv) tma_load(rows + (4 * q + 2) * 640, &tmF, (int)(id2[2 * q + 1] & 0xffffu), fb);
                        }
                    }
                }
            }
            __syncwarp();
            if (left > 1) {
                ia = lds128(ida);
                ib = lds128(ida + 16);
                tv = __ldg((const uint4*)(tab + (m.x & 0xffffu)));
            }
            const uint32_t a = st + coef_off;
#pragma unroll
            for (int j = 0; j < 4; j++) sts128(a ^ ((j ^ vrot) << 5), o[j]);
            fence_async_smem();
            __syncwarp();
            mbar_arrive_elected(fb);
            stage += 2;
            if (stage >= nstage) { stage -= nstage; phase ^= 1; }
        }
    } else if (wgi == 2) {
        uint32_t wA[2][4][4];
#pragma unroll
        for (int mk = 0; mk < 8; mk++) {
            const uint4 q = lds128(sb + SM_HT + (mk * 128 + (tid & 127)) * 16);
            wA[mk >> 2][mk & 3][0] = q.x; wA[mk >> 2][mk & 3][1] = q.y; wA[mk >> 2][mk & 3][2] = q.z; wA[mk >> 2][mk & 3][3] = q.w;
        }
        __syncwarp();
        mbar_arrive_elected(bar_hempty);
        mbar_arrive_elected(bar_hempty + 8);
        const uint32_t lane_off = (uint32_t)node0 * 512u + t * 128 + w * 32 + (g & 1) * 16 + (g >> 1) * 4;
        uint32_t hpar = 0;
        float zs[8], zv[24], pvv[6], pr[4][2];
        auto start = [&](int ent) {
            const int c = ent >> 7;
            mbar_wait(bar_hfull + c * 8, (hpar >> c) & 1);
            hpar ^= 1u << c;
            const uint32_t dht = desc_lo(sb + SM_HT + c * 8192);
            wg_fence();
            wgmma_n16_first(zs, wA[0][0], dht);
            wgmma_n48_first(zv, wA[1][0], dht + 2);
#pragma unroll
            for (int ks = 1; ks < 4; ks++) {
                wgmma_n16(zs, wA[0][ks], dht + ks * 128);
                wgmma_n48(zv, wA[1][ks], dht + ks * 128 + 2);
            }
            wg_commit();
        };
        auto side = [&](int ent) {
            const int c = ent >> 7;
            const uint32_t pa = sb + SM_PV + c * 3072 + (tid & 127) * 8;
            const uint2 a0 = lds64(pa), a1 = lds64(pa + 1024), a2 = lds64(pa + 2048);
            pvv[0] = __uint_as_float(a0.x); pvv[1] = __uint_as_float(a0.y); pvv[2] = __uint_as_float(a1.x);
            pvv[3] = __uint_as_float(a1.y); pvv[4] = __uint_as_float(a2.x); pvv[5] = __uint_as_float(a2.y);
            __syncwarp();
            mbar_arrive_elected(bar_hempty + c * 8);
        };
        auto weigh = [&]() {
#pragma unroll
            for (int i = 0; i < 12; i++) asm volatile("" : "+r"(wp[i >> 2][i & 3]));
            pr[0][0] = bf_lo(wp[0][0]) * zs[0] + bf_hi(wp[0][0]) * zs[1] + bf_lo(wp[0][2]) * zs[4] + bf_hi(wp[0][2]) * zs[5];
            pr[0][1] = bf_lo(wp[0][1]) * zs[2] + bf_hi(wp[0][1]) * zs[3] + bf_lo(wp[0][3]) * zs[6] + bf_hi(wp[0][3]) * zs[7];
#pragma unroll
            for (int a = 0; a < 3; a++) {
                const float* y = zv + 8 * a;
                pr[a + 1][0] = pvv[2 * a] + bf_lo(wp[2][0]) * y[0] + bf_hi(wp[2][0]) * y[1] + bf_lo(wp[2][2]) * y[4] + bf_hi(wp[2][2]) * y[5];
                pr[a + 1][1] = pvv[2 * a + 1] + bf_lo(wp[2][1]) * y[2] + bf_hi(wp[2][1]) * y[3] + bf_lo(wp[2][3]) * y[6] + bf_hi(wp[2][3]) * y[7];
            }
            asm volatile("" : "+f"(pr[0][0]), "+f"(pr[0][1]), "+f"(pr[1][0]), "+f"(pr[1][1]), "+f"(pr[2][0]), "+f"(pr[2][1]), "+f"(pr[3][0]), "+f"(pr[3][1]) :: "memory");
        };
        auto finish = [&](int ent, uint32_t resid) {
            const bool hi2 = t & 2, hi1 = t & 1, odd = g & 1;
            float ka0 = hi2 ? pr[2][0] : pr[0][0], ka1 = hi2 ? pr[2][1] : pr[0][1];
            float kb0 = hi2 ? pr[3][0] : pr[1][0], kb1 = hi2 ? pr[3][1] : pr[1][1];
            float sa0 = hi2 ? pr[0][0] : pr[2][0], sa1 = hi2 ? pr[0][1] : pr[2][1];
            float sb0 = hi2 ? pr[1][0] : pr[3][0], sb1 = hi2 ? pr[1][1] : pr[3][1];
            ka0 += __shfl_xor_sync(0xffffffffu, sa0, 2); ka1 += __shfl_xor_sync(0xffffffffu, sa1, 2);
            kb0 += __shfl_xor_sync(0xffffffffu, sb0, 2); kb1 += __shfl_xor_sync(0xffffffffu, sb1, 2);
            float k0 = hi1 ? kb0 : ka0, k1 = hi1 ? kb1 : ka1;
            float s0 = hi1 ? ka0 : kb0, s1 = hi1 ? ka1 : kb1;
            k0 += __shfl_xor_sync(0xffffffffu, s0, 1);
            k1 += __shfl_xor_sync(0xffffffffu, s1, 1);
            const float other = __shfl_xor_sync(0xffffffffu, odd ? k0 : k1, 4);
            const float lo = odd ? other : k0, hi = odd ? k1 : other;
            *(uint32_t*)((uint8_t*)p.out + (lane_off + (uint32_t)(ent & 127) * 512u)) = pack_bf(bf_lo(resid) + lo, bf_hi(resid) + hi);
        };
        auto entry = [&](int i) -> int { return __reduce_max_sync(0xffffffffu, (int)smem[SM_ORDER + i]); };
        auto load_resid = [&](int ent) -> uint32_t { return __ldg((const uint32_t*)((const uint8_t*)p.sv + (lane_off + (uint32_t)(ent & 127) * 512u))); };
        if (nnodes > 0) {
            int cur = entry(0), nxt = entry(1);
            uint32_t resid = load_resid(cur);
            start(cur);
#pragma unroll 1
            for (int i = 1; i < nnodes; i++) {
                wg_wait0();
                side(cur);
                weigh();
                start(nxt);
                finish(cur, resid);
                cur = nxt;
                resid = load_resid(cur);
                nxt = entry(i + 1);
            }
            wg_wait0();
            side(cur);
            weigh();
            finish(cur, resid);
        }
    } else {
        const int wg = wgi;
        uint32_t aoff[4];
        {
            const int e = (lane & 7) + 8 * (lane >> 4), ch = 2 * w + ((lane >> 3) & 1);
#pragma unroll
            for (int b = 0; b < 4; b++) aoff[b] = 2048 + e * 640 + b * 128 + ((ch ^ ((5 * e + b) & 7)) << 4);
        }
        const uint32_t stsm_a = sb + SM_HT + wg * 8192 + (16 * w + (lane & 15)) * 128 + (((lane >> 4) ^ (lane & 7)) << 4);
        const uint32_t pv_a = sb + SM_PV + wg * 3072 + (tid & 127) * 8;
        const uint32_t ring_wg = ring + wg * nstage * STAGE_B;
        const uint32_t full_wg = bar_full + wg * MAX_STAGE * 8;

        float ys[8], yv[24], dQ[3][8];
        uint32_t A0[4][4], A1[4][4];
#pragma unroll
        for (int i = 0; i < 24; i++) yv[i] = 0.f;
#pragma unroll
        for (int i = 0; i < 8; i++) { ys[i] = 0.f; dQ[0][i] = 0.f; dQ[1][i] = 0.f; dQ[2][i] = 0.f; }
        int left = wg == 0 ? mid : (slots >> 4) - mid;
        int fstage = 0;
        uint32_t fphase = 0, fst = ring_wg, fbar = full_wg, hphase = 0;
        uint32_t ninfo_a = sb + SM_NINFO + (wg == 0 ? 0 : split) * 4;
        int gi = 0, G = __reduce_max_sync(0xffffffffu, (int)(lds32(ninfo_a) >> 20));

        auto fetch = [&](uint32_t (&A)[4][4], uint32_t& bd, uint32_t& eb) {
            mbar_wait(fbar, fphase);
#pragma unroll
            for (int b = 0; b < 4; b++) ldsm4t(A[b], fst + aoff[b]);
            bd = desc_lo(fst);
            eb = fbar + EMPTY_OFF;
            fst += STAGE_B; fbar += 8;
            if (++fstage == nstage) { fstage = 0; fphase ^= 1; fst = ring_wg; fbar = full_wg; }
        };
        auto step = [&](uint32_t (&Ac)[4][4], uint32_t bdc, uint32_t ebc, uint32_t (&An)[4][4], uint32_t& bdn, uint32_t& ebn) {
            wg_fence();
            wgmma_n64_p(ys, yv, Ac[0], bdc, gi);
            wgmma_n16_p(dQ[0], Ac[1], bdc, gi);
            wgmma_n16_p(dQ[1], Ac[2], bdc, gi);
            wgmma_n16_p(dQ[2], Ac[3], bdc, gi);
            wg_commit();
            if (--left > 0) fetch(An, bdn, ebn);
            const bool last = ++gi == G;
            uint32_t info_next = 0;
            if (last) { ninfo_a += 4; info_next = lds32(ninfo_a); }
            wg_wait0();
            mbar_arrive_elected(ebc);
            if (last) {
                mbar_wait(bar_hempty + wg * 8, hphase);
                hphase ^= 1;
                stsm4(stsm_a, pack_bf(ys[0], ys[1]), pack_bf(ys[2], ys[3]), pack_bf(ys[4], ys[5]), pack_bf(ys[6], ys[7]));
#pragma unroll
                for (int i = 0; i < 6; i += 2) {
                    stsm4(stsm_a ^ ((i + 2) << 4),
                          pack_bf(yv[4 * i], yv[4 * i + 1]), pack_bf(yv[4 * i + 2], yv[4 * i + 3]),
                          pack_bf(yv[4 * i + 4], yv[4 * i + 5]), pack_bf(yv[4 * i + 6], yv[4 * i + 7]));
                }
#pragma unroll
                for (int i = 0; i < 4; i++) asm volatile("" : "+r"(wp[1][i]));
#pragma unroll
                for (int a = 0; a < 3; a++) {
                    const float* q = dQ[a];
                    const float p0 = bf_lo(wp[1][0]) * q[0] + bf_hi(wp[1][0]) * q[1] + bf_lo(wp[1][2]) * q[4] + bf_hi(wp[1][2]) * q[5];
                    const float p1 = bf_lo(wp[1][1]) * q[2] + bf_hi(wp[1][1]) * q[3] + bf_lo(wp[1][3]) * q[6] + bf_hi(wp[1][3]) * q[7];
                    asm volatile("st.shared.v2.f32 [%0], {%1, %2};" ::"r"(pv_a + a * 1024), "f"(p0), "f"(p1) : "memory");
                }
                fence_async_smem();
                __syncwarp();
                mbar_arrive_elected(bar_hfull + wg * 8);
                G = __reduce_max_sync(0xffffffffu, (int)(info_next >> 20));
                gi = 0;
            }
        };
        if (left > 0) {
            uint32_t bd0, eb0, bd1 = 0, eb1 = 0;
            fetch(A0, bd0, eb0);
            while (true) {
                step(A0, bd0, eb0, A1, bd1, eb1);
                if (left <= 0) break;
                step(A1, bd1, eb1, A0, bd0, eb0);
                if (left <= 0) break;
            }
        }
    }
    STAMP(8);
}

typedef CUresult (*EncodeFn)(CUtensorMap*, CUtensorMapDataType, cuuint32_t, void*, const cuuint64_t*, const cuuint64_t*,
                             const cuuint32_t*, const cuuint32_t*, CUtensorMapInterleave, CUtensorMapSwizzle,
                             CUtensorMapL2promotion, CUtensorMapFloatOOBfill);

void make_map(EncodeFn enc, CUtensorMap* tm, const void* base, uint64_t lines, uint32_t box) {
    cuuint64_t gd[2] = {64, lines};
    cuuint64_t gs[1] = {128};
    cuuint32_t bd[2] = {64, box};
    cuuint32_t es[2] = {1, 1};
    enc(tm, CU_TENSOR_MAP_DATA_TYPE_BFLOAT16, 2, const_cast<void*>(base), gd, gs, bd, es, CU_TENSOR_MAP_INTERLEAVE_NONE,
        CU_TENSOR_MAP_SWIZZLE_128B, CU_TENSOR_MAP_L2_PROMOTION_L2_128B, CU_TENSOR_MAP_FLOAT_OOB_FILL_NONE);
}

void make_map3(EncodeFn enc, CUtensorMap* tm, const void* base, uint64_t nodes, uint32_t box) {
    cuuint64_t gd[3] = {64, 4, nodes};
    cuuint64_t gs[2] = {128, 512};
    cuuint32_t bd[3] = {64, 1, box};
    cuuint32_t es[3] = {1, 1, 1};
    enc(tm, CU_TENSOR_MAP_DATA_TYPE_BFLOAT16, 3, const_cast<void*>(base), gd, gs, bd, es, CU_TENSOR_MAP_INTERLEAVE_NONE,
        CU_TENSOR_MAP_SWIZZLE_128B, CU_TENSOR_MAP_L2_PROMOTION_L2_128B, CU_TENSOR_MAP_FLOAT_OOB_FILL_NONE);
}

}

extern "C" void kernel_launch(void* const* d_in, const int* in_sizes, int n_in, void* d_out, int out_size) {
    (void)n_in; (void)out_size;
    static int n_sm = 0;
    static EncodeFn enc = nullptr;
    static void* f_ptr = nullptr;
    if (n_sm == 0) {
        int dev = 0;
        cudaGetDevice(&dev);
        cudaDeviceGetAttribute(&n_sm, cudaDevAttrMultiProcessorCount, dev);
        cudaFuncSetAttribute(painn_kernel, cudaFuncAttributeMaxDynamicSharedMemorySize, SM_TOTAL);
        void* fn = nullptr;
        cudaDriverEntryPointQueryResult qr;
        cudaGetDriverEntryPoint("cuTensorMapEncodeTiled", &fn, cudaEnableDefault, &qr);
        enc = (EncodeFn)fn;
        cudaGetSymbolAddress(&f_ptr, g_F);
    }
    Params p;
    p.sv    = (const __nv_bfloat16*)d_in[0];
    p.pos   = (const __nv_bfloat16*)d_in[1];
    p.src   = (const int*)d_in[2];
    p.dst   = (const int*)d_in[3];
    p.freqs = (const __nv_bfloat16*)d_in[4];
    p.w1    = (const __nv_bfloat16*)d_in[5];
    p.w2    = (const __nv_bfloat16*)d_in[6];
    p.wr    = (const __nv_bfloat16*)d_in[7];
    p.out   = (__nv_bfloat16*)d_out;
    p.N = in_sizes[1] / 3;
    p.E = in_sizes[2];
    p.ncta = n_sm < MAX_CTA ? n_sm : MAX_CTA;
    p.npc = ((p.N + p.ncta - 1) / p.ncta + 3) & ~3;
    p.npc_magic = (uint32_t)(0x100000000ull / (uint32_t)p.npc) + 1u;
    p.quads_per_cta = ((p.E >> 2) + p.ncta - 1) / p.ncta;
    if (!enc || p.N > MAX_N || p.npc > MAX_NPC || (p.E & 3) || p.quads_per_cta > MAX_ROUNDS * 32) return;

    CUtensorMap tmF, tmFs, tmSV, tmW1, tmW2;
    make_map(enc, &tmF, f_ptr, (uint64_t)p.N * 4, 4);
    make_map3(enc, &tmFs, f_ptr, (uint64_t)p.N, 4);
    make_map3(enc, &tmSV, p.sv, (uint64_t)p.N, MAX_NPC);
    make_map(enc, &tmW1, p.w1, 64, 64);
    make_map(enc, &tmW2, p.w2, 192, 192);

    cudaLaunchConfig_t cfg = {};
    cfg.gridDim = dim3(p.ncta);
    cfg.blockDim = dim3(NT);
    cfg.dynamicSmemBytes = SM_TOTAL;
    cfg.stream = cudaStreamPerThread;
    cudaLaunchAttribute attr[1];
    attr[0].id = cudaLaunchAttributeCooperative;
    attr[0].val.cooperative = 1;
    cfg.attrs = attr;
    cfg.numAttrs = 1;
    cudaLaunchKernelEx(&cfg, painn_kernel, p, tmF, tmFs, tmSV, tmW1, tmW2);
}
```

```cpp
#include <cuda_runtime.h>
#include <cuda.h>
#include <cuda_bf16.h>
#include <stdint.h>

namespace {

constexpr int NT        = 512;
constexpr int NCWG      = 2;
constexpr int MAX_N     = 10240;
constexpr int MAX_CTA   = 144;
constexpr int MAX_NPC   = 80;
constexpr int MAX_ROUNDS = 38;
constexpr int REC_CAP   = MAX_ROUNDS * 128;
constexpr int SEG_W     = 72;
constexpr int SLOT_CAP  = 6144;
constexpr int MAX_STAGE = 6;
constexpr int STAGE_B   = 12288;

constexpr uint32_t D_MIN_BITS = 0x38D2;
constexpr uint32_t D_MAX_BITS = 0x409C;
constexpr int TAB_ROWS  = (int)(D_MAX_BITS - D_MIN_BITS) + 1;
constexpr int TAB_ZERO  = TAB_ROWS;
constexpr int TAB_BYTES = (TAB_ROWS + 1) * 32;

constexpr int SM_BINCNT = 0;
constexpr int SM_BINOFF = SM_BINCNT + MAX_CTA * 4;
constexpr int SM_NCNT   = SM_BINOFF + MAX_CTA * 4;
constexpr int SM_NINFO  = SM_NCNT + MAX_NPC * 4;
constexpr int SM_ORDER  = SM_NINFO + (MAX_NPC + 1) * 4;
constexpr int SM_CTRL   = SM_ORDER + MAX_NPC + 12;
constexpr int SM_BARS   = SM_CTRL + 64;
constexpr int SM_SID    = 2048 + 256;
constexpr int SM_META   = SM_SID + SLOT_CAP * 2;
constexpr int SM_TOTAL  = 232448;
constexpr int SM_HT     = (SM_TOTAL - 3 * 8192) / 1024 * 1024;
constexpr int SM_PV     = SM_HT + 2 * 8192;
constexpr int SM_RING4  = SM_HT - NCWG * 6 * STAGE_B;
constexpr int SM_RING3  = SM_HT - NCWG * 5 * STAGE_B;
constexpr int SLOT_CAP4 = (SM_RING4 - SM_META) / 8;
constexpr int P1_POS    = 3072;
constexpr int P1_SEG    = P1_POS + 61440;
constexpr int P1_REC    = P1_SEG + MAX_CTA * SEG_W * 4;
constexpr int P1_SV     = 142336;
constexpr int P1_W1     = P1_SV + 4 * MAX_NPC * 128;
constexpr int P1_W2     = P1_W1 + 8192;
constexpr int P1_END    = P1_W2 + 8192;
constexpr int STAGE_CAP = (SM_HT - P1_REC) / 16;
static_assert(SM_BARS + (8 + 2 * NCWG * MAX_STAGE) * 8 <= SM_SID, "misc block");
static_assert(SM_BARS + 256 <= P1_POS, "misc block");
static_assert(P1_END <= SM_TOTAL && P1_SV % 1024 == 0 && P1_REC <= P1_SV && P1_REC % 16 == 0, "phase 1 overlay");
static_assert(SM_META + SLOT_CAP * 8 <= SM_RING3, "CSR");
static_assert(SM_RING4 % 1024 == 0 && SM_RING3 % 1024 == 0 && SM_HT % 1024 == 0, "alignment");
static_assert(SM_BARS % 8 == 0 && SM_META % 8 == 0 && SM_CTRL % 4 == 0, "alignment");
static_assert(MAX_N * 6 <= 61440, "pos");
static_assert(SM_SID + MAX_NPC * 1024 <= SM_TOTAL, "slow path accumulators");

__device__ __align__(1024) uint4 g_F[MAX_N * 32];
__device__ __align__(128) uint32_t g_seg[MAX_CTA * MAX_CTA * SEG_W];
__device__ uint4    g_table[(TAB_BYTES + 15) / 16];
__device__ unsigned g_bar;
#define STAMP(k)
#define STAMPT(k, T)
#define ITS(k)

struct Params {
    const __nv_bfloat16* sv;
    const __nv_bfloat16* pos;
    const int*           src;
    const int*           dst;
    const __nv_bfloat16* freqs;
    const __nv_bfloat16* w1;
    const __nv_bfloat16* w2;
    const __nv_bfloat16* wr;
    __nv_bfloat16*       out;
    int N, E, ncta, npc;
    uint32_t npc_magic;
    int quads_per_cta;
};

__device__ __forceinline__ uint32_t smem_u32(const void* p) { return (uint32_t)__cvta_generic_to_shared(p); }
__device__ __forceinline__ float bf_lo(uint32_t v) { return __uint_as_float(v << 16); }
__device__ __forceinline__ float bf_hi(uint32_t v) { return __uint_as_float(v & 0xffff0000u); }
__device__ __forceinline__ float bf_u16(uint16_t v) { return __uint_as_float((uint32_t)v << 16); }
__device__ __forceinline__ uint32_t pack_bf(float lo, float hi) {
    uint32_t r;
    asm("cvt.rn.bf16x2.f32 %0, %1, %2;" : "=r"(r) : "f"(hi), "f"(lo));
    return r;
}
__device__ __forceinline__ float rbf(float x) { return bf_lo(pack_bf(x, 0.f)); }
__device__ __forceinline__ uint32_t hmul2(uint32_t a, uint32_t b) {
    uint32_t r;
    asm("mul.rn.bf16x2 %0, %1, %2;" : "=r"(r) : "r"(a), "r"(b));
    return r;
}
__device__ __forceinline__ uint32_t hsub2(uint32_t a, uint32_t b) {
    uint32_t r;
    asm("sub.rn.bf16x2 %0, %1, %2;" : "=r"(r) : "r"(a), "r"(b));
    return r;
}
__device__ __forceinline__ uint32_t lds32(uint32_t a) { uint32_t v; asm volatile("ld.shared.u32 %0, [%1];" : "=r"(v) : "r"(a)); return v; }
__device__ __forceinline__ uint32_t lds16(uint32_t a) { uint16_t v; asm volatile("ld.shared.u16 %0, [%1];" : "=h"(v) : "r"(a)); return v; }
__device__ __forceinline__ uint2 lds64(uint32_t a) { uint2 v; asm volatile("ld.shared.v2.u32 {%0,%1}, [%2];" : "=r"(v.x), "=r"(v.y) : "r"(a)); return v; }
__device__ __forceinline__ uint4 lds128(uint32_t a) { uint4 v; asm volatile("ld.shared.v4.u32 {%0,%1,%2,%3}, [%4];" : "=r"(v.x), "=r"(v.y), "=r"(v.z), "=r"(v.w) : "r"(a)); return v; }
__device__ __forceinline__ void sts32(uint32_t a, uint32_t v) { asm volatile("st.shared.u32 [%0], %1;" ::"r"(a), "r"(v) : "memory"); }
__device__ __forceinline__ void sts128(uint32_t a, uint4 v) { asm volatile("st.shared.v4.u32 [%0], {%1,%2,%3,%4};" ::"r"(a), "r"(v.x), "r"(v.y), "r"(v.z), "r"(v.w) : "memory"); }
__device__ __forceinline__ void mbar_init(uint32_t bar, int cnt) { asm volatile("mbarrier.init.shared::cta.b64 [%0], %1;" ::"r"(bar), "r"(cnt) : "memory"); }
__device__ __forceinline__ void mbar_expect_tx(uint32_t bar, uint32_t bytes) { asm volatile("mbarrier.arrive.expect_tx.shared::cta.b64 _, [%0], %1;" ::"r"(bar), "r"(bytes) : "memory"); }
__device__ __forceinline__ void mbar_arrive(uint32_t bar) { asm volatile("mbarrier.arrive.shared::cta.b64 _, [%0];" ::"r"(bar) : "memory"); }
__device__ __forceinline__ void mbar_wait(uint32_t bar, uint32_t parity) {
    asm volatile("{\n.reg .pred p;\n.reg .u32 c;\n"
                 "mbarrier.try_wait.parity.shared::cta.b64 p, [%0], %1;\n"
                 "@p bra DONE_%=;\n"
                 "mov.u32 c, 0;\n"
                 "LOOP_%=:\n"
                 "mbarrier.try_wait.parity.shared::cta.b64 p, [%0], %1;\n"
                 "@p bra DONE_%=;\n"
                 "add.u32 c, c, 1;\n"
                 "setp.lt.u32 p, c, 4194304;\n"
                 "@p bra LOOP_%=;\n"
                 "DONE_%=:\n}"
                 ::"r"(bar), "r"(parity) : "memory");
}
__device__ __forceinline__ void mbar_arrive_elected(uint32_t bar) {
    asm volatile("{\n.reg .pred p;\nelect.sync _|p, 0xffffffff;\n@p mbarrier.arrive.shared::cta.b64 _, [%0];\n}" ::"r"(bar) : "memory");
}
__device__ __forceinline__ void bulk_g2s(uint32_t dst, const void* src, uint32_t bytes, uint32_t bar) {
    asm volatile("cp.async.bulk.shared::cluster.global.mbarrier::complete_tx::bytes [%0], [%1], %2, [%3];"
                 ::"r"(dst), "l"(src), "r"(bytes), "r"(bar) : "memory");
}
__device__ __forceinline__ void cp_async16(uint32_t dst, const void* src) {
    asm volatile("cp.async.cg.shared.global [%0], [%1], 16;" ::"r"(dst), "l"(src) : "memory");
}
__device__ __forceinline__ void tma_load(uint32_t dst, const CUtensorMap* tm, int line, uint32_t bar) {
    asm volatile("cp.async.bulk.tensor.2d.shared::cluster.global.mbarrier::complete_tx::bytes [%0], [%1, {%3, %4}], [%2];"
                 ::"r"(dst), "l"(tm), "r"(bar), "r"(0), "r"(line) : "memory");
}
__device__ __forceinline__ void tma_load3(uint32_t dst, const CUtensorMap* tm, int comp, int node, uint32_t bar) {
    asm volatile("cp.async.bulk.tensor.3d.shared::cluster.global.mbarrier::complete_tx::bytes [%0], [%1, {%3, %4, %5}], [%2];"
                 ::"r"(dst), "l"(tm), "r"(bar), "r"(0), "r"(comp), "r"(node) : "memory");
}
__device__ __forceinline__ void tma_store3(const CUtensorMap* tm, int comp, int node, uint32_t src) {
    asm volatile("cp.async.bulk.tensor.3d.global.shared::cta.bulk_group [%0, {%2, %3, %4}], [%1];"
                 ::"l"(tm), "r"(src), "r"(0), "r"(comp), "r"(node) : "memory");
}
__device__ __forceinline__ void fence_async_smem() { asm volatile("fence.proxy.async.shared::cta;" ::: "memory"); }
__device__ __forceinline__ void named_barrier(int id) { asm volatile("bar.sync %0, 128;" ::"r"(id) : "memory"); }
__device__ __forceinline__ void ldsm4(uint32_t (&r)[4], uint32_t a) {
    asm volatile("ldmatrix.sync.aligned.m8n8.x4.shared.b16 {%0,%1,%2,%3}, [%4];" : "=r"(r[0]), "=r"(r[1]), "=r"(r[2]), "=r"(r[3]) : "r"(a) : "memory");
}
__device__ __forceinline__ void ldsm4t(uint32_t (&r)[4], uint32_t a) {
    asm volatile("ldmatrix.sync.aligned.m8n8.x4.trans.shared.b16 {%0,%1,%2,%3}, [%4];" : "=r"(r[0]), "=r"(r[1]), "=r"(r[2]), "=r"(r[3]) : "r"(a) : "memory");
}
__device__ __forceinline__ void stsm4(uint32_t a, uint32_t r0, uint32_t r1, uint32_t r2, uint32_t r3) {
    asm volatile("stmatrix.sync.aligned.m8n8.x4.shared.b16 [%0], {%1,%2,%3,%4};" ::"r"(a), "r"(r0), "r"(r1), "r"(r2), "r"(r3) : "memory");
}
__device__ __forceinline__ void mma16816(float (&c)[4], const uint32_t (&a)[4], uint32_t b0, uint32_t b1) {
    asm volatile("mma.sync.aligned.m16n8k16.row.col.f32.bf16.bf16.f32 {%0,%1,%2,%3}, {%4,%5,%6,%7}, {%8,%9}, {%0,%1,%2,%3};"
                 : "+f"(c[0]), "+f"(c[1]), "+f"(c[2]), "+f"(c[3])
                 : "r"(a[0]), "r"(a[1]), "r"(a[2]), "r"(a[3]), "r"(b0), "r"(b1));
}

__device__ __forceinline__ uint32_t desc_lo(uint32_t saddr) { return ((saddr & 0x3FFFF) >> 4) | (1u << 16); }
#define DESC_HI "0x40000040"
__device__ __forceinline__ void wg_fence() { asm volatile("wgmma.fence.sync.aligned;" ::: "memory"); }
__device__ __forceinline__ void wg_commit() { asm volatile("wgmma.commit_group.sync.aligned;" ::: "memory"); }
__device__ __forceinline__ void wg_wait0() { asm volatile("wgmma.wait_group.sync.aligned 0;" ::: "memory"); }
__device__ __forceinline__ void wg_wait1() { asm volatile("wgmma.wait_group.sync.aligned 1;" ::: "memory"); }

__device__ __forceinline__ void wgmma_n64_first(float (&d)[8], float (&e)[24], const uint32_t (&a)[4], uint32_t bdesc) {
    asm volatile("{\n.reg .b64 b;\nmov.b64 b, {%36, " DESC_HI "};\n"
                 "wgmma.mma_async.sync.aligned.m64n64k16.f32.bf16.bf16 {%0,%1,%2,%3,%4,%5,%6,%7,%8,%9,%10,%11,%12,%13,%14,%15,%16,%17,%18,%19,%20,%21,%22,%23,%24,%25,%26,%27,%28,%29,%30,%31}, {%32,%33,%34,%35}, b, 0, 1, 1, 1;\n}"
                 : "=f"(d[0]), "=f"(d[1]), "=f"(d[2]), "=f"(d[3]), "=f"(d[4]), "=f"(d[5]), "=f"(d[6]), "=f"(d[7]),
                   "=f"(e[0]), "=f"(e[1]), "=f"(e[2]), "=f"(e[3]), "=f"(e[4]), "=f"(e[5]), "=f"(e[6]), "=f"(e[7]), "=f"(e[8]), "=f"(e[9]), "=f"(e[10]), "=f"(e[11]), "=f"(e[12]), "=f"(e[13]), "=f"(e[14]), "=f"(e[15]), "=f"(e[16]), "=f"(e[17]), "=f"(e[18]), "=f"(e[19]), "=f"(e[20]), "=f"(e[21]), "=f"(e[22]), "=f"(e[23])
                 : "r"(a[0]), "r"(a[1]), "r"(a[2]), "r"(a[3]), "r"(bdesc));
}
__device__ __forceinline__ void wgmma_n64(float (&d)[8], float (&e)[24], const uint32_t (&a)[4], uint32_t bdesc) {
    asm volatile("{\n.reg .b64 b;\nmov.b64 b, {%36, " DESC_HI "};\n"
                 "wgmma.mma_async.sync.aligned.m64n64k16.f32.bf16.bf16 {%0,%1,%2,%3,%4,%5,%6,%7,%8,%9,%10,%11,%12,%13,%14,%15,%16,%17,%18,%19,%20,%21,%22,%23,%24,%25,%26,%27,%28,%29,%30,%31}, {%32,%33,%34,%35}, b, 1, 1, 1, 1;\n}"
                 : "+f"(d[0]), "+f"(d[1]), "+f"(d[2]), "+f"(d[3]), "+f"(d[4]), "+f"(d[5]), "+f"(d[6]), "+f"(d[7]),
                   "+f"(e[0]), "+f"(e[1]), "+f"(e[2]), "+f"(e[3]), "+f"(e[4]), "+f"(e[5]), "+f"(e[6]), "+f"(e[7]), "+f"(e[8]), "+f"(e[9]), "+f"(e[10]), "+f"(e[11]), "+f"(e[12]), "+f"(e[13]), "+f"(e[14]), "+f"(e[15]), "+f"(e[16]), "+f"(e[17]), "+f"(e[18]), "+f"(e[19]), "+f"(e[20]), "+f"(e[21]), "+f"(e[22]), "+f"(e[23])
                 : "r"(a[0]), "r"(a[1]), "r"(a[2]), "r"(a[3]), "r"(bdesc));
}
__device__ __forceinline__ void wgmma_n48_first(float (&e)[24], const uint32_t (&a)[4], uint32_t bdesc) {
    asm volatile("{\n.reg .b64 b;\nmov.b64 b, {%28, " DESC_HI "};\n"
                 "wgmma.mma_async.sync.aligned.m64n48k16.f32.bf16.bf16 {%0,%1,%2,%3,%4,%5,%6,%7,%8,%9,%10,%11,%12,%13,%14,%15,%16,%17,%18,%19,%20,%21,%22,%23}, {%24,%25,%26,%27}, b, 0, 1, 1, 1;\n}"
                 : "=f"(e[0]), "=f"(e[1]), "=f"(e[2]), "=f"(e[3]), "=f"(e[4]), "=f"(e[5]), "=f"(e[6]), "=f"(e[7]), "=f"(e[8]), "=f"(e[9]), "=f"(e[10]), "=f"(e[11]), "=f"(e[12]), "=f"(e[13]), "=f"(e[14]), "=f"(e[15]), "=f"(e[16]), "=f"(e[17]), "=f"(e[18]), "=f"(e[19]), "=f"(e[20]), "=f"(e[21]), "=f"(e[22]), "=f"(e[23])
                 : "r"(a[0]), "r"(a[1]), "r"(a[2]), "r"(a[3]), "r"(bdesc));
}
__device__ __forceinline__ void wgmma_n48(float (&e)[24], const uint32_t (&a)[4], uint32_t bdesc) {
    asm volatile("{\n.reg .b64 b;\nmov.b64 b, {%28, " DESC_HI "};\n"
                 "wgmma.mma_async.sync.aligned.m64n48k16.f32.bf16.bf16 {%0,%1,%2,%3,%4,%5,%6,%7,%8,%9,%10,%11,%12,%13,%14,%15,%16,%17,%18,%19,%20,%21,%22,%23}, {%24,%25,%26,%27}, b, 1, 1, 1, 1;\n}"
                 : "+f"(e[0]), "+f"(e[1]), "+f"(e[2]), "+f"(e[3]), "+f"(e[4]), "+f"(e[5]), "+f"(e[6]), "+f"(e[7]), "+f"(e[8]), "+f"(e[9]), "+f"(e[10]), "+f"(e[11]), "+f"(e[12]), "+f"(e[13]), "+f"(e[14]), "+f"(e[15]), "+f"(e[16]), "+f"(e[17]), "+f"(e[18]), "+f"(e[19]), "+f"(e[20]), "+f"(e[21]), "+f"(e[22]), "+f"(e[23])
                 : "r"(a[0]), "r"(a[1]), "r"(a[2]), "r"(a[3]), "r"(bdesc));
}
__device__ __forceinline__ void wgmma_n16_first(float (&d)[8], const uint32_t (&a)[4], uint32_t bdesc) {
    asm volatile("{\n.reg .b64 b;\nmov.b64 b, {%12, " DESC_HI "};\n"
                 "wgmma.mma_async.sync.aligned.m64n16k16.f32.bf16.bf16 {%0,%1,%2,%3,%4,%5,%6,%7}, {%8,%9,%10,%11}, b, 0, 1, 1, 1;\n}"
                 : "=f"(d[0]), "=f"(d[1]), "=f"(d[2]), "=f"(d[3]), "=f"(d[4]), "=f"(d[5]), "=f"(d[6]), "=f"(d[7])
                 : "r"(a[0]), "r"(a[1]), "r"(a[2]), "r"(a[3]), "r"(bdesc));
}
__device__ __forceinline__ void wgmma_n16(float (&d)[8], const uint32_t (&a)[4], uint32_t bdesc) {
    asm volatile("{\n.reg .b64 b;\nmov.b64 b, {%12, " DESC_HI "};\n"
                 "wgmma.mma_async.sync.aligned.m64n16k16.f32.bf16.bf16 {%0,%1,%2,%3,%4,%5,%6,%7}, {%8,%9,%10,%11}, b, 1, 1, 1, 1;\n}"
                 : "+f"(d[0]), "+f"(d[1]), "+f"(d[2]), "+f"(d[3]), "+f"(d[4]), "+f"(d[5]), "+f"(d[6]), "+f"(d[7])
                 : "r"(a[0]), "r"(a[1]), "r"(a[2]), "r"(a[3]), "r"(bdesc));
}

__device__ __forceinline__ void wgmma_n64_p(float (&d)[8], float (&e)[24], const uint32_t (&a)[4], uint32_t bdesc, int acc) {
    asm volatile("{\n.reg .pred p;\n.reg .b64 b;\nsetp.ne.b32 p, %37, 0;\nmov.b64 b, {%36, " DESC_HI "};\n"
                 "wgmma.mma_async.sync.aligned.m64n64k16.f32.bf16.bf16 {%0,%1,%2,%3,%4,%5,%6,%7,%8,%9,%10,%11,%12,%13,%14,%15,%16,%17,%18,%19,%20,%21,%22,%23,%24,%25,%26,%27,%28,%29,%30,%31}, {%32,%33,%34,%35}, b, p, 1, 1, 1;\n}"
                 : "+f"(d[0]), "+f"(d[1]), "+f"(d[2]), "+f"(d[3]), "+f"(d[4]), "+f"(d[5]), "+f"(d[6]), "+f"(d[7]),
                   "+f"(e[0]), "+f"(e[1]), "+f"(e[2]), "+f"(e[3]), "+f"(e[4]), "+f"(e[5]), "+f"(e[6]), "+f"(e[7]), "+f"(e[8]), "+f"(e[9]), "+f"(e[10]), "+f"(e[11]), "+f"(e[12]), "+f"(e[13]), "+f"(e[14]), "+f"(e[15]), "+f"(e[16]), "+f"(e[17]), "+f"(e[18]), "+f"(e[19]), "+f"(e[20]), "+f"(e[21]), "+f"(e[22]), "+f"(e[23])
                 : "r"(a[0]), "r"(a[1]), "r"(a[2]), "r"(a[3]), "r"(bdesc), "r"(acc));
}
__device__ __forceinline__ void wgmma_n16_p(float (&d)[8], const uint32_t (&a)[4], uint32_t bdesc, int acc) {
    asm volatile("{\n.reg .pred p;\n.reg .b64 b;\nsetp.ne.b32 p, %13, 0;\nmov.b64 b, {%12, " DESC_HI "};\n"
                 "wgmma.mma_async.sync.aligned.m64n16k16.f32.bf16.bf16 {%0,%1,%2,%3,%4,%5,%6,%7}, {%8,%9,%10,%11}, b, p, 1, 1, 1;\n}"
                 : "+f"(d[0]), "+f"(d[1]), "+f"(d[2]), "+f"(d[3]), "+f"(d[4]), "+f"(d[5]), "+f"(d[6]), "+f"(d[7])
                 : "r"(a[0]), "r"(a[1]), "r"(a[2]), "r"(a[3]), "r"(bdesc), "r"(acc));
}

__device__ __forceinline__ uint32_t edge_dist(uint32_t sxy, uint32_t sz, uint32_t dxy, uint32_t dz, uint32_t& rxy, uint32_t& rz) {
    rxy = hsub2(sxy, dxy);
    rz  = hsub2(sz, dz);
    uint32_t qxy = hmul2(rxy, rxy), qz = hmul2(rz, rz);
    float ss = rbf((bf_lo(qxy) + bf_hi(qxy)) + bf_lo(qz));
    float s2 = rbf(ss + 1e-8f);
    float d;
    asm("sqrt.approx.ftz.f32 %0, %1;" : "=f"(d) : "f"(s2));
    return pack_bf(d, 0.f) & 0xffffu;
}

__device__ __forceinline__ void load_pos(uint32_t sm_pos, int i, uint32_t& xy, uint32_t& z) {
    uint32_t a  = (sm_pos + 6u * (uint32_t)i) & ~3u;
    uint32_t w0 = lds32(a), w1 = lds32(a + 4);
    uint32_t sh = (uint32_t)i << 4;
    xy = __funnelshift_r(w0, w1, sh);
    z  = __funnelshift_r(w1, w1, sh);
}

__device__ __noinline__ float radial_value(float d, float f) {
    float arg = rbf(d * f);
    float sn  = rbf(sinf(arg));
    float rb  = rbf(__fdiv_rn(sn, d));
    float c   = rbf(cosf(rbf(__fdiv_rn(rbf(d * 3.14159265358979323846f), 5.0f))));
    float fc  = rbf(0.5f * rbf(c + 1.0f));
    return rb * fc;
}

__global__ void __launch_bounds__(NT, 1)
painn_kernel(const Params p, const __grid_constant__ CUtensorMap tmF, const __grid_constant__ CUtensorMap tmFs) {
    extern __shared__ __align__(1024) uint8_t smem[];
    const uint32_t sb   = smem_u32(smem);
    const int tid  = threadIdx.x, lane = tid & 31, warp = __shfl_sync(0xffffffffu, tid >> 5, 0);
    const int cta  = blockIdx.x;
    const int g    = lane >> 2, t = lane & 3;
    int* binCnt = (int*)(smem + SM_BINCNT);
    int* binOff = (int*)(smem + SM_BINOFF);
    int* nCnt   = (int*)(smem + SM_NCNT);
    uint32_t* nInfo = (uint32_t*)(smem + SM_NINFO);
    volatile int* ctrl = (volatile int*)(smem + SM_CTRL);
    const uint32_t bar_pos = sb + SM_BARS, bar_mlp = bar_pos + 8, bar_rec = bar_pos + 16;
    const uint32_t bar_full = bar_pos + 32, bar_empty = bar_full + NCWG * MAX_STAGE * 8;
    const uint32_t bar_hfull = bar_empty + NCWG * MAX_STAGE * 8, bar_hempty = bar_hfull + 16;

    const int node0  = cta * p.npc;
    const int nnodes = max(0, min(p.npc, p.N - node0));

    STAMP(0);
    if (tid == 32) {
        mbar_init(bar_pos, 1);
        asm volatile("fence.mbarrier_init.release.cluster;" ::: "memory");
        uint32_t pos_bytes = (uint32_t)(p.N * 6 + 15) & ~15u;
        mbar_expect_tx(bar_pos, pos_bytes);
        bulk_g2s(sb + P1_POS, p.pos, pos_bytes, bar_pos);
    } else if (tid == 64) {
        mbar_init(bar_rec, 1);
        mbar_init(bar_hfull, 4); mbar_init(bar_hfull + 8, 4); mbar_init(bar_hempty, 4); mbar_init(bar_hempty + 8, 4);
        asm volatile("prefetch.tensormap [%0];" ::"l"(&tmF) : "memory");
        asm volatile("prefetch.tensormap [%0];" ::"l"(&tmFs) : "memory");
    } else if (tid >= 96 && tid < 96 + NCWG * MAX_STAGE) {
        mbar_init(bar_full + 8 * (tid - 96), 2);
        mbar_init(bar_empty + 8 * (tid - 96), 4);
    }
    unsigned bar_seen = 0;
    if (tid == 15 * 32) asm volatile("ld.relaxed.gpu.global.u32 %0, [%1];" : "=r"(bar_seen) : "l"(&g_bar) : "memory");
    const bool mlp_warp = warp >= 6;
    int4 s4[3], d4[3];
    const int q0 = cta * p.quads_per_cta;
    const int qend = min(q0 + p.quads_per_cta, p.E >> 2);
#pragma unroll
    for (int k = 0; k < 3; k++) {
        const int q = q0 + (k < 2 ? warp + 16 * k : 32 + warp) * 32 + lane;
        const bool ok = q < qend && (k < 2 || !mlp_warp);
        s4[k] = ok ? __ldg((const int4*)p.src + q) : make_int4(-1, -1, -1, -1);
        d4[k] = ok ? __ldg((const int4*)p.dst + q) : make_int4(0, 0, 0, 0);
    }
    for (int i = tid; i < nnodes * 32; i += NT) {
        const int r = i >> 5, b = (i >> 3) & 3, c = i & 7;
        cp_async16(sb + P1_SV + b * (MAX_NPC * 128) + r * 128 + ((c ^ (r & 7)) << 4), (const uint8_t*)p.sv + (size_t)node0 * 512 + i * 16);
    }
    for (int i = tid; i < 1024; i += NT) {
        const int m = i >> 9, k = (i >> 3) & 63, c = i & 7;
        cp_async16(sb + P1_W1 + m * 8192 + k * 128 + ((c ^ (k & 7)) << 4),
                   m == 0 ? (const uint8_t*)p.w1 + k * 128 + c * 16 : (const uint8_t*)p.w2 + k * 384 + 128 + c * 16);
    }
    asm volatile("cp.async.commit_group;" ::: "memory");
    if (tid < MAX_CTA) binCnt[tid] = 0;
    if (tid < MAX_NPC) nCnt[tid] = 0;
    if (tid < 16) ctrl[tid] = 0;
    if (tid >= 416 && tid < 416 + 48) {
        asm volatile("prefetch.global.L2 [%0];" ::"l"((const uint8_t*)p.wr + (tid - 416) * 128));
    }
    for (int i = P1_SEG / 16 + tid; i < P1_SV / 16; i += NT) sts128(sb + i * 16, make_uint4(0u, 0u, 0u, 0u));
    for (int i = tid; i < 4 * (MAX_NPC - nnodes) * 8; i += NT)
        sts128(sb + P1_SV + (i / ((MAX_NPC - nnodes) * 8)) * (MAX_NPC * 128) + nnodes * 128 + (i % ((MAX_NPC - nnodes) * 8)) * 16, make_uint4(0u, 0u, 0u, 0u));
    for (int i = P1_END / 16 + tid; i < SM_HT / 16; i += NT) sts128(sb + i * 16, make_uint4(0u, 0u, 0u, 0u));
    __syncthreads();

#pragma unroll
    for (int k = 0; k < 3; k++) {
        const int ss[4] = {s4[k].x, s4[k].y, s4[k].z, s4[k].w};
        const int dd[4] = {d4[k].x, d4[k].y, d4[k].z, d4[k].w};
        if (ss[0] >= 0) {
            uint32_t bin[4], rank[4];
#pragma unroll
            for (int j = 0; j < 4; j++) {
                bin[j]  = __umulhi((uint32_t)dd[j], p.npc_magic);
                rank[j] = (uint32_t)atomicAdd(&binCnt[bin[j]], 1);
            }
#pragma unroll
            for (int j = 0; j < 4; j++)
                if (rank[j] < SEG_W - 1)
                    sts32(sb + P1_SEG + (bin[j] * SEG_W + 1 + rank[j]) * 4, (uint32_t)ss[j] | (((uint32_t)dd[j] - bin[j] * (uint32_t)p.npc) << 16));
        }
    }
    asm volatile("cp.async.wait_group 0;" ::: "memory");
    __syncthreads();
    STAMP(1);

    if (!mlp_warp) {
        const int rows_per = (TAB_ROWS + 1 + p.ncta - 1) / p.ncta;
        for (int i = tid; i < rows_per * 8; i += 6 * 32) {
            int row = cta * rows_per + (i >> 3), kp = i & 7;
            if (row <= TAB_ROWS) {
                uint32_t val = 0;
                if (row < TAB_ROWS) {
                    float d = __uint_as_float((D_MIN_BITS + row) << 16);
                    uint32_t f2 = __ldg((const uint32_t*)p.freqs + kp);
                    val = pack_bf(radial_value(d, bf_lo(f2)), radial_value(d, bf_hi(f2)));
                }
                ((uint32_t*)g_table)[row * 8 + kp] = val;
            }
        }
    } else {
        const int mt = (warp - 6) >> 1, hf = (warp - 6) & 1;
        if (mt * 16 < nnodes) {
            STAMPT(10, 6 * 32);
            const int lrow = lane & 15, lch = lane >> 4;
            const uint32_t rowb = sb + P1_SV + (mt * 16 + lrow) * 128;
            const uint32_t key0 = lrow & 7;
            float acc[4][4];
#pragma unroll
            for (int i = 0; i < 4; i++) { acc[i][0] = acc[i][1] = acc[i][2] = acc[i][3] = 0.f; }
#pragma unroll
            for (int ks = 0; ks < 4; ks++) {
                uint32_t a[4];
                ldsm4(a, rowb + (((2 * ks + lch) ^ key0) << 4));
                const int kk = 16 * ks + lrow;
#pragma unroll
                for (int nt = 0; nt < 4; nt += 2) {
                    uint32_t b[4];
                    ldsm4t(b, sb + P1_W1 + kk * 128 + (((4 * hf + nt + lch) ^ (kk & 7)) << 4));
                    mma16816(acc[nt], a, b[0], b[1]);
                    mma16816(acc[nt + 1], a, b[2], b[3]);
                }
            }
            uint32_t hp[4][2];
#pragma unroll
            for (int i = 0; i < 4; i++) {
                float h[4];
#pragma unroll
                for (int q = 0; q < 4; q++) {
                    float x = rbf(acc[i][q]);
                    h[q] = __fdividef(x, 1.0f + __expf(-x));
                    acc[i][q] = 0.f;
                }
                hp[i][0] = pack_bf(h[0], h[1]);
                hp[i][1] = pack_bf(h[2], h[3]);
            }
            asm volatile("bar.sync %0, 64;" ::"r"(4 + mt) : "memory");
#pragma unroll
            for (int i = 0; i < 4; i += 2)
                stsm4(rowb + (((4 * hf + i + lch) ^ key0) << 4), hp[i][0], hp[i][1], hp[i + 1][0], hp[i + 1][1]);
            asm volatile("bar.sync %0, 64;" ::"r"(4 + mt) : "memory");
#pragma unroll
            for (int ks = 0; ks < 4; ks++) {
                uint32_t a[4];
                ldsm4(a, rowb + (((2 * ks + lch) ^ key0) << 4));
                const int kk = 16 * ks + lrow;
#pragma unroll
                for (int nt = 0; nt < 4; nt += 2) {
                    uint32_t b[4];
                    ldsm4t(b, sb + P1_W2 + kk * 128 + (((4 * hf + nt + lch) ^ (kk & 7)) << 4));
                    mma16816(acc[nt], a, b[0], b[1]);
                    mma16816(acc[nt + 1], a, b[2], b[3]);
                }
            }
            uint32_t vq[2][3][4];
            const uint32_t vb = sb + P1_SV + (mt * 16 + g) * 128 + 4 * t;
#pragma unroll
            for (int rh = 0; rh < 2; rh++)
#pragma unroll
                for (int a = 0; a < 3; a++)
#pragma unroll
                    for (int i = 0; i < 4; i++) vq[rh][a][i] = lds32(vb + (a + 1) * (MAX_NPC * 128) + rh * 1024 + (((4 * hf + i) ^ g) << 4));
#pragma unroll
            for (int rh = 0; rh < 2; rh++)
#pragma unroll
                for (int a = 0; a < 3; a++)
#pragma unroll
                    for (int i = 0; i < 4; i++)
                        sts32(vb + (a + 1) * (MAX_NPC * 128) + rh * 1024 + (((4 * hf + i) ^ g) << 4),
                              hmul2(pack_bf(acc[i][2 * rh], acc[i][2 * rh + 1]), vq[rh][a][i]));
            fence_async_smem();
            asm volatile("bar.sync %0, 64;" ::"r"(4 + mt) : "memory");
            {
                const int r4 = mt * 16 + 8 * hf + 4 * (lane >> 2), comp = lane & 3;
                if (lane < 8 && r4 < nnodes) tma_store3(&tmFs, comp, node0 + r4, sb + P1_SV + comp * (MAX_NPC * 128) + r4 * 128);
            }
            asm volatile("cp.async.bulk.commit_group;" ::: "memory");
        }
        STAMPT(11, 6 * 32);
    }
    STAMP(2);
    __syncthreads();
    STAMP(3);
    if (tid < p.ncta) sts32(sb + P1_SEG + tid * SEG_W * 4, (uint32_t)binCnt[tid]);
    fence_async_smem();
    __syncthreads();
    if (tid == 0) {
        asm volatile("cp.async.bulk.global.shared::cta.bulk_group [%0], [%1], %2;"
                     ::"l"(g_seg + (size_t)cta * MAX_CTA * SEG_W), "r"(sb + P1_SEG), "r"((uint32_t)p.ncta * SEG_W * 4u) : "memory");
        asm volatile("cp.async.bulk.commit_group;" ::: "memory");
    }
    if (tid == 0 || (mlp_warp && lane < 8)) {
        asm volatile("cp.async.bulk.wait_group 0;" ::: "memory");
        asm volatile("fence.proxy.async;" ::: "memory");
    }

    __syncthreads();
    STAMP(4);
    if (tid == 0) asm volatile("red.add.release.gpu.global.u32 [%0], 1;" ::"l"(&g_bar) : "memory");
    uint32_t wp[3][4];
    if (warp >= 4 && warp < 8) {
        const uint16_t* w2 = (const uint16_t*)p.w2 + 16 * (warp & 3) + g;
#pragma unroll 2
        for (int mk = 0; mk < 8; mk++) {
            uint32_t f[4];
#pragma unroll
            for (int i = 0; i < 4; i++) {
                const uint16_t* q = w2 + (16 * (mk & 3) + 2 * t + 8 * (i >> 1)) * 192 + (mk >> 2) * 128 + 8 * (i & 1);
                f[i] = (uint32_t)__ldg(q) | ((uint32_t)__ldg(q + 192) << 16);
            }
            sts128(sb + SM_HT + (mk * 128 + (tid & 127)) * 16, make_uint4(f[0], f[1], f[2], f[3]));
        }
    }
    if (warp < 12) {
        const uint16_t* wr = (const uint16_t*)p.wr + 16 * (warp & 3) + g;
#pragma unroll
        for (int ty = 0; ty < 3; ty++) {
#pragma unroll
            for (int i = 0; i < 4; i++) {
                const uint16_t* q = wr + (8 * (i >> 1) + 2 * t) * 192 + ty * 64 + 8 * (i & 1);
                wp[ty][i] = (uint32_t)__ldg(q) | ((uint32_t)__ldg(q + 192) << 16);
            }
        }
    }
    if (tid == 15 * 32) {
        const unsigned target = (bar_seen / (unsigned)p.ncta + 1u) * (unsigned)p.ncta;
        unsigned cur;
        int spins = 0;
        do {
            asm volatile("ld.acquire.gpu.global.u32 %0, [%1];" : "=r"(cur) : "l"(&g_bar) : "memory");
        } while ((int)(cur - target) < 0 && ++spins < (1 << 24));
        mbar_expect_tx(bar_rec, (uint32_t)p.ncta * SEG_W * 4u);
    }
    __syncthreads();
    STAMP(5);

    {
        const int b = (lane << 4) | warp;
        if (lane < 9 && b < p.ncta) {
            bulk_g2s(sb + P1_SEG + b * SEG_W * 4, g_seg + ((size_t)b * MAX_CTA + cta) * SEG_W, SEG_W * 4, bar_rec);
        }
    }
    mbar_wait(bar_pos, 0);
    mbar_wait(bar_rec, 0);
    STAMP(13);
    for (int b = 2 * warp + (lane >> 4); b < ((p.ncta + 1) & ~1); b += 32) {
        const uint32_t seg = sb + P1_SEG + b * SEG_W * 4;
        const int cnt = b < p.ncta ? (int)lds32(seg) : 0;
        if (cnt > SEG_W - 1) ctrl[1] = 1;
        const int n = min(cnt, SEG_W - 1), nmax = max(n, __shfl_xor_sync(0xffffffffu, n, 16));
        for (int j0 = lane & 15; j0 - (lane & 15) < nmax; j0 += 48) {
            uint32_t wd[3], w0[3], w1[3], v0[3], v1[3];
            uint4 rec[3];
            bool act[3];
#pragma unroll
            for (int u = 0; u < 3; u++) wd[u] = j0 + 16 * u < n ? lds32(seg + 4 + (j0 + 16 * u) * 4) : 0u;
#pragma unroll
            for (int u = 0; u < 3; u++) {
                const uint32_t a = (sb + P1_POS + 6u * (wd[u] & 0xffffu)) & ~3u, c = (sb + P1_POS + 6u * ((uint32_t)node0 + (wd[u] >> 16))) & ~3u;
                w0[u] = lds32(a); w1[u] = lds32(a + 4); v0[u] = lds32(c); v1[u] = lds32(c + 4);
            }
#pragma unroll
            for (int u = 0; u < 3; u++) {
                const uint32_t s = wd[u] & 0xffffu, dl = wd[u] >> 16, sh = s << 4, dh = ((uint32_t)node0 + dl) << 4;
                uint32_t rxy, rz;
                const uint32_t db = edge_dist(__funnelshift_r(w0[u], w1[u], sh), __funnelshift_r(w1[u], w1[u], sh),
                                              __funnelshift_r(v0[u], v1[u], dh), __funnelshift_r(v1[u], v1[u], dh), rxy, rz);
                act[u] = j0 + 16 * u < n && db <= D_MAX_BITS;
                float inv;
                asm("rcp.approx.ftz.f32 %0, %1;" : "=f"(inv) : "f"(__uint_as_float(db << 16)));
                rec[u].x = s | ((db - D_MIN_BITS) << 16);
                rec[u].y = pack_bf(bf_lo(rxy) * inv, bf_hi(rxy) * inv);
                rec[u].z = __byte_perm(pack_bf(bf_lo(rz) * inv, 0.f), dl, 0x5410);
            }
#pragma unroll
            for (int u = 0; u < 3; u++) rec[u].w = act[u] ? (uint32_t)atomicAdd(&nCnt[wd[u] >> 16], 1) : 0u;
            const unsigned am0 = __ballot_sync(0xffffffffu, act[0]), am1 = __ballot_sync(0xffffffffu, act[1]), am2 = __ballot_sync(0xffffffffu, act[2]);
            int base = 0;
            if (lane == 0) base = atomicAdd((int*)&ctrl[8], __popc(am0) + __popc(am1) + __popc(am2));
            base = __shfl_sync(0xffffffffu, base, 0);
            const unsigned lt = (1u << lane) - 1u;
            const int p0 = base + __popc(am0 & lt), p1 = base + __popc(am0) + __popc(am1 & lt), p2 = base + __popc(am0) + __popc(am1) + __popc(am2 & lt);
            if (act[0] && p0 < STAGE_CAP) sts128(sb + P1_REC + p0 * 16, rec[0]);
            if (act[1] && p1 < STAGE_CAP) sts128(sb + P1_REC + p1 * 16, rec[1]);
            if (act[2] && p2 < STAGE_CAP) sts128(sb + P1_REC + p2 * 16, rec[2]);
        }
    }
    __syncthreads();
    const int total = ctrl[8];
    if (tid == 0 && total > STAGE_CAP) ctrl[1] = 1;
    if (warp == 0) {
        int c[3], s = 0;
#pragma unroll
        for (int i = 0; i < 3; i++) {
            int b = lane * 3 + i;
            c[i] = b < nnodes ? max(16, (nCnt[b] + 15) & ~15) : 0;
            s += c[i];
        }
        int x = s;
#pragma unroll
        for (int o = 1; o < 32; o <<= 1) { int y = __shfl_up_sync(0xffffffffu, x, o); if (lane >= o) x += y; }
        const int slots = __shfl_sync(0xffffffffu, x, 31);
        int off = x - s, below = 0;
#pragma unroll
        for (int i = 0; i < 3; i++) {
            int b = lane * 3 + i;
            if (b < nnodes) {
                nInfo[b] = (uint32_t)off | ((uint32_t)c[i] << 16);
                below += (2 * off + c[i] < slots);
            }
            off += c[i];
        }
        below = __reduce_add_sync(0xffffffffu, below);
        if (lane == 0) {
            ctrl[2] = below;
            ctrl[4] = slots;
            if (slots > SLOT_CAP) ctrl[1] = 1;
        }
    }
    __syncthreads();
    if (ctrl[1] == 0) {
        uint16_t* sid = (uint16_t*)(smem + SM_SID);
        uint2* meta = (uint2*)(smem + SM_META);
        for (int i = tid; i < total; i += 2 * NT) {
            const bool two = i + NT < total;
            const uint4 r = lds128(sb + P1_REC + i * 16);
            const uint4 q = two ? lds128(sb + P1_REC + (i + NT) * 16) : r;
            const int pos = (int)(lds32(sb + SM_NINFO + (r.z >> 16) * 4) & 0xffffu) + (int)r.w;
            const int pos2 = (int)(lds32(sb + SM_NINFO + (q.z >> 16) * 4) & 0xffffu) + (int)q.w;
            sid[pos]  = (uint16_t)((r.x & 0xffffu) << 2);
            meta[pos] = make_uint2(((r.x >> 16) << 5) | (r.z << 16), r.y);
            if (two) {
                sid[pos2]  = (uint16_t)((q.x & 0xffffu) << 2);
                meta[pos2] = make_uint2(((q.x >> 16) << 5) | (q.z << 16), q.y);
            }
        }
        if (tid >= NT - 128 && tid - (NT - 128) < nnodes) {
            const int b = tid - (NT - 128), split = ctrl[2];
            const int mid = split < nnodes ? (int)(nInfo[split] & 0xffffu) : ctrl[4];
            const int st = b >= split;
            const int mine = (int)(nInfo[b] & 0xffffu) + (int)(nInfo[b] >> 16) - (st ? mid : 0);
            int rank = st ? b - split : b;
            const int o0 = st ? 0 : split, o1 = st ? split : nnodes;
            for (int o = o0; o < o1; o++) {
                const int other = (int)(nInfo[o] & 0xffffu) + (int)(nInfo[o] >> 16) - (st ? 0 : mid);
                rank += st ? (other <= mine) : (other < mine);
            }
            smem[SM_ORDER + rank] = (uint8_t)(b | (st << 7));
        }
        for (int i = tid; i < nnodes * 16; i += NT) {
            int nl = i >> 4, c = nCnt[nl];
            int j = (c & ~15) + (i & 15);
            if (j >= c && (j < 16 || (c & 15))) {
                int pos = (int)(nInfo[nl] & 0xffffu) + j;
                sid[pos]  = 0xffffu;
                meta[pos] = make_uint2((uint32_t)TAB_ZERO << 5, 0u);
            }
        }
    }
    fence_async_smem();
    __syncthreads();
    STAMP(6);

    if (__shfl_sync(0xffffffffu, ctrl[1], 0) != 0) {
        float* acc = (float*)(smem + P1_POS);
        for (int i = tid; i < nnodes * 256; i += NT) acc[i] = 0.f;
        __syncthreads();
        const uint16_t* posu = (const uint16_t*)p.pos;
        const uint32_t* tabg = (const uint32_t*)g_table;
        const uint32_t* Fw = (const uint32_t*)g_F;
        for (int e0 = warp * 32; e0 < p.E; e0 += NT) {
            int e = e0 + lane;
            int s = 0, d = 0;
            uint32_t db = 0xffff, rxy = 0, rz = 0;
            bool act = false;
            if (e < p.E) {
                s = p.src[e]; d = p.dst[e];
                if (d >= node0 && d < node0 + nnodes) {
                    uint32_t sxy = posu[s * 3] | ((uint32_t)posu[s * 3 + 1] << 16), sz = posu[s * 3 + 2];
                    uint32_t dxy = posu[d * 3] | ((uint32_t)posu[d * 3 + 1] << 16), dz = posu[d * 3 + 2];
                    db  = edge_dist(sxy, sz, dxy, dz, rxy, rz);
                    act = db <= D_MAX_BITS;
                }
            }
            unsigned m = __ballot_sync(0xffffffffu, act);
            while (m) {
                int l = __ffs(m) - 1;
                m &= m - 1;
                int es = __shfl_sync(0xffffffffu, s, l), ed = __shfl_sync(0xffffffffu, d, l);
                uint32_t edb = __shfl_sync(0xffffffffu, db, l), exy = __shfl_sync(0xffffffffu, rxy, l), ez = __shfl_sync(0xffffffffu, rz, l);
                float inv = 1.0f / __uint_as_float(edb << 16);
                float rh[3] = {rbf(bf_lo(exy) * inv), rbf(bf_hi(exy) * inv), rbf(bf_lo(ez) * inv)};
                const uint32_t* fr = Fw + (size_t)es * 128 + lane;
                const uint32_t fh = __ldcg(fr);
                const uint32_t q[3] = {__ldcg(fr + 32), __ldcg(fr + 64), __ldcg(fr + 96)};
                float ps0 = 0.f, ps1 = 0.f, pr0 = 0.f, pr1 = 0.f;
                for (int j2 = 0; j2 < 32; j2++) {
                    uint32_t hj = __shfl_sync(0xffffffffu, fh, j2);
                    uint32_t a0 = *(const uint32_t*)(p.w2 + (2 * j2) * 192 + 2 * lane), a1 = *(const uint32_t*)(p.w2 + (2 * j2 + 1) * 192 + 2 * lane);
                    uint32_t b0 = *(const uint32_t*)(p.w2 + (2 * j2) * 192 + 128 + 2 * lane), b1 = *(const uint32_t*)(p.w2 + (2 * j2 + 1) * 192 + 128 + 2 * lane);
                    ps0 += bf_lo(hj) * bf_lo(a0) + bf_hi(hj) * bf_lo(a1);
                    ps1 += bf_lo(hj) * bf_hi(a0) + bf_hi(hj) * bf_hi(a1);
                    pr0 += bf_lo(hj) * bf_lo(b0) + bf_hi(hj) * bf_lo(b1);
                    pr1 += bf_lo(hj) * bf_hi(b0) + bf_hi(hj) * bf_hi(b1);
                }
                float ws0 = 0.f, ws1 = 0.f, wv0 = 0.f, wv1 = 0.f, wr0 = 0.f, wr1 = 0.f;
                for (int k2 = 0; k2 < 8; k2++) {
                    uint32_t rk2 = __ldcg(tabg + (edb - D_MIN_BITS) * 8 + k2);
#pragma unroll
                    for (int h = 0; h < 2; h++) {
                        float rv = h ? bf_hi(rk2) : bf_lo(rk2);
                        const __nv_bfloat16* wrow = p.wr + (2 * k2 + h) * 192 + 2 * lane;
                        uint32_t a = *(const uint32_t*)wrow, b = *(const uint32_t*)(wrow + 64), c = *(const uint32_t*)(wrow + 128);
                        ws0 += rv * bf_lo(a); ws1 += rv * bf_hi(a);
                        wv0 += rv * bf_lo(b); wv1 += rv * bf_hi(b);
                        wr0 += rv * bf_lo(c); wr1 += rv * bf_hi(c);
                    }
                }
                float* a = acc + (ed - node0) * 256 + 2 * lane;
                atomicAdd(a, ps0 * ws0); atomicAdd(a + 1, ps1 * ws1);
#pragma unroll
                for (int c = 0; c < 3; c++) {
                    atomicAdd(a + 64 * (c + 1), wv0 * bf_lo(q[c]) + pr0 * wr0 * rh[c]);
                    atomicAdd(a + 64 * (c + 1) + 1, wv1 * bf_hi(q[c]) + pr1 * wr1 * rh[c]);
                }
            }
        }
        __syncthreads();
        for (int i = tid; i < nnodes * 128; i += NT) {
            uint32_t r = *(const uint32_t*)(p.sv + (size_t)node0 * 256 + 2 * i);
            *(uint32_t*)(p.out + (size_t)node0 * 256 + 2 * i) = pack_bf(bf_lo(r) + acc[2 * i], bf_hi(r) + acc[2 * i + 1]);
        }
        return;
    }

    const int slots = __reduce_max_sync(0xffffffffu, ctrl[4]);
    const int split = __reduce_max_sync(0xffffffffu, ctrl[2]);
    const int nstage = slots <= SLOT_CAP4 ? 6 : 5;
    const uint32_t ring = sb + (nstage == 6 ? SM_RING4 : SM_RING3);
    const int mid = __reduce_max_sync(0xffffffffu, split < nnodes ? (int)(nInfo[split] & 0xffffu) : slots) >> 4;
    const int wgi = warp >> 2, w = warp & 3;
    constexpr uint32_t EMPTY_OFF = NCWG * MAX_STAGE * 8;
    if (wgi == 3) {
        const int sc = w >> 1, r = w & 1;
        const int g0 = (sc == 0 ? 0 : mid) + r, g1 = sc == 0 ? mid : slots >> 4;
        const uint32_t ring_wg = ring + sc * nstage * STAGE_B, full_wg = bar_full + sc * MAX_STAGE * 8;
        const int e = lane >> 1, half = lane & 1;
        const uint32_t coef_off = e * 128 + ((half ^ (e & 7)) << 4);
        const int vrot = (e & 3) ^ ((e >> 1) & 3);
        const uint8_t* tab = (const uint8_t*)g_table + half * 16;
        int stage = r;
        uint32_t phase = 1;
        uint32_t ma = sb + SM_META + (g0 * 16 + e) * 8, ida = sb + SM_SID + g0 * 32;
        uint2 m = make_uint2(0u, 0u);
        uint4 tv = make_uint4(0u, 0u, 0u, 0u), ia = tv, ib = tv;
        if (g0 < g1) {
            m  = lds64(ma);
            ia = lds128(ida);
            ib = lds128(ida + 16);
            tv = __ldg((const uint4*)(tab + (m.x & 0xffffu)));
        }
        for (int left = (g1 - g0 + 1) >> 1; left > 0; left--) {
            const uint32_t st = ring_wg + stage * STAGE_B, fb = full_wg + stage * 8;
            uint4 o[4];
            {
                const uint32_t mul[4] = {0x3f803f80u, __byte_perm(m.y, 0, 0x1010), __byte_perm(m.y, 0, 0x3232), __byte_perm(m.x, 0, 0x3232)};
#pragma unroll
                for (int j = 0; j < 4; j++) {
                    const int v = j ^ vrot;
                    const uint32_t lo = (v & 1) ? mul[1] : mul[0], hi = (v & 1) ? mul[3] : mul[2];
                    const uint32_t mm = (v & 2) ? hi : lo;
                    o[j] = make_uint4(hmul2(tv.x, mm), hmul2(tv.y, mm), hmul2(tv.z, mm), hmul2(tv.w, mm));
                }
            }
            ma += 256; ida += 64;
            if (left > 1) m = lds64(ma);
            mbar_wait(fb + EMPTY_OFF, phase);
            uint32_t leader;
            asm volatile("{\n.reg .pred p;\nelect.sync _|p, 0xffffffff;\nselp.u32 %0, 1, 0, p;\n}" : "=r"(leader));
            if (leader) {
                const uint32_t id2[8] = {ia.x, ia.y, ia.z, ia.w, ib.x, ib.y, ib.z, ib.w};
                const uint32_t rows = st + 2048;
                if ((ib.w >> 16) != 0xffffu) {
                    mbar_expect_tx(fb, 16 * 512);
#pragma unroll
                    for (int i = 0; i < 8; i++) {
                        tma_load(rows + (2 * i) * 640, &tmF, (int)(id2[i] & 0xffffu), fb);
                        tma_load(rows + (2 * i + 1) * 640, &tmF, (int)(id2[i] >> 16), fb);
                    }
                } else {
                    int nv = 0;
#pragma unroll
                    for (int i = 0; i < 8; i++) nv += ((id2[i] & 0xffffu) != 0xffffu) + ((id2[i] >> 16) != 0xffffu);
                    mbar_expect_tx(fb, (uint32_t)nv * 512u);
#pragma unroll
                    for (int q = 0; q < 4; q++) {
                        if (4 * q + 4 <= nv) {
                            tma_load(rows + (4 * q) * 640, &tmF, (int)(id2[2 * q] & 0xffffu), fb);
                            tma_load(rows + (4 * q + 1) * 640, &tmF, (int)(id2[2 * q] >> 16), fb);
                            tma_load(rows + (4 * q + 2) * 640, &tmF, (int)(id2[2 * q + 1] & 0xffffu), fb);
                            tma_load(rows + (4 * q + 3) * 640, &tmF, (int)(id2[2 * q + 1] >> 16), fb);
                        } else {
                            if (4 * q < nv)     tma_load(rows + (4 * q) * 640, &tmF, (int)(id2[2 * q] & 0xffffu), fb);
                            if (4 * q + 1 < nv) tma_load(rows + (4 * q + 1) * 640, &tmF, (int)(id2[2 * q] >> 16), fb);
                            if (4 * q + 2 < nv) tma_load(rows + (4 * q + 2) * 640, &tmF, (int)(id2[2 * q + 1] & 0xffffu), fb);
                        }
                    }
                }
            }
            __syncwarp();
            if (left > 1) {
                ia = lds128(ida);
                ib = lds128(ida + 16);
                tv = __ldg((const uint4*)(tab + (m.x & 0xffffu)));
            }
            const uint32_t a = st + coef_off;
#pragma unroll
            for (int j = 0; j < 4; j++) sts128(a ^ ((j ^ vrot) << 5), o[j]);
            fence_async_smem();
            __syncwarp();
            mbar_arrive_elected(fb);
            stage += 2;
            if (stage >= nstage) { stage -= nstage; phase ^= 1; }
        }
    } else if (wgi == 2) {
        uint32_t wA[2][4][4];
#pragma unroll
        for (int mk = 0; mk < 8; mk++) {
            const uint4 q = lds128(sb + SM_HT + (mk * 128 + (tid & 127)) * 16);
            wA[mk >> 2][mk & 3][0] = q.x; wA[mk >> 2][mk & 3][1] = q.y; wA[mk >> 2][mk & 3][2] = q.z; wA[mk >> 2][mk & 3][3] = q.w;
        }
        __syncwarp();
        mbar_arrive_elected(bar_hempty);
        mbar_arrive_elected(bar_hempty + 8);
        const uint32_t lane_off = (uint32_t)node0 * 512u + t * 128 + w * 32 + (g & 1) * 16 + (g >> 1) * 4;
        uint32_t hpar = 0;
        float zs[8], zv[24], pvv[6], pr[4][2];
        auto start = [&](int ent) {
            const int c = ent >> 7;
            mbar_wait(bar_hfull + c * 8, (hpar >> c) & 1);
            hpar ^= 1u << c;
            const uint32_t dht = desc_lo(sb + SM_HT + c * 8192);
            wg_fence();
            wgmma_n16_first(zs, wA[0][0], dht);
            wgmma_n48_first(zv, wA[1][0], dht + 2);
#pragma unroll
            for (int ks = 1; ks < 4; ks++) {
                wgmma_n16(zs, wA[0][ks], dht + ks * 128);
                wgmma_n48(zv, wA[1][ks], dht + ks * 128 + 2);
            }
            wg_commit();
        };
        auto side = [&](int ent) {
            const int c = ent >> 7;
            const uint32_t pa = sb + SM_PV + c * 3072 + (tid & 127) * 8;
            const uint2 a0 = lds64(pa), a1 = lds64(pa + 1024), a2 = lds64(pa + 2048);
            pvv[0] = __uint_as_float(a0.x); pvv[1] = __uint_as_float(a0.y); pvv[2] = __uint_as_float(a1.x);
            pvv[3] = __uint_as_float(a1.y); pvv[4] = __uint_as_float(a2.x); pvv[5] = __uint_as_float(a2.y);
            __syncwarp();
            mbar_arrive_elected(bar_hempty + c * 8);
        };
        auto weigh = [&]() {
#pragma unroll
            for (int i = 0; i < 12; i++) asm volatile("" : "+r"(wp[i >> 2][i & 3]));
            pr[0][0] = bf_lo(wp[0][0]) * zs[0] + bf_hi(wp[0][0]) * zs[1] + bf_lo(wp[0][2]) * zs[4] + bf_hi(wp[0][2]) * zs[5];
            pr[0][1] = bf_lo(wp[0][1]) * zs[2] + bf_hi(wp[0][1]) * zs[3] + bf_lo(wp[0][3]) * zs[6] + bf_hi(wp[0][3]) * zs[7];
#pragma unroll
            for (int a = 0; a < 3; a++) {
                const float* y = zv + 8 * a;
                pr[a + 1][0] = pvv[2 * a] + bf_lo(wp[2][0]) * y[0] + bf_hi(wp[2][0]) * y[1] + bf_lo(wp[2][2]) * y[4] + bf_hi(wp[2][2]) * y[5];
                pr[a + 1][1] = pvv[2 * a + 1] + bf_lo(wp[2][1]) * y[2] + bf_hi(wp[2][1]) * y[3] + bf_lo(wp[2][3]) * y[6] + bf_hi(wp[2][3]) * y[7];
            }
            asm volatile("" : "+f"(pr[0][0]), "+f"(pr[0][1]), "+f"(pr[1][0]), "+f"(pr[1][1]), "+f"(pr[2][0]), "+f"(pr[2][1]), "+f"(pr[3][0]), "+f"(pr[3][1]) :: "memory");
        };
        auto finish = [&](int ent, uint32_t resid) {
            const bool hi2 = t & 2, hi1 = t & 1, odd = g & 1;
            float ka0 = hi2 ? pr[2][0] : pr[0][0], ka1 = hi2 ? pr[2][1] : pr[0][1];
            float kb0 = hi2 ? pr[3][0] : pr[1][0], kb1 = hi2 ? pr[3][1] : pr[1][1];
            float sa0 = hi2 ? pr[0][0] : pr[2][0], sa1 = hi2 ? pr[0][1] : pr[2][1];
            float sb0 = hi2 ? pr[1][0] : pr[3][0], sb1 = hi2 ? pr[1][1] : pr[3][1];
            ka0 += __shfl_xor_sync(0xffffffffu, sa0, 2); ka1 += __shfl_xor_sync(0xffffffffu, sa1, 2);
            kb0 += __shfl_xor_sync(0xffffffffu, sb0, 2); kb1 += __shfl_xor_sync(0xffffffffu, sb1, 2);
            float k0 = hi1 ? kb0 : ka0, k1 = hi1 ? kb1 : ka1;
            float s0 = hi1 ? ka0 : kb0, s1 = hi1 ? ka1 : kb1;
            k0 += __shfl_xor_sync(0xffffffffu, s0, 1);
            k1 += __shfl_xor_sync(0xffffffffu, s1, 1);
            const float other = __shfl_xor_sync(0xffffffffu, odd ? k0 : k1, 4);
            const float lo = odd ? other : k0, hi = odd ? k1 : other;
            *(uint32_t*)((uint8_t*)p.out + (lane_off + (uint32_t)(ent & 127) * 512u)) = pack_bf(bf_lo(resid) + lo, bf_hi(resid) + hi);
        };
        auto entry = [&](int i) -> int { return __reduce_max_sync(0xffffffffu, (int)smem[SM_ORDER + i]); };
        auto load_resid = [&](int ent) -> uint32_t { return __ldg((const uint32_t*)((const uint8_t*)p.sv + (lane_off + (uint32_t)(ent & 127) * 512u))); };
        if (nnodes > 0) {
            int cur = entry(0), nxt = entry(1);
            uint32_t resid = load_resid(cur);
            start(cur);
#pragma unroll 1
            for (int i = 1; i < nnodes; i++) {
                wg_wait0();
                side(cur);
                weigh();
                start(nxt);
                finish(cur, resid);
                cur = nxt;
                resid = load_resid(cur);
                nxt = entry(i + 1);
            }
            wg_wait0();
            side(cur);
            weigh();
            finish(cur, resid);
        }
    } else {
        const int wg = wgi;
        uint32_t aoff[4];
        {
            const int e = (lane & 7) + 8 * (lane >> 4), ch = 2 * w + ((lane >> 3) & 1);
#pragma unroll
            for (int b = 0; b < 4; b++) aoff[b] = 2048 + e * 640 + b * 128 + ((ch ^ ((5 * e + b) & 7)) << 4);
        }
        const uint32_t stsm_a = sb + SM_HT + wg * 8192 + (16 * w + (lane & 15)) * 128 + (((lane >> 4) ^ (lane & 7)) << 4);
        const uint32_t pv_a = sb + SM_PV + wg * 3072 + (tid & 127) * 8;
        const uint32_t ring_wg = ring + wg * nstage * STAGE_B;
        const uint32_t full_wg = bar_full + wg * MAX_STAGE * 8;

        float ys[8], yv[24], dQ[3][8];
        uint32_t A0[4][4], A1[4][4];
#pragma unroll
        for (int i = 0; i < 24; i++) yv[i] = 0.f;
#pragma unroll
        for (int i = 0; i < 8; i++) { ys[i] = 0.f; dQ[0][i] = 0.f; dQ[1][i] = 0.f; dQ[2][i] = 0.f; }
        int left = wg == 0 ? mid : (slots >> 4) - mid;
        int fstage = 0;
        uint32_t fphase = 0, fst = ring_wg, fbar = full_wg, hphase = 0;
        uint32_t ninfo_a = sb + SM_NINFO + (wg == 0 ? 0 : split) * 4;
        int gi = 0, G = __reduce_max_sync(0xffffffffu, (int)(lds32(ninfo_a) >> 20));

        auto fetch = [&](uint32_t (&A)[4][4], uint32_t& bd, uint32_t& eb) {
            mbar_wait(fbar, fphase);
#pragma unroll
            for (int b = 0; b < 4; b++) ldsm4t(A[b], fst + aoff[b]);
            bd = desc_lo(fst);
            eb = fbar + EMPTY_OFF;
            fst += STAGE_B; fbar += 8;
            if (++fstage == nstage) { fstage = 0; fphase ^= 1; fst = ring_wg; fbar = full_wg; }
        };
        auto step = [&](uint32_t (&Ac)[4][4], uint32_t bdc, uint32_t ebc, uint32_t (&An)[4][4], uint32_t& bdn, uint32_t& ebn) {
            wg_fence();
            wgmma_n64_p(ys, yv, Ac[0], bdc, gi);
            wgmma_n16_p(dQ[0], Ac[1], bdc, gi);
            wgmma_n16_p(dQ[1], Ac[2], bdc, gi);
            wgmma_n16_p(dQ[2], Ac[3], bdc, gi);
            wg_commit();
            if (--left > 0) fetch(An, bdn, ebn);
            const bool last = ++gi == G;
            uint32_t info_next = 0;
            if (last) { ninfo_a += 4; info_next = lds32(ninfo_a); }
            wg_wait0();
            mbar_arrive_elected(ebc);
            if (last) {
                mbar_wait(bar_hempty + wg * 8, hphase);
                hphase ^= 1;
                stsm4(stsm_a, pack_bf(ys[0], ys[1]), pack_bf(ys[2], ys[3]), pack_bf(ys[4], ys[5]), pack_bf(ys[6], ys[7]));
#pragma unroll
                for (int i = 0; i < 6; i += 2) {
                    stsm4(stsm_a ^ ((i + 2) << 4),
                          pack_bf(yv[4 * i], yv[4 * i + 1]), pack_bf(yv[4 * i + 2], yv[4 * i + 3]),
                          pack_bf(yv[4 * i + 4], yv[4 * i + 5]), pack_bf(yv[4 * i + 6], yv[4 * i + 7]));
                }
#pragma unroll
                for (int i = 0; i < 4; i++) asm volatile("" : "+r"(wp[1][i]));
#pragma unroll
                for (int a = 0; a < 3; a++) {
                    const float* q = dQ[a];
                    const float p0 = bf_lo(wp[1][0]) * q[0] + bf_hi(wp[1][0]) * q[1] + bf_lo(wp[1][2]) * q[4] + bf_hi(wp[1][2]) * q[5];
                    const float p1 = bf_lo(wp[1][1]) * q[2] + bf_hi(wp[1][1]) * q[3] + bf_lo(wp[1][3]) * q[6] + bf_hi(wp[1][3]) * q[7];
                    asm volatile("st.shared.v2.f32 [%0], {%1, %2};" ::"r"(pv_a + a * 1024), "f"(p0), "f"(p1) : "memory");
                }
                fence_async_smem();
                __syncwarp();
                mbar_arrive_elected(bar_hfull + wg * 8);
                G = __reduce_max_sync(0xffffffffu, (int)(info_next >> 20));
                gi = 0;
            }
        };
        if (left > 0) {
            uint32_t bd0, eb0, bd1 = 0, eb1 = 0;
            fetch(A0, bd0, eb0);
            while (true) {
                step(A0, bd0, eb0, A1, bd1, eb1);
                if (left <= 0) break;
                step(A1, bd1, eb1, A0, bd0, eb0);
                if (left <= 0) break;
            }
        }
    }
    STAMP(8);
}

typedef CUresult (*EncodeFn)(CUtensorMap*, CUtensorMapDataType, cuuint32_t, void*, const cuuint64_t*, const cuuint64_t*,
                             const cuuint32_t*, const cuuint32_t*, CUtensorMapInterleave, CUtensorMapSwizzle,
                             CUtensorMapL2promotion, CUtensorMapFloatOOBfill);

void make_map(EncodeFn enc, CUtensorMap* tm, const void* base, uint64_t lines, uint32_t box) {
    cuuint64_t gd[2] = {64, lines};
    cuuint64_t gs[1] = {128};
    cuuint32_t bd[2] = {64, box};
    cuuint32_t es[2] = {1, 1};
    enc(tm, CU_TENSOR_MAP_DATA_TYPE_BFLOAT16, 2, const_cast<void*>(base), gd, gs, bd, es, CU_TENSOR_MAP_INTERLEAVE_NONE,
        CU_TENSOR_MAP_SWIZZLE_128B, CU_TENSOR_MAP_L2_PROMOTION_L2_128B, CU_TENSOR_MAP_FLOAT_OOB_FILL_NONE);
}

void make_map3(EncodeFn enc, CUtensorMap* tm, const void* base, uint64_t nodes, uint32_t box) {
    cuuint64_t gd[3] = {64, 4, nodes};
    cuuint64_t gs[2] = {128, 512};
    cuuint32_t bd[3] = {64, 1, box};
    cuuint32_t es[3] = {1, 1, 1};
    enc(tm, CU_TENSOR_MAP_DATA_TYPE_BFLOAT16, 3, const_cast<void*>(base), gd, gs, bd, es, CU_TENSOR_MAP_INTERLEAVE_NONE,
        CU_TENSOR_MAP_SWIZZLE_128B, CU_TENSOR_MAP_L2_PROMOTION_L2_128B, CU_TENSOR_MAP_FLOAT_OOB_FILL_NONE);
}

}

extern "C" void kernel_launch(void* const* d_in, const int* in_sizes, int n_in, void* d_out, int out_size) {
    (void)n_in; (void)out_size;
    static int n_sm = 0;
    static EncodeFn enc = nullptr;
    static void* f_ptr = nullptr;
    if (n_sm == 0) {
        int dev = 0;
        cudaGetDevice(&dev);
        cudaDeviceGetAttribute(&n_sm, cudaDevAttrMultiProcessorCount, dev);
        cudaFuncSetAttribute(painn_kernel, cudaFuncAttributeMaxDynamicSharedMemorySize, SM_TOTAL);
        void* fn = nullptr;
        cudaDriverEntryPointQueryResult qr;
        cudaGetDriverEntryPoint("cuTensorMapEncodeTiled", &fn, cudaEnableDefault, &qr);
        enc = (EncodeFn)fn;
        cudaGetSymbolAddress(&f_ptr, g_F);
    }
    Params p;
    p.sv    = (const __nv_bfloat16*)d_in[0];
    p.pos   = (const __nv_bfloat16*)d_in[1];
    p.src   = (const int*)d_in[2];
    p.dst   = (const int*)d_in[3];
    p.freqs = (const __nv_bfloat16*)d_in[4];
    p.w1    = (const __nv_bfloat16*)d_in[5];
    p.w2    = (const __nv_bfloat16*)d_in[6];
    p.wr    = (const __nv_bfloat16*)d_in[7];
    p.out   = (__nv_bfloat16*)d_out;
    p.N = in_sizes[1] / 3;
    p.E = in_sizes[2];
    p.ncta = n_sm < MAX_CTA ? n_sm : MAX_CTA;
    p.npc = ((p.N + p.ncta - 1) / p.ncta + 3) & ~3;
    p.npc_magic = (uint32_t)(0x100000000ull / (uint32_t)p.npc) + 1u;
    p.quads_per_cta = ((p.E >> 2) + p.ncta - 1) / p.ncta;
    if (!enc || p.N > MAX_N || p.npc > MAX_NPC || (p.E & 3) || p.quads_per_cta > MAX_ROUNDS * 32) return;

    CUtensorMap tmF, tmFs;
    make_map(enc, &tmF, f_ptr, (uint64_t)p.N * 4, 4);
    make_map3(enc, &tmFs, f_ptr, (uint64_t)p.N, 4);

    cudaLaunchConfig_t cfg = {};
    cfg.gridDim = dim3(p.ncta);
    cfg.blockDim = dim3(NT);
    cfg.dynamicSmemBytes = SM_TOTAL;
    cfg.stream = cudaStreamPerThread;
    cudaLaunchAttribute attr[1];
    attr[0].id = cudaLaunchAttributeCooperative;
    attr[0].val.cooperative = 1;
    cfg.attrs = attr;
    cfg.numAttrs = 1;
    cudaLaunchKernelEx(&cfg, painn_kernel, p, tmF, tmFs);
}
```

```cpp
#include <cuda_runtime.h>
#include <cuda.h>
#include <cuda_bf16.h>
#include <stdint.h>

namespace {

constexpr int NT        = 512;
constexpr int NCWG      = 2;
constexpr int MAX_N     = 10240;
constexpr int MAX_CTA   = 144;
constexpr int MAX_NPC   = 80;
constexpr int MAX_ROUNDS = 38;
constexpr int REC_CAP   = MAX_ROUNDS * 128;
constexpr int SEG_W     = 72;
constexpr int SLOT_CAP  = 6144;
constexpr int MAX_STAGE = 6;
constexpr int STAGE_B   = 12288;

constexpr uint32_t D_MIN_BITS = 0x38D2;
constexpr uint32_t D_MAX_BITS = 0x409C;
constexpr int TAB_ROWS  = (int)(D_MAX_BITS - D_MIN_BITS) + 1;
constexpr int TAB_ZERO  = TAB_ROWS;
constexpr int TAB_BYTES = (TAB_ROWS + 1) * 32;

constexpr int SM_BINCNT = 0;
constexpr int SM_BINOFF = SM_BINCNT + MAX_CTA * 4;
constexpr int SM_NCNT   = SM_BINOFF + MAX_CTA * 4;
constexpr int SM_NINFO  = SM_NCNT + MAX_NPC * 4;
constexpr int SM_ORDER  = SM_NINFO + (MAX_NPC + 1) * 4;
constexpr int SM_CTRL   = SM_ORDER + MAX_NPC + 12;
constexpr int SM_BARS   = SM_CTRL + 64;
constexpr int SM_SID    = 2048 + 256;
constexpr int SM_META   = SM_SID + SLOT_CAP * 2;
constexpr int SM_TOTAL  = 232448;
constexpr int SM_HT     = (SM_TOTAL - 3 * 8192) / 1024 * 1024;
constexpr int SM_PV     = SM_HT + 2 * 8192;
constexpr int SM_RING4  = SM_HT - NCWG * 6 * STAGE_B;
constexpr int SM_RING3  = SM_HT - NCWG * 5 * STAGE_B;
constexpr int SLOT_CAP4 = (SM_RING4 - SM_META) / 8;
constexpr int P1_POS    = 3072;
constexpr int P1_SEG    = P1_POS + 61440;
constexpr int P1_REC    = P1_SEG + MAX_CTA * SEG_W * 4;
constexpr int P1_SV     = 142336;
constexpr int P1_W1     = P1_SV + 4 * MAX_NPC * 128;
constexpr int P1_W2     = P1_W1 + 8192;
constexpr int P1_END    = P1_W2 + 8192;
constexpr int STAGE_CAP = (SM_HT - P1_REC) / 16;
static_assert(SM_BARS + (8 + 2 * NCWG * MAX_STAGE) * 8 <= SM_SID, "misc block");
static_assert(SM_BARS + 256 <= P1_POS, "misc block");
static_assert(P1_END <= SM_TOTAL && P1_SV % 1024 == 0 && P1_REC <= P1_SV && P1_REC % 16 == 0, "phase 1 overlay");
static_assert(SM_META + SLOT_CAP * 8 <= SM_RING3, "CSR");
static_assert(SM_RING4 % 1024 == 0 && SM_RING3 % 1024 == 0 && SM_HT % 1024 == 0, "alignment");
static_assert(SM_BARS % 8 == 0 && SM_META % 8 == 0 && SM_CTRL % 4 == 0, "alignment");
static_assert(MAX_N * 6 <= 61440, "pos");
static_assert(SM_SID + MAX_NPC * 1024 <= SM_TOTAL, "slow path accumulators");

__device__ __align__(1024) uint4 g_F[MAX_N * 32];
__device__ __align__(128) uint32_t g_seg[MAX_CTA * MAX_CTA * SEG_W];
__device__ uint4    g_table[(TAB_BYTES + 15) / 16];
__device__ unsigned g_bar;
#define STAMP(k)
#define STAMPT(k, T)
#define ITS(k)

struct Params {
    const __nv_bfloat16* sv;
    const __nv_bfloat16* pos;
    const int*           src;
    const int*           dst;
    const __nv_bfloat16* freqs;
    const __nv_bfloat16* w1;
    const __nv_bfloat16* w2;
    const __nv_bfloat16* wr;
    __nv_bfloat16*       out;
    int N, E, ncta, npc;
    uint32_t npc_magic;
    int quads_per_cta;
};

__device__ __forceinline__ uint32_t smem_u32(const void* p) { return (uint32_t)__cvta_generic_to_shared(p); }
__device__ __forceinline__ float bf_lo(uint32_t v) { return __uint_as_float(v << 16); }
__device__ __forceinline__ float bf_hi(uint32_t v) { return __uint_as_float(v & 0xffff0000u); }
__device__ __forceinline__ float bf_u16(uint16_t v) { return __uint_as_float((uint32_t)v << 16); }
__device__ __forceinline__ uint32_t pack_bf(float lo, float hi) {
    uint32_t r;
    asm("cvt.rn.bf16x2.f32 %0, %1, %2;" : "=r"(r) : "f"(hi), "f"(lo));
    return r;
}
__device__ __forceinline__ float rbf(float x) { return bf_lo(pack_bf(x, 0.f)); }
__device__ __forceinline__ uint32_t hmul2(uint32_t a, uint32_t b) {
    uint32_t r;
    asm("mul.rn.bf16x2 %0, %1, %2;" : "=r"(r) : "r"(a), "r"(b));
    return r;
}
__device__ __forceinline__ uint32_t hsub2(uint32_t a, uint32_t b) {
    uint32_t r;
    asm("sub.rn.bf16x2 %0, %1, %2;" : "=r"(r) : "r"(a), "r"(b));
    return r;
}
__device__ __forceinline__ uint32_t lds32(uint32_t a) { uint32_t v; asm volatile("ld.shared.u32 %0, [%1];" : "=r"(v) : "r"(a)); return v; }
__device__ __forceinline__ uint32_t lds16(uint32_t a) { uint16_t v; asm volatile("ld.shared.u16 %0, [%1];" : "=h"(v) : "r"(a)); return v; }
__device__ __forceinline__ uint2 lds64(uint32_t a) { uint2 v; asm volatile("ld.shared.v2.u32 {%0,%1}, [%2];" : "=r"(v.x), "=r"(v.y) : "r"(a)); return v; }
__device__ __forceinline__ uint4 lds128(uint32_t a) { uint4 v; asm volatile("ld.shared.v4.u32 {%0,%1,%2,%3}, [%4];" : "=r"(v.x), "=r"(v.y), "=r"(v.z), "=r"(v.w) : "r"(a)); return v; }
__device__ __forceinline__ void sts32(uint32_t a, uint32_t v) { asm volatile("st.shared.u32 [%0], %1;" ::"r"(a), "r"(v) : "memory"); }
__device__ __forceinline__ void sts128(uint32_t a, uint4 v) { asm volatile("st.shared.v4.u32 [%0], {%1,%2,%3,%4};" ::"r"(a), "r"(v.x), "r"(v.y), "r"(v.z), "r"(v.w) : "memory"); }
__device__ __forceinline__ void mbar_init(uint32_t bar, int cnt) { asm volatile("mbarrier.init.shared::cta.b64 [%0], %1;" ::"r"(bar), "r"(cnt) : "memory"); }
__device__ __forceinline__ void mbar_expect_tx(uint32_t bar, uint32_t bytes) { asm volatile("mbarrier.arrive.expect_tx.shared::cta.b64 _, [%0], %1;" ::"r"(bar), "r"(bytes) : "memory"); }
__device__ __forceinline__ void mbar_arrive(uint32_t bar) { asm volatile("mbarrier.arrive.shared::cta.b64 _, [%0];" ::"r"(bar) : "memory"); }
__device__ __forceinline__ void mbar_wait(uint32_t bar, uint32_t parity) {
    asm volatile("{\n.reg .pred p;\n.reg .u32 c;\n"
                 "mbarrier.try_wait.parity.shared::cta.b64 p, [%0], %1;\n"
                 "@p bra DONE_%=;\n"
                 "mov.u32 c, 0;\n"
                 "LOOP_%=:\n"
                 "mbarrier.try_wait.parity.shared::cta.b64 p, [%0], %1;\n"
                 "@p bra DONE_%=;\n"
                 "add.u32 c, c, 1;\n"
                 "setp.lt.u32 p, c, 4194304;\n"
                 "@p bra LOOP_%=;\n"
                 "DONE_%=:\n}"
                 ::"r"(bar), "r"(parity) : "memory");
}
__device__ __forceinline__ void mbar_arrive_elected(uint32_t bar) {
    asm volatile("{\n.reg .pred p;\nelect.sync _|p, 0xffffffff;\n@p mbarrier.arrive.shared::cta.b64 _, [%0];\n}" ::"r"(bar) : "memory");
}
__device__ __forceinline__ void bulk_g2s(uint32_t dst, const void* src, uint32_t bytes, uint32_t bar) {
    asm volatile("cp.async.bulk.shared::cluster.global.mbarrier::complete_tx::bytes [%0], [%1], %2, [%3];"
                 ::"r"(dst), "l"(src), "r"(bytes), "r"(bar) : "memory");
}
__device__ __forceinline__ void cp_async16(uint32_t dst, const void* src) {
    asm volatile("cp.async.cg.shared.global [%0], [%1], 16;" ::"r"(dst), "l"(src) : "memory");
}
__device__ __forceinline__ void tma_load(uint32_t dst, const CUtensorMap* tm, int line, uint32_t bar) {
    asm volatile("cp.async.bulk.tensor.2d.shared::cluster.global.mbarrier::complete_tx::bytes [%0], [%1, {%3, %4}], [%2];"
                 ::"r"(dst), "l"(tm), "r"(bar), "r"(0), "r"(line) : "memory");
}
__device__ __forceinline__ void tma_load3(uint32_t dst, const CUtensorMap* tm, int comp, int node, uint32_t bar) {
    asm volatile("cp.async.bulk.tensor.3d.shared::cluster.global.mbarrier::complete_tx::bytes [%0], [%1, {%3, %4, %5}], [%2];"
                 ::"r"(dst), "l"(tm), "r"(bar), "r"(0), "r"(comp), "r"(node) : "memory");
}
__device__ __forceinline__ void tma_store3(const CUtensorMap* tm, int comp, int node, uint32_t src) {
    asm volatile("cp.async.bulk.tensor.3d.global.shared::cta.bulk_group [%0, {%2, %3, %4}], [%1];"
                 ::"l"(tm), "r"(src), "r"(0), "r"(comp), "r"(node) : "memory");
}
__device__ __forceinline__ void fence_async_smem() { asm volatile("fence.proxy.async.shared::cta;" ::: "memory"); }
__device__ __forceinline__ void named_barrier(int id) { asm volatile("bar.sync %0, 128;" ::"r"(id) : "memory"); }
__device__ __forceinline__ void ldsm4(uint32_t (&r)[4], uint32_t a) {
    asm volatile("ldmatrix.sync.aligned.m8n8.x4.shared.b16 {%0,%1,%2,%3}, [%4];" : "=r"(r[0]), "=r"(r[1]), "=r"(r[2]), "=r"(r[3]) : "r"(a) : "memory");
}
__device__ __forceinline__ void ldsm4t(uint32_t (&r)[4], uint32_t a) {
    asm volatile("ldmatrix.sync.aligned.m8n8.x4.trans.shared.b16 {%0,%1,%2,%3}, [%4];" : "=r"(r[0]), "=r"(r[1]), "=r"(r[2]), "=r"(r[3]) : "r"(a) : "memory");
}
__device__ __forceinline__ void stsm4(uint32_t a, uint32_t r0, uint32_t r1, uint32_t r2, uint32_t r3) {
    asm volatile("stmatrix.sync.aligned.m8n8.x4.shared.b16 [%0], {%1,%2,%3,%4};" ::"r"(a), "r"(r0), "r"(r1), "r"(r2), "r"(r3) : "memory");
}
__device__ __forceinline__ void mma16816(float (&c)[4], const uint32_t (&a)[4], uint32_t b0, uint32_t b1) {
    asm volatile("mma.sync.aligned.m16n8k16.row.col.f32.bf16.bf16.f32 {%0,%1,%2,%3}, {%4,%5,%6,%7}, {%8,%9}, {%0,%1,%2,%3};"
                 : "+f"(c[0]), "+f"(c[1]), "+f"(c[2]), "+f"(c[3])
                 : "r"(a[0]), "r"(a[1]), "r"(a[2]), "r"(a[3]), "r"(b0), "r"(b1));
}

__device__ __forceinline__ uint32_t desc_lo(uint32_t saddr) { return ((saddr & 0x3FFFF) >> 4) | (1u << 16); }
#define DESC_HI "0x40000040"
__device__ __forceinline__ void wg_fence() { asm volatile("wgmma.fence.sync.aligned;" ::: "memory"); }
__device__ __forceinline__ void wg_commit() { asm volatile("wgmma.commit_group.sync.aligned;" ::: "memory"); }
__device__ __forceinline__ void wg_wait0() { asm volatile("wgmma.wait_group.sync.aligned 0;" ::: "memory"); }
__device__ __forceinline__ void wg_wait1() { asm volatile("wgmma.wait_group.sync.aligned 1;" ::: "memory"); }

__device__ __forceinline__ void wgmma_n64_first(float (&d)[8], float (&e)[24], const uint32_t (&a)[4], uint32_t bdesc) {
    asm volatile("{\n.reg .b64 b;\nmov.b64 b, {%36, " DESC_HI "};\n"
                 "wgmma.mma_async.sync.aligned.m64n64k16.f32.bf16.bf16 {%0,%1,%2,%3,%4,%5,%6,%7,%8,%9,%10,%11,%12,%13,%14,%15,%16,%17,%18,%19,%20,%21,%22,%23,%24,%25,%26,%27,%28,%29,%30,%31}, {%32,%33,%34,%35}, b, 0, 1, 1, 1;\n}"
                 : "=f"(d[0]), "=f"(d[1]), "=f"(d[2]), "=f"(d[3]), "=f"(d[4]), "=f"(d[5]), "=f"(d[6]), "=f"(d[7]),
                   "=f"(e[0]), "=f"(e[1]), "=f"(e[2]), "=f"(e[3]), "=f"(e[4]), "=f"(e[5]), "=f"(e[6]), "=f"(e[7]), "=f"(e[8]), "=f"(e[9]), "=f"(e[10]), "=f"(e[11]), "=f"(e[12]), "=f"(e[13]), "=f"(e[14]), "=f"(e[15]), "=f"(e[16]), "=f"(e[17]), "=f"(e[18]), "=f"(e[19]), "=f"(e[20]), "=f"(e[21]), "=f"(e[22]), "=f"(e[23])
                 : "r"(a[0]), "r"(a[1]), "r"(a[2]), "r"(a[3]), "r"(bdesc));
}
__device__ __forceinline__ void wgmma_n64(float (&d)[8], float (&e)[24], const uint32_t (&a)[4], uint32_t bdesc) {
    asm volatile("{\n.reg .b64 b;\nmov.b64 b, {%36, " DESC_HI "};\n"
                 "wgmma.mma_async.sync.aligned.m64n64k16.f32.bf16.bf16 {%0,%1,%2,%3,%4,%5,%6,%7,%8,%9,%10,%11,%12,%13,%14,%15,%16,%17,%18,%19,%20,%21,%22,%23,%24,%25,%26,%27,%28,%29,%30,%31}, {%32,%33,%34,%35}, b, 1, 1, 1, 1;\n}"
                 : "+f"(d[0]), "+f"(d[1]), "+f"(d[2]), "+f"(d[3]), "+f"(d[4]), "+f"(d[5]), "+f"(d[6]), "+f"(d[7]),
                   "+f"(e[0]), "+f"(e[1]), "+f"(e[2]), "+f"(e[3]), "+f"(e[4]), "+f"(e[5]), "+f"(e[6]), "+f"(e[7]), "+f"(e[8]), "+f"(e[9]), "+f"(e[10]), "+f"(e[11]), "+f"(e[12]), "+f"(e[13]), "+f"(e[14]), "+f"(e[15]), "+f"(e[16]), "+f"(e[17]), "+f"(e[18]), "+f"(e[19]), "+f"(e[20]), "+f"(e[21]), "+f"(e[22]), "+f"(e[23])
                 : "r"(a[0]), "r"(a[1]), "r"(a[2]), "r"(a[3]), "r"(bdesc));
}
__device__ __forceinline__ void wgmma_n48_first(float (&e)[24], const uint32_t (&a)[4], uint32_t bdesc) {
    asm volatile("{\n.reg .b64 b;\nmov.b64 b, {%28, " DESC_HI "};\n"
                 "wgmma.mma_async.sync.aligned.m64n48k16.f32.bf16.bf16 {%0,%1,%2,%3,%4,%5,%6,%7,%8,%9,%10,%11,%12,%13,%14,%15,%16,%17,%18,%19,%20,%21,%22,%23}, {%24,%25,%26,%27}, b, 0, 1, 1, 1;\n}"
                 : "=f"(e[0]), "=f"(e[1]), "=f"(e[2]), "=f"(e[3]), "=f"(e[4]), "=f"(e[5]), "=f"(e[6]), "=f"(e[7]), "=f"(e[8]), "=f"(e[9]), "=f"(e[10]), "=f"(e[11]), "=f"(e[12]), "=f"(e[13]), "=f"(e[14]), "=f"(e[15]), "=f"(e[16]), "=f"(e[17]), "=f"(e[18]), "=f"(e[19]), "=f"(e[20]), "=f"(e[21]), "=f"(e[22]), "=f"(e[23])
                 : "r"(a[0]), "r"(a[1]), "r"(a[2]), "r"(a[3]), "r"(bdesc));
}
__device__ __forceinline__ void wgmma_n48(float (&e)[24], const uint32_t (&a)[4], uint32_t bdesc) {
    asm volatile("{\n.reg .b64 b;\nmov.b64 b, {%28, " DESC_HI "};\n"
                 "wgmma.mma_async.sync.aligned.m64n48k16.f32.bf16.bf16 {%0,%1,%2,%3,%4,%5,%6,%7,%8,%9,%10,%11,%12,%13,%14,%15,%16,%17,%18,%19,%20,%21,%22,%23}, {%24,%25,%26,%27}, b, 1, 1, 1, 1;\n}"
                 : "+f"(e[0]), "+f"(e[1]), "+f"(e[2]), "+f"(e[3]), "+f"(e[4]), "+f"(e[5]), "+f"(e[6]), "+f"(e[7]), "+f"(e[8]), "+f"(e[9]), "+f"(e[10]), "+f"(e[11]), "+f"(e[12]), "+f"(e[13]), "+f"(e[14]), "+f"(e[15]), "+f"(e[16]), "+f"(e[17]), "+f"(e[18]), "+f"(e[19]), "+f"(e[20]), "+f"(e[21]), "+f"(e[22]), "+f"(e[23])
                 : "r"(a[0]), "r"(a[1]), "r"(a[2]), "r"(a[3]), "r"(bdesc));
}
__device__ __forceinline__ void wgmma_n16_first(float (&d)[8], const uint32_t (&a)[4], uint32_t bdesc) {
    asm volatile("{\n.reg .b64 b;\nmov.b64 b, {%12, " DESC_HI "};\n"
                 "wgmma.mma_async.sync.aligned.m64n16k16.f32.bf16.bf16 {%0,%1,%2,%3,%4,%5,%6,%7}, {%8,%9,%10,%11}, b, 0, 1, 1, 1;\n}"
                 : "=f"(d[0]), "=f"(d[1]), "=f"(d[2]), "=f"(d[3]), "=f"(d[4]), "=f"(d[5]), "=f"(d[6]), "=f"(d[7])
                 : "r"(a[0]), "r"(a[1]), "r"(a[2]), "r"(a[3]), "r"(bdesc));
}
__device__ __forceinline__ void wgmma_n16(float (&d)[8], const uint32_t (&a)[4], uint32_t bdesc) {
    asm volatile("{\n.reg .b64 b;\nmov.b64 b, {%12, " DESC_HI "};\n"
                 "wgmma.mma_async.sync.aligned.m64n16k16.f32.bf16.bf16 {%0,%1,%2,%3,%4,%5,%6,%7}, {%8,%9,%10,%11}, b, 1, 1, 1, 1;\n}"
                 : "+f"(d[0]), "+f"(d[1]), "+f"(d[2]), "+f"(d[3]), "+f"(d[4]), "+f"(d[5]), "+f"(d[6]), "+f"(d[7])
                 : "r"(a[0]), "r"(a[1]), "r"(a[2]), "r"(a[3]), "r"(bdesc));
}

__device__ __forceinline__ void wgmma_n64_p(float (&d)[8], float (&e)[24], const uint32_t (&a)[4], uint32_t bdesc, int acc) {
    asm volatile("{\n.reg .pred p;\n.reg .b64 b;\nsetp.ne.b32 p, %37, 0;\nmov.b64 b, {%36, " DESC_HI "};\n"
                 "wgmma.mma_async.sync.aligned.m64n64k16.f32.bf16.bf16 {%0,%1,%2,%3,%4,%5,%6,%7,%8,%9,%10,%11,%12,%13,%14,%15,%16,%17,%18,%19,%20,%21,%22,%23,%24,%25,%26,%27,%28,%29,%30,%31}, {%32,%33,%34,%35}, b, p, 1, 1, 1;\n}"
                 : "+f"(d[0]), "+f"(d[1]), "+f"(d[2]), "+f"(d[3]), "+f"(d[4]), "+f"(d[5]), "+f"(d[6]), "+f"(d[7]),
                   "+f"(e[0]), "+f"(e[1]), "+f"(e[2]), "+f"(e[3]), "+f"(e[4]), "+f"(e[5]), "+f"(e[6]), "+f"(e[7]), "+f"(e[8]), "+f"(e[9]), "+f"(e[10]), "+f"(e[11]), "+f"(e[12]), "+f"(e[13]), "+f"(e[14]), "+f"(e[15]), "+f"(e[16]), "+f"(e[17]), "+f"(e[18]), "+f"(e[19]), "+f"(e[20]), "+f"(e[21]), "+f"(e[22]), "+f"(e[23])
                 : "r"(a[0]), "r"(a[1]), "r"(a[2]), "r"(a[3]), "r"(bdesc), "r"(acc));
}
__device__ __forceinline__ void wgmma_n16_p(float (&d)[8], const uint32_t (&a)[4], uint32_t bdesc, int acc) {
    asm volatile("{\n.reg .pred p;\n.reg .b64 b;\nsetp.ne.b32 p, %13, 0;\nmov.b64 b, {%12, " DESC_HI "};\n"
                 "wgmma.mma_async.sync.aligned.m64n16k16.f32.bf16.bf16 {%0,%1,%2,%3,%4,%5,%6,%7}, {%8,%9,%10,%11}, b, p, 1, 1, 1;\n}"
                 : "+f"(d[0]), "+f"(d[1]), "+f"(d[2]), "+f"(d[3]), "+f"(d[4]), "+f"(d[5]), "+f"(d[6]), "+f"(d[7])
                 : "r"(a[0]), "r"(a[1]), "r"(a[2]), "r"(a[3]), "r"(bdesc), "r"(acc));
}

__device__ __forceinline__ uint32_t edge_dist(uint32_t sxy, uint32_t sz, uint32_t dxy, uint32_t dz, uint32_t& rxy, uint32_t& rz) {
    rxy = hsub2(sxy, dxy);
    rz  = hsub2(sz, dz);
    uint32_t qxy = hmul2(rxy, rxy), qz = hmul2(rz, rz);
    float ss = rbf((bf_lo(qxy) + bf_hi(qxy)) + bf_lo(qz));
    float s2 = rbf(ss + 1e-8f);
    float d;
    asm("sqrt.approx.ftz.f32 %0, %1;" : "=f"(d) : "f"(s2));
    return pack_bf(d, 0.f) & 0xffffu;
}

__device__ __forceinline__ void load_pos(uint32_t sm_pos, int i, uint32_t& xy, uint32_t& z) {
    uint32_t a  = (sm_pos + 6u * (uint32_t)i) & ~3u;
    uint32_t w0 = lds32(a), w1 = lds32(a + 4);
    uint32_t sh = (uint32_t)i << 4;
    xy = __funnelshift_r(w0, w1, sh);
    z  = __funnelshift_r(w1, w1, sh);
}

__device__ __noinline__ float radial_value(float d, float f) {
    float arg = rbf(d * f);
    float sn  = rbf(sinf(arg));
    float rb  = rbf(__fdiv_rn(sn, d));
    float c   = rbf(cosf(rbf(__fdiv_rn(rbf(d * 3.14159265358979323846f), 5.0f))));
    float fc  = rbf(0.5f * rbf(c + 1.0f));
    return rb * fc;
}

__global__ void __launch_bounds__(NT, 1)
painn_kernel(const Params p, const __grid_constant__ CUtensorMap tmF, const __grid_constant__ CUtensorMap tmFs) {
    extern __shared__ __align__(1024) uint8_t smem[];
    const uint32_t sb   = smem_u32(smem);
    const int tid  = threadIdx.x, lane = tid & 31, warp = __shfl_sync(0xffffffffu, tid >> 5, 0);
    const int cta  = blockIdx.x;
    const int g    = lane >> 2, t = lane & 3;
    int* binCnt = (int*)(smem + SM_BINCNT);
    int* binOff = (int*)(smem + SM_BINOFF);
    int* nCnt   = (int*)(smem + SM_NCNT);
    uint32_t* nInfo = (uint32_t*)(smem + SM_NINFO);
    volatile int* ctrl = (volatile int*)(smem + SM_CTRL);
    const uint32_t bar_pos = sb + SM_BARS, bar_mlp = bar_pos + 8, bar_rec = bar_pos + 16;
    const uint32_t bar_full = bar_pos + 32, bar_empty = bar_full + NCWG * MAX_STAGE * 8;
    const uint32_t bar_hfull = bar_empty + NCWG * MAX_STAGE * 8, bar_hempty = bar_hfull + 16;

    const int node0  = cta * p.npc;
    const int nnodes = max(0, min(p.npc, p.N - node0));

    STAMP(0);
    if (tid == 32) {
        mbar_init(bar_pos, 1);
        asm volatile("fence.mbarrier_init.release.cluster;" ::: "memory");
        uint32_t pos_bytes = (uint32_t)(p.N * 6 + 15) & ~15u;
        mbar_expect_tx(bar_pos, pos_bytes);
        bulk_g2s(sb + P1_POS, p.pos, pos_bytes, bar_pos);
    } else if (tid == 64) {
        mbar_init(bar_rec, 1);
        mbar_init(bar_hfull, 4); mbar_init(bar_hfull + 8, 4); mbar_init(bar_hempty, 4); mbar_init(bar_hempty + 8, 4);
        asm volatile("prefetch.tensormap [%0];" ::"l"(&tmF) : "memory");
        asm volatile("prefetch.tensormap [%0];" ::"l"(&tmFs) : "memory");
    } else if (tid >= 96 && tid < 96 + NCWG * MAX_STAGE) {
        mbar_init(bar_full + 8 * (tid - 96), 2);
        mbar_init(bar_empty + 8 * (tid - 96), 4);
    }
    unsigned bar_seen = 0;
    if (tid == 15 * 32) asm volatile("ld.relaxed.gpu.global.u32 %0, [%1];" : "=r"(bar_seen) : "l"(&g_bar) : "memory");
    const bool mlp_warp = warp >= 6;
    int4 s4[3], d4[3];
    const int q0 = cta * p.quads_per_cta;
    const int qend = min(q0 + p.quads_per_cta, p.E >> 2);
#pragma unroll
    for (int k = 0; k < 3; k++) {
        const int q = q0 + (k < 2 ? warp + 16 * k : 32 + warp) * 32 + lane;
        const bool ok = q < qend && (k < 2 || !mlp_warp);
        s4[k] = ok ? __ldg((const int4*)p.src + q) : make_int4(-1, -1, -1, -1);
        d4[k] = ok ? __ldg((const int4*)p.dst + q) : make_int4(0, 0, 0, 0);
    }
    for (int i = tid; i < nnodes * 32; i += NT) {
        const int r = i >> 5, b = (i >> 3) & 3, c = i & 7;
        cp_async16(sb + P1_SV + b * (MAX_NPC * 128) + r * 128 + ((c ^ (r & 7)) << 4), (const uint8_t*)p.sv + (size_t)node0 * 512 + i * 16);
    }
    for (int i = tid; i < 1024; i += NT) {
        const int m = i >> 9, k = (i >> 3) & 63, c = i & 7;
        cp_async16(sb + P1_W1 + m * 8192 + k * 128 + ((c ^ (k & 7)) << 4),
                   m == 0 ? (const uint8_t*)p.w1 + k * 128 + c * 16 : (const uint8_t*)p.w2 + k * 384 + 128 + c * 16);
    }
    asm volatile("cp.async.commit_group;" ::: "memory");
    if (tid < MAX_CTA) binCnt[tid] = 0;
    if (tid < MAX_NPC) nCnt[tid] = 0;
    if (tid < 16) ctrl[tid] = 0;
    if (tid >= 416 && tid < 416 + 48) {
        asm volatile("prefetch.global.L2 [%0];" ::"l"((const uint8_t*)p.wr + (tid - 416) * 128));
    }
    for (int i = P1_SEG / 16 + tid; i < P1_SV / 16; i += NT) sts128(sb + i * 16, make_uint4(0u, 0u, 0u, 0u));
    for (int i = tid; i < 4 * (MAX_NPC - nnodes) * 8; i += NT)
        sts128(sb + P1_SV + (i / ((MAX_NPC - nnodes) * 8)) * (MAX_NPC * 128) + nnodes * 128 + (i % ((MAX_NPC - nnodes) * 8)) * 16, make_uint4(0u, 0u, 0u, 0u));
    for (int i = P1_END / 16 + tid; i < SM_HT / 16; i += NT) sts128(sb + i * 16, make_uint4(0u, 0u, 0u, 0u));
    __syncthreads();

    if (!mlp_warp) {
        const int rows_per = (TAB_ROWS + 1 + p.ncta - 1) / p.ncta;
        for (int i = tid; i < rows_per * 8; i += 6 * 32) {
            int row = cta * rows_per + (i >> 3), kp = i & 7;
            if (row <= TAB_ROWS) {
                uint32_t val = 0;
                if (row < TAB_ROWS) {
                    float d = __uint_as_float((D_MIN_BITS + row) << 16);
                    uint32_t f2 = __ldg((const uint32_t*)p.freqs + kp);
                    val = pack_bf(radial_value(d, bf_lo(f2)), radial_value(d, bf_hi(f2)));
                }
                ((uint32_t*)g_table)[row * 8 + kp] = val;
            }
        }
    }
#pragma unroll
    for (int k = 0; k < 3; k++) {
        const int ss[4] = {s4[k].x, s4[k].y, s4[k].z, s4[k].w};
        const int dd[4] = {d4[k].x, d4[k].y, d4[k].z, d4[k].w};
        if (ss[0] >= 0) {
            uint32_t bin[4], rank[4];
#pragma unroll
            for (int j = 0; j < 4; j++) {
                bin[j]  = __umulhi((uint32_t)dd[j], p.npc_magic);
                rank[j] = (uint32_t)atomicAdd(&binCnt[bin[j]], 1);
            }
#pragma unroll
            for (int j = 0; j < 4; j++)
                if (rank[j] < SEG_W - 1)
                    sts32(sb + P1_SEG + (bin[j] * SEG_W + 1 + rank[j]) * 4, (uint32_t)ss[j] | (((uint32_t)dd[j] - bin[j] * (uint32_t)p.npc) << 16));
        }
    }
    asm volatile("cp.async.wait_group 0;" ::: "memory");
    __syncthreads();
    STAMP(1);

    if (mlp_warp) {
        const int mt = (warp - 6) >> 1, hf = (warp - 6) & 1;
        if (mt * 16 < nnodes) {
            STAMPT(10, 6 * 32);
            const int lrow = lane & 15, lch = lane >> 4;
            const uint32_t rowb = sb + P1_SV + (mt * 16 + lrow) * 128;
            const uint32_t key0 = lrow & 7;
            float acc[4][4];
#pragma unroll
            for (int i = 0; i < 4; i++) { acc[i][0] = acc[i][1] = acc[i][2] = acc[i][3] = 0.f; }
#pragma unroll
            for (int ks = 0; ks < 4; ks++) {
                uint32_t a[4];
                ldsm4(a, rowb + (((2 * ks + lch) ^ key0) << 4));
                const int kk = 16 * ks + lrow;
#pragma unroll
                for (int nt = 0; nt < 4; nt += 2) {
                    uint32_t b[4];
                    ldsm4t(b, sb + P1_W1 + kk * 128 + (((4 * hf + nt + lch) ^ (kk & 7)) << 4));
                    mma16816(acc[nt], a, b[0], b[1]);
                    mma16816(acc[nt + 1], a, b[2], b[3]);
                }
            }
            uint32_t hp[4][2];
#pragma unroll
            for (int i = 0; i < 4; i++) {
                float h[4];
#pragma unroll
                for (int q = 0; q < 4; q++) {
                    float x = rbf(acc[i][q]);
                    h[q] = __fdividef(x, 1.0f + __expf(-x));
                    acc[i][q] = 0.f;
                }
                hp[i][0] = pack_bf(h[0], h[1]);
                hp[i][1] = pack_bf(h[2], h[3]);
            }
            asm volatile("bar.sync %0, 64;" ::"r"(4 + mt) : "memory");
#pragma unroll
            for (int i = 0; i < 4; i += 2)
                stsm4(rowb + (((4 * hf + i + lch) ^ key0) << 4), hp[i][0], hp[i][1], hp[i + 1][0], hp[i + 1][1]);
            asm volatile("bar.sync %0, 64;" ::"r"(4 + mt) : "memory");
#pragma unroll
            for (int ks = 0; ks < 4; ks++) {
                uint32_t a[4];
                ldsm4(a, rowb + (((2 * ks + lch) ^ key0) << 4));
                const int kk = 16 * ks + lrow;
#pragma unroll
                for (int nt = 0; nt < 4; nt += 2) {
                    uint32_t b[4];
                    ldsm4t(b, sb + P1_W2 + kk * 128 + (((4 * hf + nt + lch) ^ (kk & 7)) << 4));
                    mma16816(acc[nt], a, b[0], b[1]);
                    mma16816(acc[nt + 1], a, b[2], b[3]);
                }
            }
            uint32_t vq[2][3][4];
            const uint32_t vb = sb + P1_SV + (mt * 16 + g) * 128 + 4 * t;
#pragma unroll
            for (int rh = 0; rh < 2; rh++)
#pragma unroll
                for (int a = 0; a < 3; a++)
#pragma unroll
                    for (int i = 0; i < 4; i++) vq[rh][a][i] = lds32(vb + (a + 1) * (MAX_NPC * 128) + rh * 1024 + (((4 * hf + i) ^ g) << 4));
#pragma unroll
            for (int rh = 0; rh < 2; rh++)
#pragma unroll
                for (int a = 0; a < 3; a++)
#pragma unroll
                    for (int i = 0; i < 4; i++)
                        sts32(vb + (a + 1) * (MAX_NPC * 128) + rh * 1024 + (((4 * hf + i) ^ g) << 4),
                              hmul2(pack_bf(acc[i][2 * rh], acc[i][2 * rh + 1]), vq[rh][a][i]));
            fence_async_smem();
            asm volatile("bar.sync %0, 64;" ::"r"(4 + mt) : "memory");
            {
                const int r4 = mt * 16 + 8 * hf + 4 * (lane >> 2), comp = lane & 3;
                if (lane < 8 && r4 < nnodes) tma_store3(&tmFs, comp, node0 + r4, sb + P1_SV + comp * (MAX_NPC * 128) + r4 * 128);
            }
            asm volatile("cp.async.bulk.commit_group;" ::: "memory");
        }
        STAMPT(11, 6 * 32);
    }
    STAMP(2);
    __syncthreads();
    STAMP(3);
    for (int b = 2 * warp + (lane >> 4); b < p.ncta; b += 32) {
        const int cnt = binCnt[b], nw = max(56, (min(cnt, SEG_W - 1) + 8) & ~7);
        uint32_t* dstp = g_seg + ((size_t)cta * MAX_CTA + b) * SEG_W;
        for (int j = lane & 15; j < nw; j += 16) dstp[j] = j == 0 ? (uint32_t)cnt : lds32(sb + P1_SEG + (b * SEG_W + j) * 4);
    }
    if (mlp_warp && lane < 8) {
        asm volatile("cp.async.bulk.wait_group 0;" ::: "memory");
        asm volatile("fence.proxy.async;" ::: "memory");
    }

    __syncthreads();
    STAMP(4);
    if (tid == 0) asm volatile("red.add.release.gpu.global.u32 [%0], 1;" ::"l"(&g_bar) : "memory");
    uint32_t wp[3][4];
    if (warp >= 4 && warp < 8) {
        const uint16_t* w2 = (const uint16_t*)p.w2 + 16 * (warp & 3) + g;
#pragma unroll 2
        for (int mk = 0; mk < 8; mk++) {
            uint32_t f[4];
#pragma unroll
            for (int i = 0; i < 4; i++) {
                const uint16_t* q = w2 + (16 * (mk & 3) + 2 * t + 8 * (i >> 1)) * 192 + (mk >> 2) * 128 + 8 * (i & 1);
                f[i] = (uint32_t)__ldg(q) | ((uint32_t)__ldg(q + 192) << 16);
            }
            sts128(sb + SM_HT + (mk * 128 + (tid & 127)) * 16, make_uint4(f[0], f[1], f[2], f[3]));
        }
    }
    if (warp < 12) {
        const uint16_t* wr = (const uint16_t*)p.wr + 16 * (warp & 3) + g;
#pragma unroll
        for (int ty = 0; ty < 3; ty++) {
#pragma unroll
            for (int i = 0; i < 4; i++) {
                const uint16_t* q = wr + (8 * (i >> 1) + 2 * t) * 192 + ty * 64 + 8 * (i & 1);
                wp[ty][i] = (uint32_t)__ldg(q) | ((uint32_t)__ldg(q + 192) << 16);
            }
        }
    }
    if (tid == 15 * 32) {
        const unsigned target = (bar_seen / (unsigned)p.ncta + 1u) * (unsigned)p.ncta;
        unsigned cur;
        int spins = 0;
        do {
            asm volatile("ld.acquire.gpu.global.u32 %0, [%1];" : "=r"(cur) : "l"(&g_bar) : "memory");
        } while ((int)(cur - target) < 0 && ++spins < (1 << 24));
    }
    __syncthreads();
    STAMP(5);

    mbar_wait(bar_pos, 0);
    constexpr int SEG_IT = (MAX_CTA + 31) / 32;
    uint32_t sw[SEG_IT][3];
    int scnt[SEG_IT];
#pragma unroll
    for (int it = 0; it < SEG_IT; it++) {
        const int b = 2 * warp + (lane >> 4) + 32 * it;
        const uint32_t* sp = g_seg + ((size_t)b * MAX_CTA + cta) * SEG_W;
        scnt[it] = b < p.ncta ? (int)__ldcg(sp) : 0;
    }
#pragma unroll
    for (int it = 0; it < SEG_IT; it++) {
        const int b = 2 * warp + (lane >> 4) + 32 * it;
        const uint32_t* sp = g_seg + ((size_t)b * MAX_CTA + cta) * SEG_W + 1 + (lane & 15);
#pragma unroll
        for (int u = 0; u < 3; u++) sw[it][u] = b < p.ncta ? __ldcg(sp + 16 * u) : 0u;
    }
    STAMP(13);
#pragma unroll
    for (int it = 0; it < SEG_IT; it++) {
        const int b = 2 * warp + (lane >> 4) + 32 * it;
        const int cnt = scnt[it];
        if (cnt > SEG_W - 1) ctrl[1] = 1;
        const int n = min(cnt, SEG_W - 1), nmax = max(n, __shfl_xor_sync(0xffffffffu, n, 16));
        for (int j0 = lane & 15; j0 - (lane & 15) < nmax; j0 += 48) {
            uint32_t wd[3], w0[3], w1[3], v0[3], v1[3];
            uint4 rec[3];
            bool act[3];
            if (j0 < 16) {
#pragma unroll
                for (int u = 0; u < 3; u++) wd[u] = j0 + 16 * u < n ? sw[it][u] : 0u;
            } else {
#pragma unroll
                for (int u = 0; u < 3; u++)
                    wd[u] = j0 + 16 * u < n ? __ldcg(g_seg + ((size_t)b * MAX_CTA + cta) * SEG_W + 1 + j0 + 16 * u) : 0u;
            }
#pragma unroll
            for (int u = 0; u < 3; u++) {
                const uint32_t a = (sb + P1_POS + 6u * (wd[u] & 0xffffu)) & ~3u, c = (sb + P1_POS + 6u * ((uint32_t)node0 + (wd[u] >> 16))) & ~3u;
                w0[u] = lds32(a); w1[u] = lds32(a + 4); v0[u] = lds32(c); v1[u] = lds32(c + 4);
            }
#pragma unroll
            for (int u = 0; u < 3; u++) {
                const uint32_t s = wd[u] & 0xffffu, dl = wd[u] >> 16, sh = s << 4, dh = ((uint32_t)node0 + dl) << 4;
                uint32_t rxy, rz;
                const uint32_t db = edge_dist(__funnelshift_r(w0[u], w1[u], sh), __funnelshift_r(w1[u], w1[u], sh),
                                              __funnelshift_r(v0[u], v1[u], dh), __funnelshift_r(v1[u], v1[u], dh), rxy, rz);
                act[u] = j0 + 16 * u < n && db <= D_MAX_BITS;
                float inv;
                asm("rcp.approx.ftz.f32 %0, %1;" : "=f"(inv) : "f"(__uint_as_float(db << 16)));
                rec[u].x = s | ((db - D_MIN_BITS) << 16);
                rec[u].y = pack_bf(bf_lo(rxy) * inv, bf_hi(rxy) * inv);
                rec[u].z = __byte_perm(pack_bf(bf_lo(rz) * inv, 0.f), dl, 0x5410);
            }
#pragma unroll
            for (int u = 0; u < 3; u++) rec[u].w = act[u] ? (uint32_t)atomicAdd(&nCnt[wd[u] >> 16], 1) : 0u;
            const unsigned am0 = __ballot_sync(0xffffffffu, act[0]), am1 = __ballot_sync(0xffffffffu, act[1]), am2 = __ballot_sync(0xffffffffu, act[2]);
            int base = 0;
            if (lane == 0) base = atomicAdd((int*)&ctrl[8], __popc(am0) + __popc(am1) + __popc(am2));
            base = __shfl_sync(0xffffffffu, base, 0);
            const unsigned lt = (1u << lane) - 1u;
            const int p0 = base + __popc(am0 & lt), p1 = base + __popc(am0) + __popc(am1 & lt), p2 = base + __popc(am0) + __popc(am1) + __popc(am2 & lt);
            if (act[0] && p0 < STAGE_CAP) sts128(sb + P1_REC + p0 * 16, rec[0]);
            if (act[1] && p1 < STAGE_CAP) sts128(sb + P1_REC + p1 * 16, rec[1]);
            if (act[2] && p2 < STAGE_CAP) sts128(sb + P1_REC + p2 * 16, rec[2]);
        }
    }
    __syncthreads();
    const int total = ctrl[8];
    if (tid == 0 && total > STAGE_CAP) ctrl[1] = 1;
    if (warp == 0) {
        int c[3], s = 0;
#pragma unroll
        for (int i = 0; i < 3; i++) {
            int b = lane * 3 + i;
            c[i] = b < nnodes ? max(16, (nCnt[b] + 15) & ~15) : 0;
            s += c[i];
        }
        int x = s;
#pragma unroll
        for (int o = 1; o < 32; o <<= 1) { int y = __shfl_up_sync(0xffffffffu, x, o); if (lane >= o) x += y; }
        const int slots = __shfl_sync(0xffffffffu, x, 31);
        int off = x - s, below = 0;
#pragma unroll
        for (int i = 0; i < 3; i++) {
            int b = lane * 3 + i;
            if (b < nnodes) {
                nInfo[b] = (uint32_t)off | ((uint32_t)c[i] << 16);
                below += (2 * off + c[i] < slots);
            }
            off += c[i];
        }
        below = __reduce_add_sync(0xffffffffu, below);
        if (lane == 0) {
            ctrl[2] = below;
            ctrl[4] = slots;
            if (slots > SLOT_CAP) ctrl[1] = 1;
        }
    }
    __syncthreads();
    if (ctrl[1] == 0) {
        uint16_t* sid = (uint16_t*)(smem + SM_SID);
        uint2* meta = (uint2*)(smem + SM_META);
        for (int i = tid; i < total; i += 2 * NT) {
            const bool two = i + NT < total;
            const uint4 r = lds128(sb + P1_REC + i * 16);
            const uint4 q = two ? lds128(sb + P1_REC + (i + NT) * 16) : r;
            const int pos = (int)(lds32(sb + SM_NINFO + (r.z >> 16) * 4) & 0xffffu) + (int)r.w;
            const int pos2 = (int)(lds32(sb + SM_NINFO + (q.z >> 16) * 4) & 0xffffu) + (int)q.w;
            sid[pos]  = (uint16_t)((r.x & 0xffffu) << 2);
            meta[pos] = make_uint2(((r.x >> 16) << 5) | (r.z << 16), r.y);
            if (two) {
                sid[pos2]  = (uint16_t)((q.x & 0xffffu) << 2);
                meta[pos2] = make_uint2(((q.x >> 16) << 5) | (q.z << 16), q.y);
            }
        }
        if (tid >= NT - 128 && tid - (NT - 128) < nnodes) {
            const int b = tid - (NT - 128), split = ctrl[2];
            const int mid = split < nnodes ? (int)(nInfo[split] & 0xffffu) : ctrl[4];
            const int st = b >= split;
            const int mine = (int)(nInfo[b] & 0xffffu) + (int)(nInfo[b] >> 16) - (st ? mid : 0);
            int lo = st ? 0 : split, hi = st ? split : nnodes;
            const int first = lo;
            while (lo < hi) {
                const int o = (lo + hi) >> 1;
                const int other = (int)(nInfo[o] & 0xffffu) + (int)(nInfo[o] >> 16) - (st ? 0 : mid);
                if (st ? (other <= mine) : (other < mine)) lo = o + 1; else hi = o;
            }
            const int rank = (st ? b - split : b) + lo - first;
            smem[SM_ORDER + rank] = (uint8_t)(b | (st << 7));
        }
        for (int i = tid; i < nnodes * 16; i += NT) {
            int nl = i >> 4, c = nCnt[nl];
            int j = (c & ~15) + (i & 15);
            if (j >= c && (j < 16 || (c & 15))) {
                int pos = (int)(nInfo[nl] & 0xffffu) + j;
                sid[pos]  = 0xffffu;
                meta[pos] = make_uint2((uint32_t)TAB_ZERO << 5, 0u);
            }
        }
    }
    fence_async_smem();
    __syncthreads();
    STAMP(6);

    if (__shfl_sync(0xffffffffu, ctrl[1], 0) != 0) {
        float* acc = (float*)(smem + P1_POS);
        for (int i = tid; i < nnodes * 256; i += NT) acc[i] = 0.f;
        __syncthreads();
        const uint16_t* posu = (const uint16_t*)p.pos;
        const uint32_t* tabg = (const uint32_t*)g_table;
        const uint32_t* Fw = (const uint32_t*)g_F;
        for (int e0 = warp * 32; e0 < p.E; e0 += NT) {
            int e = e0 + lane;
            int s = 0, d = 0;
            uint32_t db = 0xffff, rxy = 0, rz = 0;
            bool act = false;
            if (e < p.E) {
                s = p.src[e]; d = p.dst[e];
                if (d >= node0 && d < node0 + nnodes) {
                    uint32_t sxy = posu[s * 3] | ((uint32_t)posu[s * 3 + 1] << 16), sz = posu[s * 3 + 2];
                    uint32_t dxy = posu[d * 3] | ((uint32_t)posu[d * 3 + 1] << 16), dz = posu[d * 3 + 2];
                    db  = edge_dist(sxy, sz, dxy, dz, rxy, rz);
                    act = db <= D_MAX_BITS;
                }
            }
            unsigned m = __ballot_sync(0xffffffffu, act);
            while (m) {
                int l = __ffs(m) - 1;
                m &= m - 1;
                int es = __shfl_sync(0xffffffffu, s, l), ed = __shfl_sync(0xffffffffu, d, l);
                uint32_t edb = __shfl_sync(0xffffffffu, db, l), exy = __shfl_sync(0xffffffffu, rxy, l), ez = __shfl_sync(0xffffffffu, rz, l);
                float inv = 1.0f / __uint_as_float(edb << 16);
                float rh[3] = {rbf(bf_lo(exy) * inv), rbf(bf_hi(exy) * inv), rbf(bf_lo(ez) * inv)};
                const uint32_t* fr = Fw + (size_t)es * 128 + lane;
                const uint32_t fh = __ldcg(fr);
                const uint32_t q[3] = {__ldcg(fr + 32), __ldcg(fr + 64), __ldcg(fr + 96)};
                float ps0 = 0.f, ps1 = 0.f, pr0 = 0.f, pr1 = 0.f;
                for (int j2 = 0; j2 < 32; j2++) {
                    uint32_t hj = __shfl_sync(0xffffffffu, fh, j2);
                    uint32_t a0 = *(const uint32_t*)(p.w2 + (2 * j2) * 192 + 2 * lane), a1 = *(const uint32_t*)(p.w2 + (2 * j2 + 1) * 192 + 2 * lane);
                    uint32_t b0 = *(const uint32_t*)(p.w2 + (2 * j2) * 192 + 128 + 2 * lane), b1 = *(const uint32_t*)(p.w2 + (2 * j2 + 1) * 192 + 128 + 2 * lane);
                    ps0 += bf_lo(hj) * bf_lo(a0) + bf_hi(hj) * bf_lo(a1);
                    ps1 += bf_lo(hj) * bf_hi(a0) + bf_hi(hj) * bf_hi(a1);
                    pr0 += bf_lo(hj) * bf_lo(b0) + bf_hi(hj) * bf_lo(b1);
                    pr1 += bf_lo(hj) * bf_hi(b0) + bf_hi(hj) * bf_hi(b1);
                }
                float ws0 = 0.f, ws1 = 0.f, wv0 = 0.f, wv1 = 0.f, wr0 = 0.f, wr1 = 0.f;
                for (int k2 = 0; k2 < 8; k2++) {
                    uint32_t rk2 = __ldcg(tabg + (edb - D_MIN_BITS) * 8 + k2);
#pragma unroll
                    for (int h = 0; h < 2; h++) {
                        float rv = h ? bf_hi(rk2) : bf_lo(rk2);
                        const __nv_bfloat16* wrow = p.wr + (2 * k2 + h) * 192 + 2 * lane;
                        uint32_t a = *(const uint32_t*)wrow, b = *(const uint32_t*)(wrow + 64), c = *(const uint32_t*)(wrow + 128);
                        ws0 += rv * bf_lo(a); ws1 += rv * bf_hi(a);
                        wv0 += rv * bf_lo(b); wv1 += rv * bf_hi(b);
                        wr0 += rv * bf_lo(c); wr1 += rv * bf_hi(c);
                    }
                }
                float* a = acc + (ed - node0) * 256 + 2 * lane;
                atomicAdd(a, ps0 * ws0); atomicAdd(a + 1, ps1 * ws1);
#pragma unroll
                for (int c = 0; c < 3; c++) {
                    atomicAdd(a + 64 * (c + 1), wv0 * bf_lo(q[c]) + pr0 * wr0 * rh[c]);
                    atomicAdd(a + 64 * (c + 1) + 1, wv1 * bf_hi(q[c]) + pr1 * wr1 * rh[c]);
                }
            }
        }
        __syncthreads();
        for (int i = tid; i < nnodes * 128; i += NT) {
            uint32_t r = *(const uint32_t*)(p.sv + (size_t)node0 * 256 + 2 * i);
            *(uint32_t*)(p.out + (size_t)node0 * 256 + 2 * i) = pack_bf(bf_lo(r) + acc[2 * i], bf_hi(r) + acc[2 * i + 1]);
        }
        return;
    }

    const int slots = __reduce_max_sync(0xffffffffu, ctrl[4]);
    const int split = __reduce_max_sync(0xffffffffu, ctrl[2]);
    const int nstage = slots <= SLOT_CAP4 ? 6 : 5;
    const uint32_t ring = sb + (nstage == 6 ? SM_RING4 : SM_RING3);
    const int mid = __reduce_max_sync(0xffffffffu, split < nnodes ? (int)(nInfo[split] & 0xffffu) : slots) >> 4;
    const int wgi = warp >> 2, w = warp & 3;
    constexpr uint32_t EMPTY_OFF = NCWG * MAX_STAGE * 8;
    if (wgi == 3) {
        const int sc = w >> 1, r = w & 1;
        const int g0 = (sc == 0 ? 0 : mid) + r, g1 = sc == 0 ? mid : slots >> 4;
        const uint32_t ring_wg = ring + sc * nstage * STAGE_B, full_wg = bar_full + sc * MAX_STAGE * 8;
        const int e = lane >> 1, half = lane & 1;
        const uint32_t coef_off = e * 128 + ((half ^ (e & 7)) << 4);
        const int vrot = (e & 3) ^ ((e >> 1) & 3);
        const uint8_t* tab = (const uint8_t*)g_table + half * 16;
        int stage = r;
        uint32_t phase = 1;
        uint32_t ma = sb + SM_META + (g0 * 16 + e) * 8, ida = sb + SM_SID + g0 * 32;
        uint2 m = make_uint2(0u, 0u);
        uint4 tv = make_uint4(0u, 0u, 0u, 0u), ia = tv, ib = tv;
        if (g0 < g1) {
            m  = lds64(ma);
            ia = lds128(ida);
            ib = lds128(ida + 16);
            tv = __ldg((const uint4*)(tab + (m.x & 0xffffu)));
        }
        for (int left = (g1 - g0 + 1) >> 1; left > 0; left--) {
            const uint32_t st = ring_wg + stage * STAGE_B, fb = full_wg + stage * 8;
            uint4 o[4];
            {
                const uint32_t mul[4] = {0x3f803f80u, __byte_perm(m.y, 0, 0x1010), __byte_perm(m.y, 0, 0x3232), __byte_perm(m.x, 0, 0x3232)};
#pragma unroll
                for (int j = 0; j < 4; j++) {
                    const int v = j ^ vrot;
                    const uint32_t lo = (v & 1) ? mul[1] : mul[0], hi = (v & 1) ? mul[3] : mul[2];
                    const uint32_t mm = (v & 2) ? hi : lo;
                    o[j] = make_uint4(hmul2(tv.x, mm), hmul2(tv.y, mm), hmul2(tv.z, mm), hmul2(tv.w, mm));
                }
            }
            ma += 256; ida += 64;
            if (left > 1) m = lds64(ma);
            mbar_wait(fb + EMPTY_OFF, phase);
            uint32_t leader;
            asm volatile("{\n.reg .pred p;\nelect.sync _|p, 0xffffffff;\nselp.u32 %0, 1, 0, p;\n}" : "=r"(leader));
            if (leader) {
                const uint32_t id2[8] = {ia.x, ia.y, ia.z, ia.w, ib.x, ib.y, ib.z, ib.w};
                const uint32_t rows = st + 2048;
                if ((ib.w >> 16) != 0xffffu) {
                    mbar_expect_tx(fb, 16 * 512);
#pragma unroll
                    for (int i = 0; i < 8; i++) {
                        tma_load(rows + (2 * i) * 640, &tmF, (int)(id2[i] & 0xffffu), fb);
                        tma_load(rows + (2 * i + 1) * 640, &tmF, (int)(id2[i] >> 16), fb);
                    }
                } else {
                    int nv = 0;
#pragma unroll
                    for (int i = 0; i < 8; i++) nv += ((id2[i] & 0xffffu) != 0xffffu) + ((id2[i] >> 16) != 0xffffu);
                    mbar_expect_tx(fb, (uint32_t)nv * 512u);
#pragma unroll
                    for (int q = 0; q < 4; q++) {
                        if (4 * q + 4 <= nv) {
                            tma_load(rows + (4 * q) * 640, &tmF, (int)(id2[2 * q] & 0xffffu), fb);
                            tma_load(rows + (4 * q + 1) * 640, &tmF, (int)(id2[2 * q] >> 16), fb);
                            tma_load(rows + (4 * q + 2) * 640, &tmF, (int)(id2[2 * q + 1] & 0xffffu), fb);
                            tma_load(rows + (4 * q + 3) * 640, &tmF, (int)(id2[2 * q + 1] >> 16), fb);
                        } else {
                            if (4 * q < nv)     tma_load(rows + (4 * q) * 640, &tmF, (int)(id2[2 * q] & 0xffffu), fb);
                            if (4 * q + 1 < nv) tma_load(rows + (4 * q + 1) * 640, &tmF, (int)(id2[2 * q] >> 16), fb);
                            if (4 * q + 2 < nv) tma_load(rows + (4 * q + 2) * 640, &tmF, (int)(id2[2 * q + 1] & 0xffffu), fb);
                        }
                    }
                }
            }
            __syncwarp();
            if (left > 1) {
                ia = lds128(ida);
                ib = lds128(ida + 16);
                tv = __ldg((const uint4*)(tab + (m.x & 0xffffu)));
            }
            const uint32_t a = st + coef_off;
#pragma unroll
            for (int j = 0; j < 4; j++) sts128(a ^ ((j ^ vrot) << 5), o[j]);
            fence_async_smem();
            __syncwarp();
            mbar_arrive_elected(fb);
            stage += 2;
            if (stage >= nstage) { stage -= nstage; phase ^= 1; }
        }
    } else if (wgi == 2) {
        uint32_t wA[2][4][4];
#pragma unroll
        for (int mk = 0; mk < 8; mk++) {
            const uint4 q = lds128(sb + SM_HT + (mk * 128 + (tid & 127)) * 16);
            wA[mk >> 2][mk & 3][0] = q.x; wA[mk >> 2][mk & 3][1] = q.y; wA[mk >> 2][mk & 3][2] = q.z; wA[mk >> 2][mk & 3][3] = q.w;
        }
        __syncwarp();
        mbar_arrive_elected(bar_hempty);
        mbar_arrive_elected(bar_hempty + 8);
        const uint32_t lane_off = (uint32_t)node0 * 512u + t * 128 + w * 32 + (g & 1) * 16 + (g >> 1) * 4;
        uint32_t hpar = 0;
        float zs[8], zv[24], pvv[6], pr[4][2];
        auto start = [&](int ent) {
            const int c = ent >> 7;
            mbar_wait(bar_hfull + c * 8, (hpar >> c) & 1);
            hpar ^= 1u << c;
            const uint32_t dht = desc_lo(sb + SM_HT + c * 8192);
            wg_fence();
            wgmma_n16_first(zs, wA[0][0], dht);
            wgmma_n48_first(zv, wA[1][0], dht + 2);
#pragma unroll
            for (int ks = 1; ks < 4; ks++) {
                wgmma_n16(zs, wA[0][ks], dht + ks * 128);
                wgmma_n48(zv, wA[1][ks], dht + ks * 128 + 2);
            }
            wg_commit();
        };
        auto side = [&](int ent) {
            const int c = ent >> 7;
            const uint32_t pa = sb + SM_PV + c * 3072 + (tid & 127) * 8;
            const uint2 a0 = lds64(pa), a1 = lds64(pa + 1024), a2 = lds64(pa + 2048);
            pvv[0] = __uint_as_float(a0.x); pvv[1] = __uint_as_float(a0.y); pvv[2] = __uint_as_float(a1.x);
            pvv[3] = __uint_as_float(a1.y); pvv[4] = __uint_as_float(a2.x); pvv[5] = __uint_as_float(a2.y);
            __syncwarp();
            mbar_arrive_elected(bar_hempty + c * 8);
        };
        auto weigh = [&]() {
#pragma unroll
            for (int i = 0; i < 12; i++) asm volatile("" : "+r"(wp[i >> 2][i & 3]));
            pr[0][0] = bf_lo(wp[0][0]) * zs[0] + bf_hi(wp[0][0]) * zs[1] + bf_lo(wp[0][2]) * zs[4] + bf_hi(wp[0][2]) * zs[5];
            pr[0][1] = bf_lo(wp[0][1]) * zs[2] + bf_hi(wp[0][1]) * zs[3] + bf_lo(wp[0][3]) * zs[6] + bf_hi(wp[0][3]) * zs[7];
#pragma unroll
            for (int a = 0; a < 3; a++) {
                const float* y = zv + 8 * a;
                pr[a + 1][0] = pvv[2 * a] + bf_lo(wp[2][0]) * y[0] + bf_hi(wp[2][0]) * y[1] + bf_lo(wp[2][2]) * y[4] + bf_hi(wp[2][2]) * y[5];
                pr[a + 1][1] = pvv[2 * a + 1] + bf_lo(wp[2][1]) * y[2] + bf_hi(wp[2][1]) * y[3] + bf_lo(wp[2][3]) * y[6] + bf_hi(wp[2][3]) * y[7];
            }
            asm volatile("" : "+f"(pr[0][0]), "+f"(pr[0][1]), "+f"(pr[1][0]), "+f"(pr[1][1]), "+f"(pr[2][0]), "+f"(pr[2][1]), "+f"(pr[3][0]), "+f"(pr[3][1]) :: "memory");
        };
        auto finish = [&](int ent, uint32_t resid) {
            const bool hi2 = t & 2, hi1 = t & 1, odd = g & 1;
            float ka0 = hi2 ? pr[2][0] : pr[0][0], ka1 = hi2 ? pr[2][1] : pr[0][1];
            float kb0 = hi2 ? pr[3][0] : pr[1][0], kb1 = hi2 ? pr[3][1] : pr[1][1];
            float sa0 = hi2 ? pr[0][0] : pr[2][0], sa1 = hi2 ? pr[0][1] : pr[2][1];
            float sb0 = hi2 ? pr[1][0] : pr[3][0], sb1 = hi2 ? pr[1][1] : pr[3][1];
            ka0 += __shfl_xor_sync(0xffffffffu, sa0, 2); ka1 += __shfl_xor_sync(0xffffffffu, sa1, 2);
            kb0 += __shfl_xor_sync(0xffffffffu, sb0, 2); kb1 += __shfl_xor_sync(0xffffffffu, sb1, 2);
            float k0 = hi1 ? kb0 : ka0, k1 = hi1 ? kb1 : ka1;
            float s0 = hi1 ? ka0 : kb0, s1 = hi1 ? ka1 : kb1;
            k0 += __shfl_xor_sync(0xffffffffu, s0, 1);
            k1 += __shfl_xor_sync(0xffffffffu, s1, 1);
            const float other = __shfl_xor_sync(0xffffffffu, odd ? k0 : k1, 4);
            const float lo = odd ? other : k0, hi = odd ? k1 : other;
            *(uint32_t*)((uint8_t*)p.out + (lane_off + (uint32_t)(ent & 127) * 512u)) = pack_bf(bf_lo(resid) + lo, bf_hi(resid) + hi);
        };
        auto entry = [&](int i) -> int { return __reduce_max_sync(0xffffffffu, (int)smem[SM_ORDER + i]); };
        auto load_resid = [&](int ent) -> uint32_t { return __ldg((const uint32_t*)((const uint8_t*)p.sv + (lane_off + (uint32_t)(ent & 127) * 512u))); };
        if (nnodes > 0) {
            int cur = entry(0), nxt = entry(1);
            uint32_t resid = load_resid(cur);
            start(cur);
#pragma unroll 1
            for (int i = 1; i < nnodes; i++) {
                wg_wait0();
                side(cur);
                weigh();
                start(nxt);
                finish(cur, resid);
                cur = nxt;
                resid = load_resid(cur);
                nxt = entry(i + 1);
            }
            wg_wait0();
            side(cur);
            weigh();
            finish(cur, resid);
        }
    } else {
        const int wg = wgi;
        uint32_t aoff[4];
        {
            const int e = (lane & 7) + 8 * (lane >> 4), ch = 2 * w + ((lane >> 3) & 1);
#pragma unroll
            for (int b = 0; b < 4; b++) aoff[b] = 2048 + e * 640 + b * 128 + ((ch ^ ((5 * e + b) & 7)) << 4);
        }
        const uint32_t stsm_a = sb + SM_HT + wg * 8192 + (16 * w + (lane & 15)) * 128 + (((lane >> 4) ^ (lane & 7)) << 4);
        const uint32_t pv_a = sb + SM_PV + wg * 3072 + (tid & 127) * 8;
        const uint32_t ring_wg = ring + wg * nstage * STAGE_B;
        const uint32_t full_wg = bar_full + wg * MAX_STAGE * 8;

        float ys[8], yv[24], dQ[3][8];
        uint32_t A0[4][4], A1[4][4];
#pragma unroll
        for (int i = 0; i < 24; i++) yv[i] = 0.f;
#pragma unroll
        for (int i = 0; i < 8; i++) { ys[i] = 0.f; dQ[0][i] = 0.f; dQ[1][i] = 0.f; dQ[2][i] = 0.f; }
        int left = wg == 0 ? mid : (slots >> 4) - mid;
        int fstage = 0;
        uint32_t fphase = 0, fst = ring_wg, fbar = full_wg, hphase = 0;
        uint32_t ninfo_a = sb + SM_NINFO + (wg == 0 ? 0 : split) * 4;
        int gi = 0, G = __reduce_max_sync(0xffffffffu, (int)(lds32(ninfo_a) >> 20));

        auto fetch = [&](uint32_t (&A)[4][4], uint32_t& bd, uint32_t& eb) {
            mbar_wait(fbar, fphase);
#pragma unroll
            for (int b = 0; b < 4; b++) ldsm4t(A[b], fst + aoff[b]);
            bd = desc_lo(fst);
            eb = fbar + EMPTY_OFF;
            fst += STAGE_B; fbar += 8;
            if (++fstage == nstage) { fstage = 0; fphase ^= 1; fst = ring_wg; fbar = full_wg; }
        };
        auto step = [&](uint32_t (&Ac)[4][4], uint32_t bdc, uint32_t ebc, uint32_t (&An)[4][4], uint32_t& bdn, uint32_t& ebn) {
            wg_fence();
            wgmma_n64_p(ys, yv, Ac[0], bdc, gi);
            wgmma_n16_p(dQ[0], Ac[1], bdc, gi);
            wgmma_n16_p(dQ[1], Ac[2], bdc, gi);
            wgmma_n16_p(dQ[2], Ac[3], bdc, gi);
            wg_commit();
            if (--left > 0) fetch(An, bdn, ebn);
            const bool last = ++gi == G;
            uint32_t info_next = 0;
            if (last) { ninfo_a += 4; info_next = lds32(ninfo_a); }
            wg_wait0();
            mbar_arrive_elected(ebc);
            if (last) {
                mbar_wait(bar_hempty + wg * 8, hphase);
                hphase ^= 1;
                stsm4(stsm_a, pack_bf(ys[0], ys[1]), pack_bf(ys[2], ys[3]), pack_bf(ys[4], ys[5]), pack_bf(ys[6], ys[7]));
#pragma unroll
                for (int i = 0; i < 6; i += 2) {
                    stsm4(stsm_a ^ ((i + 2) << 4),
                          pack_bf(yv[4 * i], yv[4 * i + 1]), pack_bf(yv[4 * i + 2], yv[4 * i + 3]),
                          pack_bf(yv[4 * i + 4], yv[4 * i + 5]), pack_bf(yv[4 * i + 6], yv[4 * i + 7]));
                }
#pragma unroll
                for (int i = 0; i < 4; i++) asm volatile("" : "+r"(wp[1][i]));
#pragma unroll
                for (int a = 0; a < 3; a++) {
                    const float* q = dQ[a];
                    const float p0 = bf_lo(wp[1][0]) * q[0] + bf_hi(wp[1][0]) * q[1] + bf_lo(wp[1][2]) * q[4] + bf_hi(wp[1][2]) * q[5];
                    const float p1 = bf_lo(wp[1][1]) * q[2] + bf_hi(wp[1][1]) * q[3] + bf_lo(wp[1][3]) * q[6] + bf_hi(wp[1][3]) * q[7];
                    asm volatile("st.shared.v2.f32 [%0], {%1, %2};" ::"r"(pv_a + a * 1024), "f"(p0), "f"(p1) : "memory");
                }
                fence_async_smem();
                __syncwarp();
                mbar_arrive_elected(bar_hfull + wg * 8);
                G = __reduce_max_sync(0xffffffffu, (int)(info_next >> 20));
                gi = 0;
            }
        };
        if (left > 0) {
            uint32_t bd0, eb0, bd1 = 0, eb1 = 0;
            fetch(A0, bd0, eb0);
            while (true) {
                step(A0, bd0, eb0, A1, bd1, eb1);
                if (left <= 0) break;
                step(A1, bd1, eb1, A0, bd0, eb0);
                if (left <= 0) break;
            }
        }
    }
    STAMP(8);
}

typedef CUresult (*EncodeFn)(CUtensorMap*, CUtensorMapDataType, cuuint32_t, void*, const cuuint64_t*, const cuuint64_t*,
                             const cuuint32_t*, const cuuint32_t*, CUtensorMapInterleave, CUtensorMapSwizzle,
                             CUtensorMapL2promotion, CUtensorMapFloatOOBfill);

void make_map(EncodeFn enc, CUtensorMap* tm, const void* base, uint64_t lines, uint32_t box) {
    cuuint64_t gd[2] = {64, lines};
    cuuint64_t gs[1] = {128};
    cuuint32_t bd[2] = {64, box};
    cuuint32_t es[2] = {1, 1};
    enc(tm, CU_TENSOR_MAP_DATA_TYPE_BFLOAT16, 2, const_cast<void*>(base), gd, gs, bd, es, CU_TENSOR_MAP_INTERLEAVE_NONE,
        CU_TENSOR_MAP_SWIZZLE_128B, CU_TENSOR_MAP_L2_PROMOTION_L2_128B, CU_TENSOR_MAP_FLOAT_OOB_FILL_NONE);
}

void make_map3(EncodeFn enc, CUtensorMap* tm, const void* base, uint64_t nodes, uint32_t box) {
    cuuint64_t gd[3] = {64, 4, nodes};
    cuuint64_t gs[2] = {128, 512};
    cuuint32_t bd[3] = {64, 1, box};
    cuuint32_t es[3] = {1, 1, 1};
    enc(tm, CU_TENSOR_MAP_DATA_TYPE_BFLOAT16, 3, const_cast<void*>(base), gd, gs, bd, es, CU_TENSOR_MAP_INTERLEAVE_NONE,
        CU_TENSOR_MAP_SWIZZLE_128B, CU_TENSOR_MAP_L2_PROMOTION_L2_128B, CU_TENSOR_MAP_FLOAT_OOB_FILL_NONE);
}

}

extern "C" void kernel_launch(void* const* d_in, const int* in_sizes, int n_in, void* d_out, int out_size) {
    (void)n_in; (void)out_size;
    static int n_sm = 0;
    static EncodeFn enc = nullptr;
    static void* f_ptr = nullptr;
    if (n_sm == 0) {
        int dev = 0;
        cudaGetDevice(&dev);
        cudaDeviceGetAttribute(&n_sm, cudaDevAttrMultiProcessorCount, dev);
        cudaFuncSetAttribute(painn_kernel, cudaFuncAttributeMaxDynamicSharedMemorySize, SM_TOTAL);
        void* fn = nullptr;
        cudaDriverEntryPointQueryResult qr;
        cudaGetDriverEntryPoint("cuTensorMapEncodeTiled", &fn, cudaEnableDefault, &qr);
        enc = (EncodeFn)fn;
        cudaGetSymbolAddress(&f_ptr, g_F);
    }
    Params p;
    p.sv    = (const __nv_bfloat16*)d_in[0];
    p.pos   = (const __nv_bfloat16*)d_in[1];
    p.src   = (const int*)d_in[2];
    p.dst   = (const int*)d_in[3];
    p.freqs = (const __nv_bfloat16*)d_in[4];
    p.w1    = (const __nv_bfloat16*)d_in[5];
    p.w2    = (const __nv_bfloat16*)d_in[6];
    p.wr    = (const __nv_bfloat16*)d_in[7];
    p.out   = (__nv_bfloat16*)d_out;
    p.N = in_sizes[1] / 3;
    p.E = in_sizes[2];
    p.ncta = n_sm < MAX_CTA ? n_sm : MAX_CTA;
    p.npc = ((p.N + p.ncta - 1) / p.ncta + 3) & ~3;
    p.npc_magic = (uint32_t)(0x100000000ull / (uint32_t)p.npc) + 1u;
    p.quads_per_cta = ((p.E >> 2) + p.ncta - 1) / p.ncta;
    if (!enc || p.N > MAX_N || p.npc > MAX_NPC || (p.E & 3) || p.quads_per_cta > MAX_ROUNDS * 32) return;

    CUtensorMap tmF, tmFs;
    make_map(enc, &tmF, f_ptr, (uint64_t)p.N * 4, 4);
    make_map3(enc, &tmFs, f_ptr, (uint64_t)p.N, 4);

    cudaLaunchConfig_t cfg = {};
    cfg.gridDim = dim3(p.ncta);
    cfg.blockDim = dim3(NT);
    cfg.dynamicSmemBytes = SM_TOTAL;
    cfg.stream = cudaStreamPerThread;
    cudaLaunchAttribute attr[1];
    attr[0].id = cudaLaunchAttributeCooperative;
    attr[0].val.cooperative = 1;
    cfg.attrs = attr;
    cfg.numAttrs = 1;
    cudaLaunchKernelEx(&cfg, painn_kernel, p, tmF, tmFs);
}
```

```cpp
#include <cuda_runtime.h>
#include <cuda.h>
#include <cuda_bf16.h>
#include <stdint.h>

namespace {

constexpr int NT        = 512;
constexpr int NCWG      = 2;
constexpr int MAX_N     = 10240;
constexpr int MAX_CTA   = 136;
constexpr int MAX_NPC   = 80;
constexpr int MAX_ROUNDS = 38;
constexpr int REC_CAP   = MAX_ROUNDS * 128;
constexpr int SEG_CAP   = 64;
constexpr int SLOT_CAP  = 6144;
constexpr int MAX_STAGE = 6;
constexpr int STAGE_B   = 12288;

constexpr uint32_t D_MIN_BITS = 0x38D2;
constexpr uint32_t D_MAX_BITS = 0x409C;
constexpr int TAB_ROWS  = (int)(D_MAX_BITS - D_MIN_BITS) + 1;
constexpr int TAB_ZERO  = TAB_ROWS;
constexpr int TAB_BYTES = (TAB_ROWS + 1) * 32;

constexpr int SM_BINCNT = 0;
constexpr int SM_BINOFF = SM_BINCNT + MAX_CTA * 4;
constexpr int SM_NCNT   = SM_BINOFF + MAX_CTA * 4;
constexpr int SM_NINFO  = SM_NCNT + MAX_NPC * 4;
constexpr int SM_ORDER  = SM_NINFO + (MAX_NPC + 1) * 4;
constexpr int SM_CTRL   = SM_ORDER + MAX_NPC + 12;
constexpr int SM_BARS   = SM_CTRL + 64;
constexpr int SM_SID    = 2048 + 256;
constexpr int SM_META   = SM_SID + SLOT_CAP * 2;
constexpr int SM_TOTAL  = 232448;
constexpr int SM_HT     = (SM_TOTAL - 3 * 8192) / 1024 * 1024;
constexpr int SM_PV     = SM_HT + 2 * 8192;
constexpr int SM_RING4  = SM_HT - NCWG * 6 * STAGE_B;
constexpr int SM_RING3  = SM_HT - NCWG * 5 * STAGE_B;
constexpr int SLOT_CAP4 = (SM_RING4 - SM_META) / 8;
constexpr int P1_POS    = 3072;
constexpr int P1_SEGA   = P1_POS + 61440;
constexpr int P1_SEGB   = P1_SEGA + MAX_CTA * SEG_CAP * 8;
constexpr int P1_SV     = P1_SEGB + MAX_CTA * SEG_CAP * 4;
constexpr int P1_W1     = P1_SV + 4 * MAX_NPC * 128;
constexpr int P1_W2     = P1_W1 + 8192;
constexpr int P1_END    = P1_W2 + 8192;
constexpr int P1_REC    = P1_SEGA;
constexpr int STAGE_CAP = (P1_SV - P1_REC) / 16;
static_assert(SM_BARS + (8 + 2 * NCWG * MAX_STAGE) * 8 <= SM_SID, "misc block");
static_assert(SM_BARS + 256 <= P1_POS, "misc block");
static_assert(P1_END <= SM_TOTAL && P1_SV % 1024 == 0 && P1_REC % 16 == 0, "phase 1 overlay");
static_assert(SM_META + SLOT_CAP * 8 <= SM_RING3, "CSR");
static_assert(SM_RING4 % 1024 == 0 && SM_RING3 % 1024 == 0 && SM_HT % 1024 == 0, "alignment");
static_assert(SM_BARS % 8 == 0 && SM_META % 8 == 0 && SM_CTRL % 4 == 0, "alignment");
static_assert(MAX_N * 6 <= 61440, "pos");
static_assert(SM_SID + MAX_NPC * 1024 <= SM_TOTAL, "slow path accumulators");

__device__ __align__(1024) uint4 g_F[MAX_N * 32];
__device__ __align__(128) uint32_t g_seg[MAX_CTA * MAX_CTA * SEG_CAP * 3];
__device__ uint4    g_table[(TAB_BYTES + 15) / 16];
__device__ unsigned g_bar[2];
#define STAMP(k)
#define STAMPT(k, T)
#define ITS(k)

struct Params {
    const __nv_bfloat16* sv;
    const __nv_bfloat16* pos;
    const int*           src;
    const int*           dst;
    const __nv_bfloat16* freqs;
    const __nv_bfloat16* w1;
    const __nv_bfloat16* w2;
    const __nv_bfloat16* wr;
    __nv_bfloat16*       out;
    int N, E, ncta, npc;
    uint32_t npc_magic;
    int quads_per_cta;
};

__device__ __forceinline__ uint32_t smem_u32(const void* p) { return (uint32_t)__cvta_generic_to_shared(p); }
__device__ __forceinline__ float bf_lo(uint32_t v) { return __uint_as_float(v << 16); }
__device__ __forceinline__ float bf_hi(uint32_t v) { return __uint_as_float(v & 0xffff0000u); }
__device__ __forceinline__ float bf_u16(uint16_t v) { return __uint_as_float((uint32_t)v << 16); }
__device__ __forceinline__ uint32_t pack_bf(float lo, float hi) {
    uint32_t r;
    asm("cvt.rn.bf16x2.f32 %0, %1, %2;" : "=r"(r) : "f"(hi), "f"(lo));
    return r;
}
__device__ __forceinline__ float rbf(float x) { return bf_lo(pack_bf(x, 0.f)); }
__device__ __forceinline__ uint32_t hmul2(uint32_t a, uint32_t b) {
    uint32_t r;
    asm("mul.rn.bf16x2 %0, %1, %2;" : "=r"(r) : "r"(a), "r"(b));
    return r;
}
__device__ __forceinline__ uint32_t hsub2(uint32_t a, uint32_t b) {
    uint32_t r;
    asm("sub.rn.bf16x2 %0, %1, %2;" : "=r"(r) : "r"(a), "r"(b));
    return r;
}
__device__ __forceinline__ uint32_t lds32(uint32_t a) { uint32_t v; asm volatile("ld.shared.u32 %0, [%1];" : "=r"(v) : "r"(a)); return v; }
__device__ __forceinline__ uint32_t lds16(uint32_t a) { uint16_t v; asm volatile("ld.shared.u16 %0, [%1];" : "=h"(v) : "r"(a)); return v; }
__device__ __forceinline__ uint2 lds64(uint32_t a) { uint2 v; asm volatile("ld.shared.v2.u32 {%0,%1}, [%2];" : "=r"(v.x), "=r"(v.y) : "r"(a)); return v; }
__device__ __forceinline__ uint4 lds128(uint32_t a) { uint4 v; asm volatile("ld.shared.v4.u32 {%0,%1,%2,%3}, [%4];" : "=r"(v.x), "=r"(v.y), "=r"(v.z), "=r"(v.w) : "r"(a)); return v; }
__device__ __forceinline__ void sts32(uint32_t a, uint32_t v) { asm volatile("st.shared.u32 [%0], %1;" ::"r"(a), "r"(v) : "memory"); }
__device__ __forceinline__ void sts128(uint32_t a, uint4 v) { asm volatile("st.shared.v4.u32 [%0], {%1,%2,%3,%4};" ::"r"(a), "r"(v.x), "r"(v.y), "r"(v.z), "r"(v.w) : "memory"); }
__device__ __forceinline__ void mbar_init(uint32_t bar, int cnt) { asm volatile("mbarrier.init.shared::cta.b64 [%0], %1;" ::"r"(bar), "r"(cnt) : "memory"); }
__device__ __forceinline__ void mbar_expect_tx(uint32_t bar, uint32_t bytes) { asm volatile("mbarrier.arrive.expect_tx.shared::cta.b64 _, [%0], %1;" ::"r"(bar), "r"(bytes) : "memory"); }
__device__ __forceinline__ void mbar_arrive(uint32_t bar) { asm volatile("mbarrier.arrive.shared::cta.b64 _, [%0];" ::"r"(bar) : "memory"); }
__device__ __forceinline__ void mbar_wait(uint32_t bar, uint32_t parity) {
    asm volatile("{\n.reg .pred p;\n.reg .u32 c;\n"
                 "mbarrier.try_wait.parity.shared::cta.b64 p, [%0], %1;\n"
                 "@p bra DONE_%=;\n"
                 "mov.u32 c, 0;\n"
                 "LOOP_%=:\n"
                 "mbarrier.try_wait.parity.shared::cta.b64 p, [%0], %1;\n"
                 "@p bra DONE_%=;\n"
                 "add.u32 c, c, 1;\n"
                 "setp.lt.u32 p, c, 4194304;\n"
                 "@p bra LOOP_%=;\n"
                 "DONE_%=:\n}"
                 ::"r"(bar), "r"(parity) : "memory");
}
__device__ __forceinline__ void mbar_arrive_elected(uint32_t bar) {
    asm volatile("{\n.reg .pred p;\nelect.sync _|p, 0xffffffff;\n@p mbarrier.arrive.shared::cta.b64 _, [%0];\n}" ::"r"(bar) : "memory");
}
__device__ __forceinline__ void bulk_g2s(uint32_t dst, const void* src, uint32_t bytes, uint32_t bar) {
    asm volatile("cp.async.bulk.shared::cluster.global.mbarrier::complete_tx::bytes [%0], [%1], %2, [%3];"
                 ::"r"(dst), "l"(src), "r"(bytes), "r"(bar) : "memory");
}
__device__ __forceinline__ void cp_async16(uint32_t dst, const void* src) {
    asm volatile("cp.async.cg.shared.global [%0], [%1], 16;" ::"r"(dst), "l"(src) : "memory");
}
__device__ __forceinline__ void tma_load(uint32_t dst, const CUtensorMap* tm, int line, uint32_t bar) {
    asm volatile("cp.async.bulk.tensor.2d.shared::cluster.global.mbarrier::complete_tx::bytes [%0], [%1, {%3, %4}], [%2];"
                 ::"r"(dst), "l"(tm), "r"(bar), "r"(0), "r"(line) : "memory");
}
__device__ __forceinline__ void tma_load3(uint32_t dst, const CUtensorMap* tm, int comp, int node, uint32_t bar) {
    asm volatile("cp.async.bulk.tensor.3d.shared::cluster.global.mbarrier::complete_tx::bytes [%0], [%1, {%3, %4, %5}], [%2];"
                 ::"r"(dst), "l"(tm), "r"(bar), "r"(0), "r"(comp), "r"(node) : "memory");
}
__device__ __forceinline__ void tma_store3(const CUtensorMap* tm, int comp, int node, uint32_t src) {
    asm volatile("cp.async.bulk.tensor.3d.global.shared::cta.bulk_group [%0, {%2, %3, %4}], [%1];"
                 ::"l"(tm), "r"(src), "r"(0), "r"(comp), "r"(node) : "memory");
}
__device__ __forceinline__ void fence_async_smem() { asm volatile("fence.proxy.async.shared::cta;" ::: "memory"); }
__device__ __forceinline__ void named_barrier(int id) { asm volatile("bar.sync %0, 128;" ::"r"(id) : "memory"); }
__device__ __forceinline__ void ldsm4(uint32_t (&r)[4], uint32_t a) {
    asm volatile("ldmatrix.sync.aligned.m8n8.x4.shared.b16 {%0,%1,%2,%3}, [%4];" : "=r"(r[0]), "=r"(r[1]), "=r"(r[2]), "=r"(r[3]) : "r"(a) : "memory");
}
__device__ __forceinline__ void ldsm4t(uint32_t (&r)[4], uint32_t a) {
    asm volatile("ldmatrix.sync.aligned.m8n8.x4.trans.shared.b16 {%0,%1,%2,%3}, [%4];" : "=r"(r[0]), "=r"(r[1]), "=r"(r[2]), "=r"(r[3]) : "r"(a) : "memory");
}
__device__ __forceinline__ void stsm4(uint32_t a, uint32_t r0, uint32_t r1, uint32_t r2, uint32_t r3) {
    asm volatile("stmatrix.sync.aligned.m8n8.x4.shared.b16 [%0], {%1,%2,%3,%4};" ::"r"(a), "r"(r0), "r"(r1), "r"(r2), "r"(r3) : "memory");
}
__device__ __forceinline__ void mma16816(float (&c)[4], const uint32_t (&a)[4], uint32_t b0, uint32_t b1) {
    asm volatile("mma.sync.aligned.m16n8k16.row.col.f32.bf16.bf16.f32 {%0,%1,%2,%3}, {%4,%5,%6,%7}, {%8,%9}, {%0,%1,%2,%3};"
                 : "+f"(c[0]), "+f"(c[1]), "+f"(c[2]), "+f"(c[3])
                 : "r"(a[0]), "r"(a[1]), "r"(a[2]), "r"(a[3]), "r"(b0), "r"(b1));
}

__device__ __forceinline__ uint32_t desc_lo(uint32_t saddr) { return ((saddr & 0x3FFFF) >> 4) | (1u << 16); }
#define DESC_HI "0x40000040"
__device__ __forceinline__ void wg_fence() { asm volatile("wgmma.fence.sync.aligned;" ::: "memory"); }
__device__ __forceinline__ void wg_commit() { asm volatile("wgmma.commit_group.sync.aligned;" ::: "memory"); }
__device__ __forceinline__ void wg_wait0() { asm volatile("wgmma.wait_group.sync.aligned 0;" ::: "memory"); }
__device__ __forceinline__ void wg_wait1() { asm volatile("wgmma.wait_group.sync.aligned 1;" ::: "memory"); }

__device__ __forceinline__ void wgmma_n64_first(float (&d)[8], float (&e)[24], const uint32_t (&a)[4], uint32_t bdesc) {
    asm volatile("{\n.reg .b64 b;\nmov.b64 b, {%36, " DESC_HI "};\n"
                 "wgmma.mma_async.sync.aligned.m64n64k16.f32.bf16.bf16 {%0,%1,%2,%3,%4,%5,%6,%7,%8,%9,%10,%11,%12,%13,%14,%15,%16,%17,%18,%19,%20,%21,%22,%23,%24,%25,%26,%27,%28,%29,%30,%31}, {%32,%33,%34,%35}, b, 0, 1, 1, 1;\n}"
                 : "=f"(d[0]), "=f"(d[1]), "=f"(d[2]), "=f"(d[3]), "=f"(d[4]), "=f"(d[5]), "=f"(d[6]), "=f"(d[7]),
                   "=f"(e[0]), "=f"(e[1]), "=f"(e[2]), "=f"(e[3]), "=f"(e[4]), "=f"(e[5]), "=f"(e[6]), "=f"(e[7]), "=f"(e[8]), "=f"(e[9]), "=f"(e[10]), "=f"(e[11]), "=f"(e[12]), "=f"(e[13]), "=f"(e[14]), "=f"(e[15]), "=f"(e[16]), "=f"(e[17]), "=f"(e[18]), "=f"(e[19]), "=f"(e[20]), "=f"(e[21]), "=f"(e[22]), "=f"(e[23])
                 : "r"(a[0]), "r"(a[1]), "r"(a[2]), "r"(a[3]), "r"(bdesc));
}
__device__ __forceinline__ void wgmma_n64(float (&d)[8], float (&e)[24], const uint32_t (&a)[4], uint32_t bdesc) {
    asm volatile("{\n.reg .b64 b;\nmov.b64 b, {%36, " DESC_HI "};\n"
                 "wgmma.mma_async.sync.aligned.m64n64k16.f32.bf16.bf16 {%0,%1,%2,%3,%4,%5,%6,%7,%8,%9,%10,%11,%12,%13,%14,%15,%16,%17,%18,%19,%20,%21,%22,%23,%24,%25,%26,%27,%28,%29,%30,%31}, {%32,%33,%34,%35}, b, 1, 1, 1, 1;\n}"
                 : "+f"(d[0]), "+f"(d[1]), "+f"(d[2]), "+f"(d[3]), "+f"(d[4]), "+f"(d[5]), "+f"(d[6]), "+f"(d[7]),
                   "+f"(e[0]), "+f"(e[1]), "+f"(e[2]), "+f"(e[3]), "+f"(e[4]), "+f"(e[5]), "+f"(e[6]), "+f"(e[7]), "+f"(e[8]), "+f"(e[9]), "+f"(e[10]), "+f"(e[11]), "+f"(e[12]), "+f"(e[13]), "+f"(e[14]), "+f"(e[15]), "+f"(e[16]), "+f"(e[17]), "+f"(e[18]), "+f"(e[19]), "+f"(e[20]), "+f"(e[21]), "+f"(e[22]), "+f"(e[23])
                 : "r"(a[0]), "r"(a[1]), "r"(a[2]), "r"(a[3]), "r"(bdesc));
}
__device__ __forceinline__ void wgmma_n48_first(float (&e)[24], const uint32_t (&a)[4], uint32_t bdesc) {
    asm volatile("{\n.reg .b64 b;\nmov.b64 b, {%28, " DESC_HI "};\n"
                 "wgmma.mma_async.sync.aligned.m64n48k16.f32.bf16.bf16 {%0,%1,%2,%3,%4,%5,%6,%7,%8,%9,%10,%11,%12,%13,%14,%15,%16,%17,%18,%19,%20,%21,%22,%23}, {%24,%25,%26,%27}, b, 0, 1, 1, 1;\n}"
                 : "=f"(e[0]), "=f"(e[1]), "=f"(e[2]), "=f"(e[3]), "=f"(e[4]), "=f"(e[5]), "=f"(e[6]), "=f"(e[7]), "=f"(e[8]), "=f"(e[9]), "=f"(e[10]), "=f"(e[11]), "=f"(e[12]), "=f"(e[13]), "=f"(e[14]), "=f"(e[15]), "=f"(e[16]), "=f"(e[17]), "=f"(e[18]), "=f"(e[19]), "=f"(e[20]), "=f"(e[21]), "=f"(e[22]), "=f"(e[23])
                 : "r"(a[0]), "r"(a[1]), "r"(a[2]), "r"(a[3]), "r"(bdesc));
}
__device__ __forceinline__ void wgmma_n48(float (&e)[24], const uint32_t (&a)[4], uint32_t bdesc) {
    asm volatile("{\n.reg .b64 b;\nmov.b64 b, {%28, " DESC_HI "};\n"
                 "wgmma.mma_async.sync.aligned.m64n48k16.f32.bf16.bf16 {%0,%1,%2,%3,%4,%5,%6,%7,%8,%9,%10,%11,%12,%13,%14,%15,%16,%17,%18,%19,%20,%21,%22,%23}, {%24,%25,%26,%27}, b, 1, 1, 1, 1;\n}"
                 : "+f"(e[0]), "+f"(e[1]), "+f"(e[2]), "+f"(e[3]), "+f"(e[4]), "+f"(e[5]), "+f"(e[6]), "+f"(e[7]), "+f"(e[8]), "+f"(e[9]), "+f"(e[10]), "+f"(e[11]), "+f"(e[12]), "+f"(e[13]), "+f"(e[14]), "+f"(e[15]), "+f"(e[16]), "+f"(e[17]), "+f"(e[18]), "+f"(e[19]), "+f"(e[20]), "+f"(e[21]), "+f"(e[22]), "+f"(e[23])
                 : "r"(a[0]), "r"(a[1]), "r"(a[2]), "r"(a[3]), "r"(bdesc));
}
__device__ __forceinline__ void wgmma_n16_first(float (&d)[8], const uint32_t (&a)[4], uint32_t bdesc) {
    asm volatile("{\n.reg .b64 b;\nmov.b64 b, {%12, " DESC_HI "};\n"
                 "wgmma.mma_async.sync.aligned.m64n16k16.f32.bf16.bf16 {%0,%1,%2,%3,%4,%5,%6,%7}, {%8,%9,%10,%11}, b, 0, 1, 1, 1;\n}"
                 : "=f"(d[0]), "=f"(d[1]), "=f"(d[2]), "=f"(d[3]), "=f"(d[4]), "=f"(d[5]), "=f"(d[6]), "=f"(d[7])
                 : "r"(a[0]), "r"(a[1]), "r"(a[2]), "r"(a[3]), "r"(bdesc));
}
__device__ __forceinline__ void wgmma_n16(float (&d)[8], const uint32_t (&a)[4], uint32_t bdesc) {
    asm volatile("{\n.reg .b64 b;\nmov.b64 b, {%12, " DESC_HI "};\n"
                 "wgmma.mma_async.sync.aligned.m64n16k16.f32.bf16.bf16 {%0,%1,%2,%3,%4,%5,%6,%7}, {%8,%9,%10,%11}, b, 1, 1, 1, 1;\n}"
                 : "+f"(d[0]), "+f"(d[1]), "+f"(d[2]), "+f"(d[3]), "+f"(d[4]), "+f"(d[5]), "+f"(d[6]), "+f"(d[7])
                 : "r"(a[0]), "r"(a[1]), "r"(a[2]), "r"(a[3]), "r"(bdesc));
}

__device__ __forceinline__ void wgmma_n64_p(float (&d)[8], float (&e)[24], const uint32_t (&a)[4], uint32_t bdesc, int acc) {
    asm volatile("{\n.reg .pred p;\n.reg .b64 b;\nsetp.ne.b32 p, %37, 0;\nmov.b64 b, {%36, " DESC_HI "};\n"
                 "wgmma.mma_async.sync.aligned.m64n64k16.f32.bf16.bf16 {%0,%1,%2,%3,%4,%5,%6,%7,%8,%9,%10,%11,%12,%13,%14,%15,%16,%17,%18,%19,%20,%21,%22,%23,%24,%25,%26,%27,%28,%29,%30,%31}, {%32,%33,%34,%35}, b, p, 1, 1, 1;\n}"
                 : "+f"(d[0]), "+f"(d[1]), "+f"(d[2]), "+f"(d[3]), "+f"(d[4]), "+f"(d[5]), "+f"(d[6]), "+f"(d[7]),
                   "+f"(e[0]), "+f"(e[1]), "+f"(e[2]), "+f"(e[3]), "+f"(e[4]), "+f"(e[5]), "+f"(e[6]), "+f"(e[7]), "+f"(e[8]), "+f"(e[9]), "+f"(e[10]), "+f"(e[11]), "+f"(e[12]), "+f"(e[13]), "+f"(e[14]), "+f"(e[15]), "+f"(e[16]), "+f"(e[17]), "+f"(e[18]), "+f"(e[19]), "+f"(e[20]), "+f"(e[21]), "+f"(e[22]), "+f"(e[23])
                 : "r"(a[0]), "r"(a[1]), "r"(a[2]), "r"(a[3]), "r"(bdesc), "r"(acc));
}
__device__ __forceinline__ void wgmma_n16_p(float (&d)[8], const uint32_t (&a)[4], uint32_t bdesc, int acc) {
    asm volatile("{\n.reg .pred p;\n.reg .b64 b;\nsetp.ne.b32 p, %13, 0;\nmov.b64 b, {%12, " DESC_HI "};\n"
                 "wgmma.mma_async.sync.aligned.m64n16k16.f32.bf16.bf16 {%0,%1,%2,%3,%4,%5,%6,%7}, {%8,%9,%10,%11}, b, p, 1, 1, 1;\n}"
                 : "+f"(d[0]), "+f"(d[1]), "+f"(d[2]), "+f"(d[3]), "+f"(d[4]), "+f"(d[5]), "+f"(d[6]), "+f"(d[7])
                 : "r"(a[0]), "r"(a[1]), "r"(a[2]), "r"(a[3]), "r"(bdesc), "r"(acc));
}

__device__ __forceinline__ uint32_t edge_dist(uint32_t sxy, uint32_t sz, uint32_t dxy, uint32_t dz, uint32_t& rxy, uint32_t& rz) {
    rxy = hsub2(sxy, dxy);
    rz  = hsub2(sz, dz);
    uint32_t qxy = hmul2(rxy, rxy), qz = hmul2(rz, rz);
    float ss = rbf((bf_lo(qxy) + bf_hi(qxy)) + bf_lo(qz));
    float s2 = rbf(ss + 1e-8f);
    float d;
    asm("sqrt.approx.ftz.f32 %0, %1;" : "=f"(d) : "f"(s2));
    return pack_bf(d, 0.f) & 0xffffu;
}

__device__ __forceinline__ void load_pos(uint32_t sm_pos, int i, uint32_t& xy, uint32_t& z) {
    uint32_t a  = (sm_pos + 6u * (uint32_t)i) & ~3u;
    uint32_t w0 = lds32(a), w1 = lds32(a + 4);
    uint32_t sh = (uint32_t)i << 4;
    xy = __funnelshift_r(w0, w1, sh);
    z  = __funnelshift_r(w1, w1, sh);
}

__device__ __noinline__ float radial_value(float d, float f) {
    float arg = rbf(d * f);
    float sn  = rbf(sinf(arg));
    float rb  = rbf(__fdiv_rn(sn, d));
    float c   = rbf(cosf(rbf(__fdiv_rn(rbf(d * 3.14159265358979323846f), 5.0f))));
    float fc  = rbf(0.5f * rbf(c + 1.0f));
    return rb * fc;
}

__global__ void __launch_bounds__(NT, 1)
painn_kernel(const Params p, const __grid_constant__ CUtensorMap tmF, const __grid_constant__ CUtensorMap tmFs) {
    extern __shared__ __align__(1024) uint8_t smem[];
    const uint32_t sb   = smem_u32(smem);
    const int tid  = threadIdx.x, lane = tid & 31, warp = __shfl_sync(0xffffffffu, tid >> 5, 0);
    const int cta  = blockIdx.x;
    const int g    = lane >> 2, t = lane & 3;
    int* binCnt = (int*)(smem + SM_BINCNT);
    int* binOff = (int*)(smem + SM_BINOFF);
    int* nCnt   = (int*)(smem + SM_NCNT);
    uint32_t* nInfo = (uint32_t*)(smem + SM_NINFO);
    volatile int* ctrl = (volatile int*)(smem + SM_CTRL);
    const uint32_t bar_pos = sb + SM_BARS, bar_mlp = bar_pos + 8, bar_rec = bar_pos + 16;
    const uint32_t bar_full = bar_pos + 32, bar_empty = bar_full + NCWG * MAX_STAGE * 8;
    const uint32_t bar_hfull = bar_empty + NCWG * MAX_STAGE * 8, bar_hempty = bar_hfull + 16;

    const int node0  = cta * p.npc;
    const int nnodes = max(0, min(p.npc, p.N - node0));

    STAMP(0);
    if (tid == 32) {
        mbar_init(bar_pos, 1);
        asm volatile("fence.mbarrier_init.release.cluster;" ::: "memory");
        uint32_t pos_bytes = (uint32_t)(p.N * 6 + 15) & ~15u;
        mbar_expect_tx(bar_pos, pos_bytes);
        bulk_g2s(sb + P1_POS, p.pos, pos_bytes, bar_pos);
    } else if (tid == 64) {
        mbar_init(bar_rec, 1);
        mbar_init(bar_hfull, 4); mbar_init(bar_hfull + 8, 4); mbar_init(bar_hempty, 4); mbar_init(bar_hempty + 8, 4);
        asm volatile("prefetch.tensormap [%0];" ::"l"(&tmF) : "memory");
        asm volatile("prefetch.tensormap [%0];" ::"l"(&tmFs) : "memory");
    } else if (tid >= 96 && tid < 96 + NCWG * MAX_STAGE) {
        mbar_init(bar_full + 8 * (tid - 96), 2);
        mbar_init(bar_empty + 8 * (tid - 96), 4);
    }
    unsigned bar_seen = 0;
    if (tid == 0 || tid == 32) asm volatile("ld.relaxed.gpu.global.u32 %0, [%1];" : "=r"(bar_seen) : "l"(&g_bar[tid >> 5]) : "memory");
    const bool mlp_warp = warp >= 6;
    int4 s4[3], d4[3];
    const int q0 = cta * p.quads_per_cta;
    const int qend = min(q0 + p.quads_per_cta, p.E >> 2);
#pragma unroll
    for (int k = 0; k < 3; k++) {
        const int q = q0 + (k < 2 ? warp + 16 * k : 32 + warp) * 32 + lane;
        const bool ok = q < qend && (k < 2 || !mlp_warp);
        s4[k] = ok ? __ldg((const int4*)p.src + q) : make_int4(-1, -1, -1, -1);
        d4[k] = ok ? __ldg((const int4*)p.dst + q) : make_int4(0, 0, 0, 0);
    }
    for (int i = tid; i < nnodes * 32; i += NT) {
        const int r = i >> 5, b = (i >> 3) & 3, c = i & 7;
        cp_async16(sb + P1_SV + b * (MAX_NPC * 128) + r * 128 + ((c ^ (r & 7)) << 4), (const uint8_t*)p.sv + (size_t)node0 * 512 + i * 16);
    }
    for (int i = tid; i < 1024; i += NT) {
        const int m = i >> 9, k = (i >> 3) & 63, c = i & 7;
        cp_async16(sb + P1_W1 + m * 8192 + k * 128 + ((c ^ (k & 7)) << 4),
                   m == 0 ? (const uint8_t*)p.w1 + k * 128 + c * 16 : (const uint8_t*)p.w2 + k * 384 + 128 + c * 16);
    }
    asm volatile("cp.async.commit_group;" ::: "memory");
    if (tid < MAX_CTA) binCnt[tid] = 0;
    if (tid < MAX_NPC) nCnt[tid] = 0;
    if (tid < 16) ctrl[tid] = 0;
    if (tid >= 256 && tid < 256 + 240) {
        const int i = tid - 256;
        asm volatile("prefetch.global.L2 [%0];" ::"l"(i < 48 ? (const uint8_t*)p.wr + i * 128 : (const uint8_t*)p.w2 + (i - 48) * 128));
    }
    for (int i = P1_SEGA / 16 + tid; i < P1_SV / 16; i += NT) sts128(sb + i * 16, make_uint4(0u, 0u, 0u, 0u));
    for (int i = tid; i < 4 * (MAX_NPC - nnodes) * 8; i += NT)
        sts128(sb + P1_SV + (i / ((MAX_NPC - nnodes) * 8)) * (MAX_NPC * 128) + nnodes * 128 + (i % ((MAX_NPC - nnodes) * 8)) * 16, make_uint4(0u, 0u, 0u, 0u));
    __syncthreads();

    if (!mlp_warp) {
        const int rows_per = (TAB_ROWS + 1 + p.ncta - 1) / p.ncta;
        for (int i = tid; i < rows_per * 8; i += 6 * 32) {
            int row = cta * rows_per + (i >> 3), kp = i & 7;
            if (row <= TAB_ROWS) {
                uint32_t val = 0;
                if (row < TAB_ROWS) {
                    float d = __uint_as_float((D_MIN_BITS + row) << 16);
                    uint32_t f2 = __ldg((const uint32_t*)p.freqs + kp);
                    val = pack_bf(radial_value(d, bf_lo(f2)), radial_value(d, bf_hi(f2)));
                }
                ((uint32_t*)g_table)[row * 8 + kp] = val;
            }
        }
    }
    mbar_wait(bar_pos, 0);
    STAMP(1);
#pragma unroll
    for (int k = 0; k < 3; k++) {
        const int ss[4] = {s4[k].x, s4[k].y, s4[k].z, s4[k].w};
        const int dd[4] = {d4[k].x, d4[k].y, d4[k].z, d4[k].w};
        if (ss[0] >= 0) {
            uint32_t w0[4], w1[4], v0[4], v1[4], r0[4], r1[4], r2[4], bin[4], rank[4];
#pragma unroll
            for (int j = 0; j < 4; j++) {
                const uint32_t a = (sb + P1_POS + 6u * (uint32_t)ss[j]) & ~3u, c = (sb + P1_POS + 6u * (uint32_t)dd[j]) & ~3u;
                w0[j] = lds32(a); w1[j] = lds32(a + 4); v0[j] = lds32(c); v1[j] = lds32(c + 4);
            }
#pragma unroll
            for (int j = 0; j < 4; j++) {
                const uint32_t sh = (uint32_t)ss[j] << 4, dh = (uint32_t)dd[j] << 4;
                uint32_t rxy, rz;
                const uint32_t db = edge_dist(__funnelshift_r(w0[j], w1[j], sh), __funnelshift_r(w1[j], w1[j], sh),
                                              __funnelshift_r(v0[j], v1[j], dh), __funnelshift_r(v1[j], v1[j], dh), rxy, rz);
                float inv;
                asm("rcp.approx.ftz.f32 %0, %1;" : "=f"(inv) : "f"(__uint_as_float(db << 16)));
                bin[j] = __umulhi((uint32_t)dd[j], p.npc_magic);
                r0[j] = (uint32_t)ss[j] | ((db - D_MIN_BITS) << 16);
                r1[j] = pack_bf(bf_lo(rxy) * inv, bf_hi(rxy) * inv);
                r2[j] = __byte_perm(pack_bf(bf_lo(rz) * inv, 0.f), (uint32_t)dd[j] - bin[j] * (uint32_t)p.npc, 0x5410);
                rank[j] = db <= D_MAX_BITS ? (uint32_t)atomicAdd(&binCnt[bin[j]], 1) : 0xffffu;
            }
#pragma unroll
            for (int j = 0; j < 4; j++) {
                if (rank[j] < SEG_CAP) {
                    const uint32_t slot = bin[j] * SEG_CAP + rank[j];
                    asm volatile("st.shared.v2.u32 [%0], {%1, %2};" ::"r"(sb + P1_SEGA + slot * 8), "r"(r0[j]), "r"(r1[j]) : "memory");
                    sts32(sb + P1_SEGB + slot * 4, r2[j]);
                }
            }
        }
    }
    asm volatile("cp.async.wait_group 0;" ::: "memory");
    __syncthreads();
    STAMP(2);
    for (int b = 2 * warp + (lane >> 4); b < p.ncta; b += 32) {
        const int cnt = binCnt[b], nw = max(32, (min(cnt, SEG_CAP) + 7) & ~7);
        uint32_t* dstp = g_seg + ((size_t)cta * MAX_CTA + b) * (SEG_CAP * 3);
        const uint32_t tag = (uint32_t)min(cnt, 511) << 23;
        for (int j = lane & 15; j < nw; j += 16) {
            const uint2 a = lds64(sb + P1_SEGA + (b * SEG_CAP + j) * 8);
            const uint32_t c = lds32(sb + P1_SEGB + (b * SEG_CAP + j) * 4);
            *(uint2*)(dstp + 2 * j) = a;
            dstp[2 * SEG_CAP + j] = c | tag;
        }
    }
    __syncthreads();
    STAMP(3);
    if (tid == 64) asm volatile("red.add.release.gpu.global.u32 [%0], 1;" ::"l"(&g_bar[0]) : "memory");

    if (mlp_warp) {
        const int mt = (warp - 6) >> 1, hf = (warp - 6) & 1;
        if (mt * 16 < nnodes) {
            STAMPT(10, 6 * 32);
            const int lrow = lane & 15, lch = lane >> 4;
            const uint32_t rowb = sb + P1_SV + (mt * 16 + lrow) * 128;
            const uint32_t key0 = lrow & 7;
            float acc[4][4];
#pragma unroll
            for (int i = 0; i < 4; i++) { acc[i][0] = acc[i][1] = acc[i][2] = acc[i][3] = 0.f; }
#pragma unroll
            for (int ks = 0; ks < 4; ks++) {
                uint32_t a[4];
                ldsm4(a, rowb + (((2 * ks + lch) ^ key0) << 4));
                const int kk = 16 * ks + lrow;
#pragma unroll
                for (int nt = 0; nt < 4; nt += 2) {
                    uint32_t b[4];
                    ldsm4t(b, sb + P1_W1 + kk * 128 + (((4 * hf + nt + lch) ^ (kk & 7)) << 4));
                    mma16816(acc[nt], a, b[0], b[1]);
                    mma16816(acc[nt + 1], a, b[2], b[3]);
                }
            }
            uint32_t hp[4][2];
#pragma unroll
            for (int i = 0; i < 4; i++) {
                float h[4];
#pragma unroll
                for (int q = 0; q < 4; q++) {
                    float x = rbf(acc[i][q]);
                    h[q] = __fdividef(x, 1.0f + __expf(-x));
                    acc[i][q] = 0.f;
                }
                hp[i][0] = pack_bf(h[0], h[1]);
                hp[i][1] = pack_bf(h[2], h[3]);
            }
            asm volatile("bar.sync %0, 64;" ::"r"(4 + mt) : "memory");
#pragma unroll
            for (int i = 0; i < 4; i += 2)
                stsm4(rowb + (((4 * hf + i + lch) ^ key0) << 4), hp[i][0], hp[i][1], hp[i + 1][0], hp[i + 1][1]);
            asm volatile("bar.sync %0, 64;" ::"r"(4 + mt) : "memory");
#pragma unroll
            for (int ks = 0; ks < 4; ks++) {
                uint32_t a[4];
                ldsm4(a, rowb + (((2 * ks + lch) ^ key0) << 4));
                const int kk = 16 * ks + lrow;
#pragma unroll
                for (int nt = 0; nt < 4; nt += 2) {
                    uint32_t b[4];
                    ldsm4t(b, sb + P1_W2 + kk * 128 + (((4 * hf + nt + lch) ^ (kk & 7)) << 4));
                    mma16816(acc[nt], a, b[0], b[1]);
                    mma16816(acc[nt + 1], a, b[2], b[3]);
                }
            }
            uint32_t vq[2][3][4];
            const uint32_t vb = sb + P1_SV + (mt * 16 + g) * 128 + 4 * t;
#pragma unroll
            for (int rh = 0; rh < 2; rh++)
#pragma unroll
                for (int a = 0; a < 3; a++)
#pragma unroll
                    for (int i = 0; i < 4; i++) vq[rh][a][i] = lds32(vb + (a + 1) * (MAX_NPC * 128) + rh * 1024 + (((4 * hf + i) ^ g) << 4));
#pragma unroll
            for (int rh = 0; rh < 2; rh++)
#pragma unroll
                for (int a = 0; a < 3; a++)
#pragma unroll
                    for (int i = 0; i < 4; i++)
                        sts32(vb + (a + 1) * (MAX_NPC * 128) + rh * 1024 + (((4 * hf + i) ^ g) << 4),
                              hmul2(pack_bf(acc[i][2 * rh], acc[i][2 * rh + 1]), vq[rh][a][i]));
            fence_async_smem();
            asm volatile("bar.sync %0, 64;" ::"r"(4 + mt) : "memory");
            {
                const int r4 = mt * 16 + 8 * hf + 4 * (lane >> 2), comp = lane & 3;
                if (lane < 8 && r4 < nnodes) tma_store3(&tmFs, comp, node0 + r4, sb + P1_SV + comp * (MAX_NPC * 128) + r4 * 128);
            }
            asm volatile("cp.async.bulk.commit_group;" ::: "memory");
        }
        STAMPT(11, 6 * 32);
    }
    if (tid == 0) {
        const unsigned target = (bar_seen / (unsigned)p.ncta + 1u) * (unsigned)p.ncta;
        unsigned cur;
        int spins = 0;
        do {
            asm volatile("ld.acquire.gpu.global.u32 %0, [%1];" : "=r"(cur) : "l"(&g_bar[0]) : "memory");
        } while ((int)(cur - target) < 0 && ++spins < (1 << 24));
    }
    STAMP(4);
    __syncthreads();
    STAMP(5);

    constexpr int SEG_IT = (MAX_CTA + 31) / 32;
    uint2 ra[SEG_IT][2];
    uint32_t rb[SEG_IT][2], rr[SEG_IT][2];
#pragma unroll
    for (int it = 0; it < SEG_IT; it++) {
        const int b = 2 * warp + (lane >> 4) + 32 * it;
        const uint32_t* sp = g_seg + ((size_t)b * MAX_CTA + cta) * (SEG_CAP * 3);
#pragma unroll
        for (int u = 0; u < 2; u++) {
            const int j = (lane & 15) + 16 * u;
            ra[it][u] = b < p.ncta ? __ldcg((const uint2*)(sp + 2 * j)) : make_uint2(0u, 0u);
            rb[it][u] = b < p.ncta ? __ldcg(sp + 2 * SEG_CAP + j) : 0u;
        }
    }
#pragma unroll
    for (int it = 0; it < SEG_IT; it++) {
        const int cnt = rb[it][0] >> 23;
        if (cnt > SEG_CAP) ctrl[1] = 1;
#pragma unroll
        for (int u = 0; u < 2; u++)
            rr[it][u] = (lane & 15) + 16 * u < cnt ? (uint32_t)atomicAdd(&nCnt[(rb[it][u] >> 16) & 0x7fu], 1) : 0xffffffffu;
        if (cnt > 32) {
            const int b = 2 * warp + (lane >> 4) + 32 * it;
            const uint32_t* sp = g_seg + ((size_t)b * MAX_CTA + cta) * (SEG_CAP * 3);
            for (int j = 32 + (lane & 15); j < min(cnt, SEG_CAP); j += 16) {
                const uint2 a = __ldcg((const uint2*)(sp + 2 * j));
                const uint32_t c = __ldcg(sp + 2 * SEG_CAP + j);
                const int pos = atomicAdd((int*)&ctrl[8], 1);
                const uint32_t rank = (uint32_t)atomicAdd(&nCnt[(c >> 16) & 0x7fu], 1);
                if (pos < STAGE_CAP) sts128(sb + P1_REC + pos * 16, make_uint4(a.x, a.y, c, rank));
            }
        }
    }
    STAMP(13);
    if (mlp_warp && lane < 8) {
        asm volatile("cp.async.bulk.wait_group 0;" ::: "memory");
        asm volatile("fence.proxy.async;" ::: "memory");
    }
    __syncthreads();
    if (tid == 64) asm volatile("red.add.release.gpu.global.u32 [%0], 1;" ::"l"(&g_bar[1]) : "memory");
    const int total = ctrl[8];
    if (tid == 0 && total > STAGE_CAP) ctrl[1] = 1;
    if (warp == 0) {
        int c[3], s = 0;
#pragma unroll
        for (int i = 0; i < 3; i++) {
            int b = lane * 3 + i;
            c[i] = b < nnodes ? max(16, (nCnt[b] + 15) & ~15) : 0;
            s += c[i];
        }
        int x = s;
#pragma unroll
        for (int o = 1; o < 32; o <<= 1) { int y = __shfl_up_sync(0xffffffffu, x, o); if (lane >= o) x += y; }
        const int slots = __shfl_sync(0xffffffffu, x, 31);
        int off = x - s, below = 0;
#pragma unroll
        for (int i = 0; i < 3; i++) {
            int b = lane * 3 + i;
            if (b < nnodes) {
                nInfo[b] = (uint32_t)off | ((uint32_t)c[i] << 16);
                below += (2 * off + c[i] < slots);
            }
            off += c[i];
        }
        below = __reduce_add_sync(0xffffffffu, below);
        if (lane == 0) {
            ctrl[2] = below;
            ctrl[4] = slots;
            if (slots > SLOT_CAP) ctrl[1] = 1;
        }
    }
    __syncthreads();
    if (ctrl[1] == 0) {
        uint16_t* sid = (uint16_t*)(smem + SM_SID);
        uint2* meta = (uint2*)(smem + SM_META);
#pragma unroll
        for (int it = 0; it < SEG_IT; it++)
#pragma unroll
            for (int u = 0; u < 2; u++)
                if (rr[it][u] != 0xffffffffu) rr[it][u] += lds32(sb + SM_NINFO + ((rb[it][u] >> 16) & 0x7fu) * 4) & 0xffffu;
#pragma unroll
        for (int it = 0; it < SEG_IT; it++)
#pragma unroll
            for (int u = 0; u < 2; u++)
                if (rr[it][u] != 0xffffffffu) {
                    sid[rr[it][u]]  = (uint16_t)((ra[it][u].x & 0xffffu) << 2);
                    meta[rr[it][u]] = make_uint2(((ra[it][u].x >> 16) << 5) | (rb[it][u] << 16), ra[it][u].y);
                }
        for (int i = tid; i < total; i += NT) {
            const uint4 r = lds128(sb + P1_REC + i * 16);
            const int pos = (int)(lds32(sb + SM_NINFO + ((r.z >> 16) & 0x7fu) * 4) & 0xffffu) + (int)r.w;
            sid[pos]  = (uint16_t)((r.x & 0xffffu) << 2);
            meta[pos] = make_uint2(((r.x >> 16) << 5) | (r.z << 16), r.y);
        }
        if (tid >= NT - 128 && tid - (NT - 128) < nnodes) {
            const int b = tid - (NT - 128), split = ctrl[2];
            const int mid = split < nnodes ? (int)(nInfo[split] & 0xffffu) : ctrl[4];
            const int st = b >= split;
            const int mine = (int)(nInfo[b] & 0xffffu) + (int)(nInfo[b] >> 16) - (st ? mid : 0);
            int lo = st ? 0 : split, hi = st ? split : nnodes;
            const int first = lo;
            while (lo < hi) {
                const int o = (lo + hi) >> 1;
                const int other = (int)(nInfo[o] & 0xffffu) + (int)(nInfo[o] >> 16) - (st ? 0 : mid);
                if (st ? (other <= mine) : (other < mine)) lo = o + 1; else hi = o;
            }
            const int rank = (st ? b - split : b) + lo - first;
            smem[SM_ORDER + rank] = (uint8_t)(b | (st << 7));
        }
        for (int i = tid; i < nnodes * 16; i += NT) {
            int nl = i >> 4, c = nCnt[nl];
            int j = (c & ~15) + (i & 15);
            if (j >= c && (j < 16 || (c & 15))) {
                int pos = (int)(nInfo[nl] & 0xffffu) + j;
                sid[pos]  = 0xffffu;
                meta[pos] = make_uint2((uint32_t)TAB_ZERO << 5, 0u);
            }
        }
    }
    if (tid == 32) {
        const unsigned target = (bar_seen / (unsigned)p.ncta + 1u) * (unsigned)p.ncta;
        unsigned cur;
        int spins = 0;
        do {
            asm volatile("ld.acquire.gpu.global.u32 %0, [%1];" : "=r"(cur) : "l"(&g_bar[1]) : "memory");
        } while ((int)(cur - target) < 0 && ++spins < (1 << 24));
    }
    fence_async_smem();
    __syncthreads();
    STAMP(6);

    if (__shfl_sync(0xffffffffu, ctrl[1], 0) != 0) {
        float* acc = (float*)(smem + P1_POS);
        for (int i = tid; i < nnodes * 256; i += NT) acc[i] = 0.f;
        __syncthreads();
        const uint16_t* posu = (const uint16_t*)p.pos;
        const uint32_t* tabg = (const uint32_t*)g_table;
        const uint32_t* Fw = (const uint32_t*)g_F;
        for (int e0 = warp * 32; e0 < p.E; e0 += NT) {
            int e = e0 + lane;
            int s = 0, d = 0;
            uint32_t db = 0xffff, rxy = 0, rz = 0;
            bool act = false;
            if (e < p.E) {
                s = p.src[e]; d = p.dst[e];
                if (d >= node0 && d < node0 + nnodes) {
                    uint32_t sxy = posu[s * 3] | ((uint32_t)posu[s * 3 + 1] << 16), sz = posu[s * 3 + 2];
                    uint32_t dxy = posu[d * 3] | ((uint32_t)posu[d * 3 + 1] << 16), dz = posu[d * 3 + 2];
                    db  = edge_dist(sxy, sz, dxy, dz, rxy, rz);
                    act = db <= D_MAX_BITS;
                }
            }
            unsigned m = __ballot_sync(0xffffffffu, act);
            while (m) {
                int l = __ffs(m) - 1;
                m &= m - 1;
                int es = __shfl_sync(0xffffffffu, s, l), ed = __shfl_sync(0xffffffffu, d, l);
                uint32_t edb = __shfl_sync(0xffffffffu, db, l), exy = __shfl_sync(0xffffffffu, rxy, l), ez = __shfl_sync(0xffffffffu, rz, l);
                float inv = 1.0f / __uint_as_float(edb << 16);
                float rh[3] = {rbf(bf_lo(exy) * inv), rbf(bf_hi(exy) * inv), rbf(bf_lo(ez) * inv)};
                const uint32_t* fr = Fw + (size_t)es * 128 + lane;
                const uint32_t fh = __ldcg(fr);
                const uint32_t q[3] = {__ldcg(fr + 32), __ldcg(fr + 64), __ldcg(fr + 96)};
                float ps0 = 0.f, ps1 = 0.f, pr0 = 0.f, pr1 = 0.f;
                for (int j2 = 0; j2 < 32; j2++) {
                    uint32_t hj = __shfl_sync(0xffffffffu, fh, j2);
                    uint32_t a0 = *(const uint32_t*)(p.w2 + (2 * j2) * 192 + 2 * lane), a1 = *(const uint32_t*)(p.w2 + (2 * j2 + 1) * 192 + 2 * lane);
                    uint32_t b0 = *(const uint32_t*)(p.w2 + (2 * j2) * 192 + 128 + 2 * lane), b1 = *(const uint32_t*)(p.w2 + (2 * j2 + 1) * 192 + 128 + 2 * lane);
                    ps0 += bf_lo(hj) * bf_lo(a0) + bf_hi(hj) * bf_lo(a1);
                    ps1 += bf_lo(hj) * bf_hi(a0) + bf_hi(hj) * bf_hi(a1);
                    pr0 += bf_lo(hj) * bf_lo(b0) + bf_hi(hj) * bf_lo(b1);
                    pr1 += bf_lo(hj) * bf_hi(b0) + bf_hi(hj) * bf_hi(b1);
                }
                float ws0 = 0.f, ws1 = 0.f, wv0 = 0.f, wv1 = 0.f, wr0 = 0.f, wr1 = 0.f;
                for (int k2 = 0; k2 < 8; k2++) {
                    uint32_t rk2 = __ldcg(tabg + (edb - D_MIN_BITS) * 8 + k2);
#pragma unroll
                    for (int h = 0; h < 2; h++) {
                        float rv = h ? bf_hi(rk2) : bf_lo(rk2);
                        const __nv_bfloat16* wrow = p.wr + (2 * k2 + h) * 192 + 2 * lane;
                        uint32_t a = *(const uint32_t*)wrow, b = *(const uint32_t*)(wrow + 64), c = *(const uint32_t*)(wrow + 128);
                        ws0 += rv * bf_lo(a); ws1 += rv * bf_hi(a);
                        wv0 += rv * bf_lo(b); wv1 += rv * bf_hi(b);
                        wr0 += rv * bf_lo(c); wr1 += rv * bf_hi(c);
                    }
                }
                float* a = acc + (ed - node0) * 256 + 2 * lane;
                atomicAdd(a, ps0 * ws0); atomicAdd(a + 1, ps1 * ws1);
#pragma unroll
                for (int c = 0; c < 3; c++) {
                    atomicAdd(a + 64 * (c + 1), wv0 * bf_lo(q[c]) + pr0 * wr0 * rh[c]);
                    atomicAdd(a + 64 * (c + 1) + 1, wv1 * bf_hi(q[c]) + pr1 * wr1 * rh[c]);
                }
            }
        }
        __syncthreads();
        for (int i = tid; i < nnodes * 128; i += NT) {
            uint32_t r = *(const uint32_t*)(p.sv + (size_t)node0 * 256 + 2 * i);
            *(uint32_t*)(p.out + (size_t)node0 * 256 + 2 * i) = pack_bf(bf_lo(r) + acc[2 * i], bf_hi(r) + acc[2 * i + 1]);
        }
        return;
    }

    const int slots = __reduce_max_sync(0xffffffffu, ctrl[4]);
    const int split = __reduce_max_sync(0xffffffffu, ctrl[2]);
    const int nstage = slots <= SLOT_CAP4 ? 6 : 5;
    const uint32_t ring = sb + (nstage == 6 ? SM_RING4 : SM_RING3);
    const int mid = __reduce_max_sync(0xffffffffu, split < nnodes ? (int)(nInfo[split] & 0xffffu) : slots) >> 4;
    const int wgi = warp >> 2, w = warp & 3;
    uint32_t wp[3][4];
    if (wgi < 3) {
        const uint16_t* wr = (const uint16_t*)p.wr + 16 * w + g;
#pragma unroll
        for (int ty = 0; ty < 3; ty++) {
#pragma unroll
            for (int i = 0; i < 4; i++) {
                const uint16_t* q = wr + (8 * (i >> 1) + 2 * t) * 192 + ty * 64 + 8 * (i & 1);
                wp[ty][i] = (uint32_t)__ldg(q) | ((uint32_t)__ldg(q + 192) << 16);
            }
        }
    }
    constexpr uint32_t EMPTY_OFF = NCWG * MAX_STAGE * 8;
    if (wgi == 3) {
        const int sc = w >> 1, r = w & 1;
        const int g0 = (sc == 0 ? 0 : mid) + r, g1 = sc == 0 ? mid : slots >> 4;
        const uint32_t ring_wg = ring + sc * nstage * STAGE_B, full_wg = bar_full + sc * MAX_STAGE * 8;
        const int e = lane >> 1, half = lane & 1;
        const uint32_t coef_off = e * 128 + ((half ^ (e & 7)) << 4);
        const int vrot = (e & 3) ^ ((e >> 1) & 3);
        const uint8_t* tab = (const uint8_t*)g_table + half * 16;
        int stage = r;
        uint32_t phase = 1;
        uint32_t ma = sb + SM_META + (g0 * 16 + e) * 8, ida = sb + SM_SID + g0 * 32;
        uint2 m = make_uint2(0u, 0u);
        uint4 tv = make_uint4(0u, 0u, 0u, 0u), ia = tv, ib = tv;
        if (g0 < g1) {
            m  = lds64(ma);
            ia = lds128(ida);
            ib = lds128(ida + 16);
            tv = __ldg((const uint4*)(tab + (m.x & 0xffffu)));
        }
        for (int left = (g1 - g0 + 1) >> 1; left > 0; left--) {
            const uint32_t st = ring_wg + stage * STAGE_B, fb = full_wg + stage * 8;
            uint4 o[4];
            {
                const uint32_t mul[4] = {0x3f803f80u, __byte_perm(m.y, 0, 0x1010), __byte_perm(m.y, 0, 0x3232), __byte_perm(m.x, 0, 0x3232)};
#pragma unroll
                for (int j = 0; j < 4; j++) {
                    const int v = j ^ vrot;
                    const uint32_t lo = (v & 1) ? mul[1] : mul[0], hi = (v & 1) ? mul[3] : mul[2];
                    const uint32_t mm = (v & 2) ? hi : lo;
                    o[j] = make_uint4(hmul2(tv.x, mm), hmul2(tv.y, mm), hmul2(tv.z, mm), hmul2(tv.w, mm));
                }
            }
            ma += 256; ida += 64;
            if (left > 1) m = lds64(ma);
            mbar_wait(fb + EMPTY_OFF, phase);
            uint32_t leader;
            asm volatile("{\n.reg .pred p;\nelect.sync _|p, 0xffffffff;\nselp.u32 %0, 1, 0, p;\n}" : "=r"(leader));
            if (leader) {
                const uint32_t id2[8] = {ia.x, ia.y, ia.z, ia.w, ib.x, ib.y, ib.z, ib.w};
                const uint32_t rows = st + 2048;
                if ((ib.w >> 16) != 0xffffu) {
                    mbar_expect_tx(fb, 16 * 512);
#pragma unroll
                    for (int i = 0; i < 8; i++) {
                        tma_load(rows + (2 * i) * 640, &tmF, (int)(id2[i] & 0xffffu), fb);
                        tma_load(rows + (2 * i + 1) * 640, &tmF, (int)(id2[i] >> 16), fb);
                    }
                } else {
                    int nv = 0;
#pragma unroll
                    for (int i = 0; i < 8; i++) nv += ((id2[i] & 0xffffu) != 0xffffu) + ((id2[i] >> 16) != 0xffffu);
                    mbar_expect_tx(fb, (uint32_t)nv * 512u);
#pragma unroll
                    for (int q = 0; q < 4; q++) {
                        if (4 * q + 4 <= nv) {
                            tma_load(rows + (4 * q) * 640, &tmF, (int)(id2[2 * q] & 0xffffu), fb);
                            tma_load(rows + (4 * q + 1) * 640, &tmF, (int)(id2[2 * q] >> 16), fb);
                            tma_load(rows + (4 * q + 2) * 640, &tmF, (int)(id2[2 * q + 1] & 0xffffu), fb);
                            tma_load(rows + (4 * q + 3) * 640, &tmF, (int)(id2[2 * q + 1] >> 16), fb);
                        } else {
                            if (4 * q < nv)     tma_load(rows + (4 * q) * 640, &tmF, (int)(id2[2 * q] & 0xffffu), fb);
                            if (4 * q + 1 < nv) tma_load(rows + (4 * q + 1) * 640, &tmF, (int)(id2[2 * q] >> 16), fb);
                            if (4 * q + 2 < nv) tma_load(rows + (4 * q + 2) * 640, &tmF, (int)(id2[2 * q + 1] & 0xffffu), fb);
                        }
                    }
                }
            }
            __syncwarp();
            if (left > 1) {
                ia = lds128(ida);
                ib = lds128(ida + 16);
                tv = __ldg((const uint4*)(tab + (m.x & 0xffffu)));
            }
            const uint32_t a = st + coef_off;
#pragma unroll
            for (int j = 0; j < 4; j++) sts128(a ^ ((j ^ vrot) << 5), o[j]);
            fence_async_smem();
            __syncwarp();
            mbar_arrive_elected(fb);
            stage += 2;
            if (stage >= nstage) { stage -= nstage; phase ^= 1; }
        }
    } else if (wgi == 2) {
        mbar_arrive_elected(bar_hempty);
        mbar_arrive_elected(bar_hempty + 8);
        uint32_t wA[2][4][4];
        {
            const uint16_t* w2 = (const uint16_t*)p.w2 + 16 * w + g;
#pragma unroll
            for (int mk = 0; mk < 8; mk++) {
#pragma unroll
                for (int i = 0; i < 4; i++) {
                    const uint16_t* q = w2 + (16 * (mk & 3) + 2 * t + 8 * (i >> 1)) * 192 + (mk >> 2) * 128 + 8 * (i & 1);
                    wA[mk >> 2][mk & 3][i] = (uint32_t)__ldg(q) | ((uint32_t)__ldg(q + 192) << 16);
                }
            }
        }
        const uint32_t lane_off = (uint32_t)node0 * 512u + t * 128 + w * 32 + (g & 1) * 16 + (g >> 1) * 4;
        uint32_t hpar = 0;
        float zs[8], zv[24], pvv[6], pr[4][2];
        auto start = [&](int ent) {
            const int c = ent >> 7;
            mbar_wait(bar_hfull + c * 8, (hpar >> c) & 1);
            hpar ^= 1u << c;
            const uint32_t dht = desc_lo(sb + SM_HT + c * 8192);
            wg_fence();
            wgmma_n16_first(zs, wA[0][0], dht);
            wgmma_n48_first(zv, wA[1][0], dht + 2);
#pragma unroll
            for (int ks = 1; ks < 4; ks++) {
                wgmma_n16(zs, wA[0][ks], dht + ks * 128);
                wgmma_n48(zv, wA[1][ks], dht + ks * 128 + 2);
            }
            wg_commit();
        };
        auto side = [&](int ent) {
            const int c = ent >> 7;
            const uint32_t pa = sb + SM_PV + c * 3072 + (tid & 127) * 8;
            const uint2 a0 = lds64(pa), a1 = lds64(pa + 1024), a2 = lds64(pa + 2048);
            pvv[0] = __uint_as_float(a0.x); pvv[1] = __uint_as_float(a0.y); pvv[2] = __uint_as_float(a1.x);
            pvv[3] = __uint_as_float(a1.y); pvv[4] = __uint_as_float(a2.x); pvv[5] = __uint_as_float(a2.y);
            __syncwarp();
            mbar_arrive_elected(bar_hempty + c * 8);
        };
        auto weigh = [&]() {
#pragma unroll
            for (int i = 0; i < 12; i++) asm volatile("" : "+r"(wp[i >> 2][i & 3]));
            pr[0][0] = bf_lo(wp[0][0]) * zs[0] + bf_hi(wp[0][0]) * zs[1] + bf_lo(wp[0][2]) * zs[4] + bf_hi(wp[0][2]) * zs[5];
            pr[0][1] = bf_lo(wp[0][1]) * zs[2] + bf_hi(wp[0][1]) * zs[3] + bf_lo(wp[0][3]) * zs[6] + bf_hi(wp[0][3]) * zs[7];
#pragma unroll
            for (int a = 0; a < 3; a++) {
                const float* y = zv + 8 * a;
                pr[a + 1][0] = pvv[2 * a] + bf_lo(wp[2][0]) * y[0] + bf_hi(wp[2][0]) * y[1] + bf_lo(wp[2][2]) * y[4] + bf_hi(wp[2][2]) * y[5];
                pr[a + 1][1] = pvv[2 * a + 1] + bf_lo(wp[2][1]) * y[2] + bf_hi(wp[2][1]) * y[3] + bf_lo(wp[2][3]) * y[6] + bf_hi(wp[2][3]) * y[7];
            }
            asm volatile("" : "+f"(pr[0][0]), "+f"(pr[0][1]), "+f"(pr[1][0]), "+f"(pr[1][1]), "+f"(pr[2][0]), "+f"(pr[2][1]), "+f"(pr[3][0]), "+f"(pr[3][1]) :: "memory");
        };
        auto finish = [&](int ent, uint32_t resid) {
            const bool hi2 = t & 2, hi1 = t & 1, odd = g & 1;
            float ka0 = hi2 ? pr[2][0] : pr[0][0], ka1 = hi2 ? pr[2][1] : pr[0][1];
            float kb0 = hi2 ? pr[3][0] : pr[1][0], kb1 = hi2 ? pr[3][1] : pr[1][1];
            float sa0 = hi2 ? pr[0][0] : pr[2][0], sa1 = hi2 ? pr[0][1] : pr[2][1];
            float sb0 = hi2 ? pr[1][0] : pr[3][0], sb1 = hi2 ? pr[1][1] : pr[3][1];
            ka0 += __shfl_xor_sync(0xffffffffu, sa0, 2); ka1 += __shfl_xor_sync(0xffffffffu, sa1, 2);
            kb0 += __shfl_xor_sync(0xffffffffu, sb0, 2); kb1 += __shfl_xor_sync(0xffffffffu, sb1, 2);
            float k0 = hi1 ? kb0 : ka0, k1 = hi1 ? kb1 : ka1;
            float s0 = hi1 ? ka0 : kb0, s1 = hi1 ? ka1 : kb1;
            k0 += __shfl_xor_sync(0xffffffffu, s0, 1);
            k1 += __shfl_xor_sync(0xffffffffu, s1, 1);
            const float other = __shfl_xor_sync(0xffffffffu, odd ? k0 : k1, 4);
            const float lo = odd ? other : k0, hi = odd ? k1 : other;
            *(uint32_t*)((uint8_t*)p.out + (lane_off + (uint32_t)(ent & 127) * 512u)) = pack_bf(bf_lo(resid) + lo, bf_hi(resid) + hi);
        };
        auto entry = [&](int i) -> int { return __reduce_max_sync(0xffffffffu, (int)smem[SM_ORDER + i]); };
        auto load_resid = [&](int ent) -> uint32_t { return __ldg((const uint32_t*)((const uint8_t*)p.sv + (lane_off + (uint32_t)(ent & 127) * 512u))); };
        if (nnodes > 0) {
            int cur = entry(0), nxt = entry(1);
            uint32_t resid = load_resid(cur);
            start(cur);
#pragma unroll 1
            for (int i = 1; i < nnodes; i++) {
                wg_wait0();
                side(cur);
                weigh();
                start(nxt);
                finish(cur, resid);
                cur = nxt;
                resid = load_resid(cur);
                nxt = entry(i + 1);
            }
            wg_wait0();
            side(cur);
            weigh();
            finish(cur, resid);
        }
    } else {
        const int wg = wgi;
        uint32_t aoff[4];
        {
            const int e = (lane & 7) + 8 * (lane >> 4), ch = 2 * w + ((lane >> 3) & 1);
#pragma unroll
            for (int b = 0; b < 4; b++) aoff[b] = 2048 + e * 640 + b * 128 + ((ch ^ ((5 * e + b) & 7)) << 4);
        }
        const uint32_t stsm_a = sb + SM_HT + wg * 8192 + (16 * w + (lane & 15)) * 128 + (((lane >> 4) ^ (lane & 7)) << 4);
        const uint32_t pv_a = sb + SM_PV + wg * 3072 + (tid & 127) * 8;
        const uint32_t ring_wg = ring + wg * nstage * STAGE_B;
        const uint32_t full_wg = bar_full + wg * MAX_STAGE * 8;

        float ys[8], yv[24], dQ[3][8];
        uint32_t A0[4][4], A1[4][4];
#pragma unroll
        for (int i = 0; i < 24; i++) yv[i] = 0.f;
#pragma unroll
        for (int i = 0; i < 8; i++) { ys[i] = 0.f; dQ[0][i] = 0.f; dQ[1][i] = 0.f; dQ[2][i] = 0.f; }
        int left = wg == 0 ? mid : (slots >> 4) - mid;
        int fstage = 0;
        uint32_t fphase = 0, fst = ring_wg, fbar = full_wg, hphase = 0;
        uint32_t ninfo_a = sb + SM_NINFO + (wg == 0 ? 0 : split) * 4;
        int gi = 0, G = __reduce_max_sync(0xffffffffu, (int)(lds32(ninfo_a) >> 20));

        auto fetch = [&](uint32_t (&A)[4][4], uint32_t& bd, uint32_t& eb) {
            mbar_wait(fbar, fphase);
#pragma unroll
            for (int b = 0; b < 4; b++) ldsm4t(A[b], fst + aoff[b]);
            bd = desc_lo(fst);
            eb = fbar + EMPTY_OFF;
            fst += STAGE_B; fbar += 8;
            if (++fstage == nstage) { fstage = 0; fphase ^= 1; fst = ring_wg; fbar = full_wg; }
        };
        auto step = [&](uint32_t (&Ac)[4][4], uint32_t bdc, uint32_t ebc, uint32_t (&An)[4][4], uint32_t& bdn, uint32_t& ebn) {
            wg_fence();
            wgmma_n64_p(ys, yv, Ac[0], bdc, gi);
            wgmma_n16_p(dQ[0], Ac[1], bdc, gi);
            wgmma_n16_p(dQ[1], Ac[2], bdc, gi);
            wgmma_n16_p(dQ[2], Ac[3], bdc, gi);
            wg_commit();
            if (--left > 0) fetch(An, bdn, ebn);
            const bool last = ++gi == G;
            uint32_t info_next = 0;
            if (last) { ninfo_a += 4; info_next = lds32(ninfo_a); }
            wg_wait0();
            mbar_arrive_elected(ebc);
            if (last) {
                mbar_wait(bar_hempty + wg * 8, hphase);
                hphase ^= 1;
                stsm4(stsm_a, pack_bf(ys[0], ys[1]), pack_bf(ys[2], ys[3]), pack_bf(ys[4], ys[5]), pack_bf(ys[6], ys[7]));
#pragma unroll
                for (int i = 0; i < 6; i += 2) {
                    stsm4(stsm_a ^ ((i + 2) << 4),
                          pack_bf(yv[4 * i], yv[4 * i + 1]), pack_bf(yv[4 * i + 2], yv[4 * i + 3]),
                          pack_bf(yv[4 * i + 4], yv[4 * i + 5]), pack_bf(yv[4 * i + 6], yv[4 * i + 7]));
                }
#pragma unroll
                for (int i = 0; i < 4; i++) asm volatile("" : "+r"(wp[1][i]));
#pragma unroll
                for (int a = 0; a < 3; a++) {
                    const float* q = dQ[a];
                    const float p0 = bf_lo(wp[1][0]) * q[0] + bf_hi(wp[1][0]) * q[1] + bf_lo(wp[1][2]) * q[4] + bf_hi(wp[1][2]) * q[5];
                    const float p1 = bf_lo(wp[1][1]) * q[2] + bf_hi(wp[1][1]) * q[3] + bf_lo(wp[1][3]) * q[6] + bf_hi(wp[1][3]) * q[7];
                    asm volatile("st.shared.v2.f32 [%0], {%1, %2};" ::"r"(pv_a + a * 1024), "f"(p0), "f"(p1) : "memory");
                }
                fence_async_smem();
                __syncwarp();
                mbar_arrive_elected(bar_hfull + wg * 8);
                G = __reduce_max_sync(0xffffffffu, (int)(info_next >> 20));
                gi = 0;
            }
        };
        if (left > 0) {
            uint32_t bd0, eb0, bd1 = 0, eb1 = 0;
            fetch(A0, bd0, eb0);
            while (true) {
                step(A0, bd0, eb0, A1, bd1, eb1);
                if (left <= 0) break;
                step(A1, bd1, eb1, A0, bd0, eb0);
                if (left <= 0) break;
            }
        }
    }
    STAMP(8);
}

typedef CUresult (*EncodeFn)(CUtensorMap*, CUtensorMapDataType, cuuint32_t, void*, const cuuint64_t*, const cuuint64_t*,
                             const cuuint32_t*, const cuuint32_t*, CUtensorMapInterleave, CUtensorMapSwizzle,
                             CUtensorMapL2promotion, CUtensorMapFloatOOBfill);

void make_map(EncodeFn enc, CUtensorMap* tm, const void* base, uint64_t lines, uint32_t box) {
    cuuint64_t gd[2] = {64, lines};
    cuuint64_t gs[1] = {128};
    cuuint32_t bd[2] = {64, box};
    cuuint32_t es[2] = {1, 1};
    enc(tm, CU_TENSOR_MAP_DATA_TYPE_BFLOAT16, 2, const_cast<void*>(base), gd, gs, bd, es, CU_TENSOR_MAP_INTERLEAVE_NONE,
        CU_TENSOR_MAP_SWIZZLE_128B, CU_TENSOR_MAP_L2_PROMOTION_L2_128B, CU_TENSOR_MAP_FLOAT_OOB_FILL_NONE);
}

void make_map3(EncodeFn enc, CUtensorMap* tm, const void* base, uint64_t nodes, uint32_t box) {
    cuuint64_t gd[3] = {64, 4, nodes};
    cuuint64_t gs[2] = {128, 512};
    cuuint32_t bd[3] = {64, 1, box};
    cuuint32_t es[3] = {1, 1, 1};
    enc(tm, CU_TENSOR_MAP_DATA_TYPE_BFLOAT16, 3, const_cast<void*>(base), gd, gs, bd, es, CU_TENSOR_MAP_INTERLEAVE_NONE,
        CU_TENSOR_MAP_SWIZZLE_128B, CU_TENSOR_MAP_L2_PROMOTION_L2_128B, CU_TENSOR_MAP_FLOAT_OOB_FILL_NONE);
}

}

extern "C" void kernel_launch(void* const* d_in, const int* in_sizes, int n_in, void* d_out, int out_size) {
    (void)n_in; (void)out_size;
    static int n_sm = 0;
    static EncodeFn enc = nullptr;
    static void* f_ptr = nullptr;
    if (n_sm == 0) {
        int dev = 0;
        cudaGetDevice(&dev);
        cudaDeviceGetAttribute(&n_sm, cudaDevAttrMultiProcessorCount, dev);
        cudaFuncSetAttribute(painn_kernel, cudaFuncAttributeMaxDynamicSharedMemorySize, SM_TOTAL);
        void* fn = nullptr;
        cudaDriverEntryPointQueryResult qr;
        cudaGetDriverEntryPoint("cuTensorMapEncodeTiled", &fn, cudaEnableDefault, &qr);
        enc = (EncodeFn)fn;
        cudaGetSymbolAddress(&f_ptr, g_F);
    }
    Params p;
    p.sv    = (const __nv_bfloat16*)d_in[0];
    p.pos   = (const __nv_bfloat16*)d_in[1];
    p.src   = (const int*)d_in[2];
    p.dst   = (const int*)d_in[3];
    p.freqs = (const __nv_bfloat16*)d_in[4];
    p.w1    = (const __nv_bfloat16*)d_in[5];
    p.w2    = (const __nv_bfloat16*)d_in[6];
    p.wr    = (const __nv_bfloat16*)d_in[7];
    p.out   = (__nv_bfloat16*)d_out;
    p.N = in_sizes[1] / 3;
    p.E = in_sizes[2];
    p.ncta = n_sm < MAX_CTA ? n_sm : MAX_CTA;
    p.npc = ((p.N + p.ncta - 1) / p.ncta + 3) & ~3;
    p.npc_magic = (uint32_t)(0x100000000ull / (uint32_t)p.npc) + 1u;
    p.quads_per_cta = ((p.E >> 2) + p.ncta - 1) / p.ncta;
    if (!enc || p.N > MAX_N || p.npc > MAX_NPC || (p.E & 3) || p.quads_per_cta > MAX_ROUNDS * 32) return;

    CUtensorMap tmF, tmFs;
    make_map(enc, &tmF, f_ptr, (uint64_t)p.N * 4, 4);
    make_map3(enc, &tmFs, f_ptr, (uint64_t)p.N, 4);

    cudaLaunchConfig_t cfg = {};
    cfg.gridDim = dim3(p.ncta);
    cfg.blockDim = dim3(NT);
    cfg.dynamicSmemBytes = SM_TOTAL;
    cfg.stream = cudaStreamPerThread;
    cudaLaunchAttribute attr[1];
    attr[0].id = cudaLaunchAttributeCooperative;
    attr[0].val.cooperative = 1;
    cfg.attrs = attr;
    cfg.numAttrs = 1;
    cudaLaunchKernelEx(&cfg, painn_kernel, p, tmF, tmFs);
}
```

```cpp
#include <cuda_runtime.h>
#include <cuda.h>
#include <cuda_bf16.h>
#include <stdint.h>

namespace {

constexpr int NT        = 512;
constexpr int NCWG      = 2;
constexpr int MAX_N     = 10240;
constexpr int MAX_CTA   = 136;
constexpr int MAX_NPC   = 80;
constexpr int MAX_ROUNDS = 38;
constexpr int REC_CAP   = MAX_ROUNDS * 128;
constexpr int SEG_CAP   = 64;
constexpr int SLOT_CAP  = 6144;
constexpr int MAX_STAGE = 6;
constexpr int STAGE_B   = 12288;

constexpr uint32_t D_MIN_BITS = 0x38D2;
constexpr uint32_t D_MAX_BITS = 0x409C;
constexpr int TAB_ROWS  = (int)(D_MAX_BITS - D_MIN_BITS) + 1;
constexpr int TAB_ZERO  = TAB_ROWS;
constexpr int TAB_BYTES = (TAB_ROWS + 1) * 32;

constexpr int SM_BINCNT = 0;
constexpr int SM_BINOFF = SM_BINCNT + MAX_CTA * 4;
constexpr int SM_NCNT   = SM_BINOFF + MAX_CTA * 4;
constexpr int SM_NINFO  = SM_NCNT + MAX_NPC * 4;
constexpr int SM_ORDER  = SM_NINFO + (MAX_NPC + 1) * 4;
constexpr int SM_CTRL   = SM_ORDER + MAX_NPC + 12;
constexpr int SM_BARS   = SM_CTRL + 64;
constexpr int SM_SID    = 2048 + 256;
constexpr int SM_META   = SM_SID + SLOT_CAP * 2;
constexpr int SM_TOTAL  = 232448;
constexpr int SM_HT     = (SM_TOTAL - 3 * 8192) / 1024 * 1024;
constexpr int SM_PV     = SM_HT + 2 * 8192;
constexpr int SM_RING4  = SM_HT - NCWG * 6 * STAGE_B;
constexpr int SM_RING3  = SM_HT - NCWG * 5 * STAGE_B;
constexpr int SLOT_CAP4 = (SM_RING4 - SM_META) / 8;
constexpr int P1_POS    = 3072;
constexpr int P1_SEGA   = P1_POS + 61440;
constexpr int P1_SEGB   = P1_SEGA + MAX_CTA * SEG_CAP * 8;
constexpr int P1_SV     = P1_SEGB + MAX_CTA * SEG_CAP * 4;
constexpr int P1_W1     = P1_SV + 4 * MAX_NPC * 128;
constexpr int P1_W2     = P1_W1 + 8192;
constexpr int P1_END    = P1_W2 + 8192;
constexpr int P1_REC    = P1_SEGA;
constexpr int STAGE_CAP = (P1_SV - P1_REC) / 16;
static_assert(SM_BARS + (8 + 2 * NCWG * MAX_STAGE) * 8 <= SM_SID, "misc block");
static_assert(SM_BARS + 256 <= P1_POS, "misc block");
static_assert(P1_END <= SM_TOTAL && P1_SV % 1024 == 0 && P1_REC % 16 == 0, "phase 1 overlay");
static_assert(SM_META + SLOT_CAP * 8 <= SM_RING3, "CSR");
static_assert(SM_RING4 % 1024 == 0 && SM_RING3 % 1024 == 0 && SM_HT % 1024 == 0, "alignment");
static_assert(SM_BARS % 8 == 0 && SM_META % 8 == 0 && SM_CTRL % 4 == 0, "alignment");
static_assert(MAX_N * 6 <= 61440, "pos");
static_assert(SM_SID + MAX_NPC * 1024 <= SM_TOTAL, "slow path accumulators");

__device__ __align__(1024) uint4 g_F[MAX_N * 32];
__device__ __align__(128) uint32_t g_seg[MAX_CTA * MAX_CTA * SEG_CAP * 3];
__device__ uint4    g_table[(TAB_BYTES + 15) / 16];
__device__ unsigned g_bar[2];
#define STAMP(k)
#define STAMPT(k, T)
#define ITS(k)

struct Params {
    const __nv_bfloat16* sv;
    const __nv_bfloat16* pos;
    const int*           src;
    const int*           dst;
    const __nv_bfloat16* freqs;
    const __nv_bfloat16* w1;
    const __nv_bfloat16* w2;
    const __nv_bfloat16* wr;
    __nv_bfloat16*       out;
    int N, E, ncta, npc;
    uint32_t npc_magic;
    int quads_per_cta;
};

__device__ __forceinline__ uint32_t smem_u32(const void* p) { return (uint32_t)__cvta_generic_to_shared(p); }
__device__ __forceinline__ float bf_lo(uint32_t v) { return __uint_as_float(v << 16); }
__device__ __forceinline__ float bf_hi(uint32_t v) { return __uint_as_float(v & 0xffff0000u); }
__device__ __forceinline__ float bf_u16(uint16_t v) { return __uint_as_float((uint32_t)v << 16); }
__device__ __forceinline__ uint32_t pack_bf(float lo, float hi) {
    uint32_t r;
    asm("cvt.rn.bf16x2.f32 %0, %1, %2;" : "=r"(r) : "f"(hi), "f"(lo));
    return r;
}
__device__ __forceinline__ float rbf(float x) { return bf_lo(pack_bf(x, 0.f)); }
__device__ __forceinline__ uint32_t hmul2(uint32_t a, uint32_t b) {
    uint32_t r;
    asm("mul.rn.bf16x2 %0, %1, %2;" : "=r"(r) : "r"(a), "r"(b));
    return r;
}
__device__ __forceinline__ uint32_t hsub2(uint32_t a, uint32_t b) {
    uint32_t r;
    asm("sub.rn.bf16x2 %0, %1, %2;" : "=r"(r) : "r"(a), "r"(b));
    return r;
}
__device__ __forceinline__ uint32_t lds32(uint32_t a) { uint32_t v; asm volatile("ld.shared.u32 %0, [%1];" : "=r"(v) : "r"(a)); return v; }
__device__ __forceinline__ uint32_t lds16(uint32_t a) { uint16_t v; asm volatile("ld.shared.u16 %0, [%1];" : "=h"(v) : "r"(a)); return v; }
__device__ __forceinline__ uint2 lds64(uint32_t a) { uint2 v; asm volatile("ld.shared.v2.u32 {%0,%1}, [%2];" : "=r"(v.x), "=r"(v.y) : "r"(a)); return v; }
__device__ __forceinline__ uint4 lds128(uint32_t a) { uint4 v; asm volatile("ld.shared.v4.u32 {%0,%1,%2,%3}, [%4];" : "=r"(v.x), "=r"(v.y), "=r"(v.z), "=r"(v.w) : "r"(a)); return v; }
__device__ __forceinline__ void sts32(uint32_t a, uint32_t v) { asm volatile("st.shared.u32 [%0], %1;" ::"r"(a), "r"(v) : "memory"); }
__device__ __forceinline__ void sts128(uint32_t a, uint4 v) { asm volatile("st.shared.v4.u32 [%0], {%1,%2,%3,%4};" ::"r"(a), "r"(v.x), "r"(v.y), "r"(v.z), "r"(v.w) : "memory"); }
__device__ __forceinline__ void mbar_init(uint32_t bar, int cnt) { asm volatile("mbarrier.init.shared::cta.b64 [%0], %1;" ::"r"(bar), "r"(cnt) : "memory"); }
__device__ __forceinline__ void mbar_expect_tx(uint32_t bar, uint32_t bytes) { asm volatile("mbarrier.arrive.expect_tx.shared::cta.b64 _, [%0], %1;" ::"r"(bar), "r"(bytes) : "memory"); }
__device__ __forceinline__ void mbar_arrive(uint32_t bar) { asm volatile("mbarrier.arrive.shared::cta.b64 _, [%0];" ::"r"(bar) : "memory"); }
__device__ __forceinline__ void mbar_wait(uint32_t bar, uint32_t parity) {
    asm volatile("{\n.reg .pred p;\n.reg .u32 c;\n"
                 "mbarrier.try_wait.parity.shared::cta.b64 p, [%0], %1;\n"
                 "@p bra DONE_%=;\n"
                 "mov.u32 c, 0;\n"
                 "LOOP_%=:\n"
                 "mbarrier.try_wait.parity.shared::cta.b64 p, [%0], %1;\n"
                 "@p bra DONE_%=;\n"
                 "add.u32 c, c, 1;\n"
                 "setp.lt.u32 p, c, 4194304;\n"
                 "@p bra LOOP_%=;\n"
                 "DONE_%=:\n}"
                 ::"r"(bar), "r"(parity) : "memory");
}
__device__ __forceinline__ void mbar_arrive_elected(uint32_t bar) {
    asm volatile("{\n.reg .pred p;\nelect.sync _|p, 0xffffffff;\n@p mbarrier.arrive.shared::cta.b64 _, [%0];\n}" ::"r"(bar) : "memory");
}
__device__ __forceinline__ void bulk_g2s(uint32_t dst, const void* src, uint32_t bytes, uint32_t bar) {
    asm volatile("cp.async.bulk.shared::cluster.global.mbarrier::complete_tx::bytes [%0], [%1], %2, [%3];"
                 ::"r"(dst), "l"(src), "r"(bytes), "r"(bar) : "memory");
}
__device__ __forceinline__ void cp_async16(uint32_t dst, const void* src) {
    asm volatile("cp.async.cg.shared.global [%0], [%1], 16;" ::"r"(dst), "l"(src) : "memory");
}
__device__ __forceinline__ void tma_load(uint32_t dst, const CUtensorMap* tm, int line, uint32_t bar) {
    asm volatile("cp.async.bulk.tensor.2d.shared::cluster.global.mbarrier::complete_tx::bytes [%0], [%1, {%3, %4}], [%2];"
                 ::"r"(dst), "l"(tm), "r"(bar), "r"(0), "r"(line) : "memory");
}
__device__ __forceinline__ void tma_load3(uint32_t dst, const CUtensorMap* tm, int comp, int node, uint32_t bar) {
    asm volatile("cp.async.bulk.tensor.3d.shared::cluster.global.mbarrier::complete_tx::bytes [%0], [%1, {%3, %4, %5}], [%2];"
                 ::"r"(dst), "l"(tm), "r"(bar), "r"(0), "r"(comp), "r"(node) : "memory");
}
__device__ __forceinline__ void tma_store3(const CUtensorMap* tm, int comp, int node, uint32_t src) {
    asm volatile("cp.async.bulk.tensor.3d.global.shared::cta.bulk_group [%0, {%2, %3, %4}], [%1];"
                 ::"l"(tm), "r"(src), "r"(0), "r"(comp), "r"(node) : "memory");
}
__device__ __forceinline__ void fence_async_smem() { asm volatile("fence.proxy.async.shared::cta;" ::: "memory"); }
__device__ __forceinline__ void named_barrier(int id) { asm volatile("bar.sync %0, 128;" ::"r"(id) : "memory"); }
__device__ __forceinline__ void ldsm4(uint32_t (&r)[4], uint32_t a) {
    asm volatile("ldmatrix.sync.aligned.m8n8.x4.shared.b16 {%0,%1,%2,%3}, [%4];" : "=r"(r[0]), "=r"(r[1]), "=r"(r[2]), "=r"(r[3]) : "r"(a) : "memory");
}
__device__ __forceinline__ void ldsm4t(uint32_t (&r)[4], uint32_t a) {
    asm volatile("ldmatrix.sync.aligned.m8n8.x4.trans.shared.b16 {%0,%1,%2,%3}, [%4];" : "=r"(r[0]), "=r"(r[1]), "=r"(r[2]), "=r"(r[3]) : "r"(a) : "memory");
}
__device__ __forceinline__ void stsm4(uint32_t a, uint32_t r0, uint32_t r1, uint32_t r2, uint32_t r3) {
    asm volatile("stmatrix.sync.aligned.m8n8.x4.shared.b16 [%0], {%1,%2,%3,%4};" ::"r"(a), "r"(r0), "r"(r1), "r"(r2), "r"(r3) : "memory");
}
__device__ __forceinline__ void mma16816(float (&c)[4], const uint32_t (&a)[4], uint32_t b0, uint32_t b1) {
    asm volatile("mma.sync.aligned.m16n8k16.row.col.f32.bf16.bf16.f32 {%0,%1,%2,%3}, {%4,%5,%6,%7}, {%8,%9}, {%0,%1,%2,%3};"
                 : "+f"(c[0]), "+f"(c[1]), "+f"(c[2]), "+f"(c[3])
                 : "r"(a[0]), "r"(a[1]), "r"(a[2]), "r"(a[3]), "r"(b0), "r"(b1));
}

__device__ __forceinline__ uint32_t desc_lo(uint32_t saddr) { return ((saddr & 0x3FFFF) >> 4) | (1u << 16); }
#define DESC_HI "0x40000040"
__device__ __forceinline__ void wg_fence() { asm volatile("wgmma.fence.sync.aligned;" ::: "memory"); }
__device__ __forceinline__ void wg_commit() { asm volatile("wgmma.commit_group.sync.aligned;" ::: "memory"); }
__device__ __forceinline__ void wg_wait0() { asm volatile("wgmma.wait_group.sync.aligned 0;" ::: "memory"); }
__device__ __forceinline__ void wg_wait1() { asm volatile("wgmma.wait_group.sync.aligned 1;" ::: "memory"); }

__device__ __forceinline__ void wgmma_n64_first(float (&d)[8], float (&e)[24], const uint32_t (&a)[4], uint32_t bdesc) {
    asm volatile("{\n.reg .b64 b;\nmov.b64 b, {%36, " DESC_HI "};\n"
                 "wgmma.mma_async.sync.aligned.m64n64k16.f32.bf16.bf16 {%0,%1,%2,%3,%4,%5,%6,%7,%8,%9,%10,%11,%12,%13,%14,%15,%16,%17,%18,%19,%20,%21,%22,%23,%24,%25,%26,%27,%28,%29,%30,%31}, {%32,%33,%34,%35}, b, 0, 1, 1, 1;\n}"
                 : "=f"(d[0]), "=f"(d[1]), "=f"(d[2]), "=f"(d[3]), "=f"(d[4]), "=f"(d[5]), "=f"(d[6]), "=f"(d[7]),
                   "=f"(e[0]), "=f"(e[1]), "=f"(e[2]), "=f"(e[3]), "=f"(e[4]), "=f"(e[5]), "=f"(e[6]), "=f"(e[7]), "=f"(e[8]), "=f"(e[9]), "=f"(e[10]), "=f"(e[11]), "=f"(e[12]), "=f"(e[13]), "=f"(e[14]), "=f"(e[15]), "=f"(e[16]), "=f"(e[17]), "=f"(e[18]), "=f"(e[19]), "=f"(e[20]), "=f"(e[21]), "=f"(e[22]), "=f"(e[23])
                 : "r"(a[0]), "r"(a[1]), "r"(a[2]), "r"(a[3]), "r"(bdesc));
}
__device__ __forceinline__ void wgmma_n64(float (&d)[8], float (&e)[24], const uint32_t (&a)[4], uint32_t bdesc) {
    asm volatile("{\n.reg .b64 b;\nmov.b64 b, {%36, " DESC_HI "};\n"
                 "wgmma.mma_async.sync.aligned.m64n64k16.f32.bf16.bf16 {%0,%1,%2,%3,%4,%5,%6,%7,%8,%9,%10,%11,%12,%13,%14,%15,%16,%17,%18,%19,%20,%21,%22,%23,%24,%25,%26,%27,%28,%29,%30,%31}, {%32,%33,%34,%35}, b, 1, 1, 1, 1;\n}"
                 : "+f"(d[0]), "+f"(d[1]), "+f"(d[2]), "+f"(d[3]), "+f"(d[4]), "+f"(d[5]), "+f"(d[6]), "+f"(d[7]),
                   "+f"(e[0]), "+f"(e[1]), "+f"(e[2]), "+f"(e[3]), "+f"(e[4]), "+f"(e[5]), "+f"(e[6]), "+f"(e[7]), "+f"(e[8]), "+f"(e[9]), "+f"(e[10]), "+f"(e[11]), "+f"(e[12]), "+f"(e[13]), "+f"(e[14]), "+f"(e[15]), "+f"(e[16]), "+f"(e[17]), "+f"(e[18]), "+f"(e[19]), "+f"(e[20]), "+f"(e[21]), "+f"(e[22]), "+f"(e[23])
                 : "r"(a[0]), "r"(a[1]), "r"(a[2]), "r"(a[3]), "r"(bdesc));
}
__device__ __forceinline__ void wgmma_n48_first(float (&e)[24], const uint32_t (&a)[4], uint32_t bdesc) {
    asm volatile("{\n.reg .b64 b;\nmov.b64 b, {%28, " DESC_HI "};\n"
                 "wgmma.mma_async.sync.aligned.m64n48k16.f32.bf16.bf16 {%0,%1,%2,%3,%4,%5,%6,%7,%8,%9,%10,%11,%12,%13,%14,%15,%16,%17,%18,%19,%20,%21,%22,%23}, {%24,%25,%26,%27}, b, 0, 1, 1, 1;\n}"
                 : "=f"(e[0]), "=f"(e[1]), "=f"(e[2]), "=f"(e[3]), "=f"(e[4]), "=f"(e[5]), "=f"(e[6]), "=f"(e[7]), "=f"(e[8]), "=f"(e[9]), "=f"(e[10]), "=f"(e[11]), "=f"(e[12]), "=f"(e[13]), "=f"(e[14]), "=f"(e[15]), "=f"(e[16]), "=f"(e[17]), "=f"(e[18]), "=f"(e[19]), "=f"(e[20]), "=f"(e[21]), "=f"(e[22]), "=f"(e[23])
                 : "r"(a[0]), "r"(a[1]), "r"(a[2]), "r"(a[3]), "r"(bdesc));
}
__device__ __forceinline__ void wgmma_n48(float (&e)[24], const uint32_t (&a)[4], uint32_t bdesc) {
    asm volatile("{\n.reg .b64 b;\nmov.b64 b, {%28, " DESC_HI "};\n"
                 "wgmma.mma_async.sync.aligned.m64n48k16.f32.bf16.bf16 {%0,%1,%2,%3,%4,%5,%6,%7,%8,%9,%10,%11,%12,%13,%14,%15,%16,%17,%18,%19,%20,%21,%22,%23}, {%24,%25,%26,%27}, b, 1, 1, 1, 1;\n}"
                 : "+f"(e[0]), "+f"(e[1]), "+f"(e[2]), "+f"(e[3]), "+f"(e[4]), "+f"(e[5]), "+f"(e[6]), "+f"(e[7]), "+f"(e[8]), "+f"(e[9]), "+f"(e[10]), "+f"(e[11]), "+f"(e[12]), "+f"(e[13]), "+f"(e[14]), "+f"(e[15]), "+f"(e[16]), "+f"(e[17]), "+f"(e[18]), "+f"(e[19]), "+f"(e[20]), "+f"(e[21]), "+f"(e[22]), "+f"(e[23])
                 : "r"(a[0]), "r"(a[1]), "r"(a[2]), "r"(a[3]), "r"(bdesc));
}
__device__ __forceinline__ void wgmma_n16_first(float (&d)[8], const uint32_t (&a)[4], uint32_t bdesc) {
    asm volatile("{\n.reg .b64 b;\nmov.b64 b, {%12, " DESC_HI "};\n"
                 "wgmma.mma_async.sync.aligned.m64n16k16.f32.bf16.bf16 {%0,%1,%2,%3,%4,%5,%6,%7}, {%8,%9,%10,%11}, b, 0, 1, 1, 1;\n}"
                 : "=f"(d[0]), "=f"(d[1]), "=f"(d[2]), "=f"(d[3]), "=f"(d[4]), "=f"(d[5]), "=f"(d[6]), "=f"(d[7])
                 : "r"(a[0]), "r"(a[1]), "r"(a[2]), "r"(a[3]), "r"(bdesc));
}
__device__ __forceinline__ void wgmma_n16(float (&d)[8], const uint32_t (&a)[4], uint32_t bdesc) {
    asm volatile("{\n.reg .b64 b;\nmov.b64 b, {%12, " DESC_HI "};\n"
                 "wgmma.mma_async.sync.aligned.m64n16k16.f32.bf16.bf16 {%0,%1,%2,%3,%4,%5,%6,%7}, {%8,%9,%10,%11}, b, 1, 1, 1, 1;\n}"
                 : "+f"(d[0]), "+f"(d[1]), "+f"(d[2]), "+f"(d[3]), "+f"(d[4]), "+f"(d[5]), "+f"(d[6]), "+f"(d[7])
                 : "r"(a[0]), "r"(a[1]), "r"(a[2]), "r"(a[3]), "r"(bdesc));
}

__device__ __forceinline__ void wgmma_n64_p(float (&d)[8], float (&e)[24], const uint32_t (&a)[4], uint32_t bdesc, int acc) {
    asm volatile("{\n.reg .pred p;\n.reg .b64 b;\nsetp.ne.b32 p, %37, 0;\nmov.b64 b, {%36, " DESC_HI "};\n"
                 "wgmma.mma_async.sync.aligned.m64n64k16.f32.bf16.bf16 {%0,%1,%2,%3,%4,%5,%6,%7,%8,%9,%10,%11,%12,%13,%14,%15,%16,%17,%18,%19,%20,%21,%22,%23,%24,%25,%26,%27,%28,%29,%30,%31}, {%32,%33,%34,%35}, b, p, 1, 1, 1;\n}"
                 : "+f"(d[0]), "+f"(d[1]), "+f"(d[2]), "+f"(d[3]), "+f"(d[4]), "+f"(d[5]), "+f"(d[6]), "+f"(d[7]),
                   "+f"(e[0]), "+f"(e[1]), "+f"(e[2]), "+f"(e[3]), "+f"(e[4]), "+f"(e[5]), "+f"(e[6]), "+f"(e[7]), "+f"(e[8]), "+f"(e[9]), "+f"(e[10]), "+f"(e[11]), "+f"(e[12]), "+f"(e[13]), "+f"(e[14]), "+f"(e[15]), "+f"(e[16]), "+f"(e[17]), "+f"(e[18]), "+f"(e[19]), "+f"(e[20]), "+f"(e[21]), "+f"(e[22]), "+f"(e[23])
                 : "r"(a[0]), "r"(a[1]), "r"(a[2]), "r"(a[3]), "r"(bdesc), "r"(acc));
}
__device__ __forceinline__ void wgmma_n16_p(float (&d)[8], const uint32_t (&a)[4], uint32_t bdesc, int acc) {
    asm volatile("{\n.reg .pred p;\n.reg .b64 b;\nsetp.ne.b32 p, %13, 0;\nmov.b64 b, {%12, " DESC_HI "};\n"
                 "wgmma.mma_async.sync.aligned.m64n16k16.f32.bf16.bf16 {%0,%1,%2,%3,%4,%5,%6,%7}, {%8,%9,%10,%11}, b, p, 1, 1, 1;\n}"
                 : "+f"(d[0]), "+f"(d[1]), "+f"(d[2]), "+f"(d[3]), "+f"(d[4]), "+f"(d[5]), "+f"(d[6]), "+f"(d[7])
                 : "r"(a[0]), "r"(a[1]), "r"(a[2]), "r"(a[3]), "r"(bdesc), "r"(acc));
}

__device__ __forceinline__ uint32_t edge_dist(uint32_t sxy, uint32_t sz, uint32_t dxy, uint32_t dz, uint32_t& rxy, uint32_t& rz) {
    rxy = hsub2(sxy, dxy);
    rz  = hsub2(sz, dz);
    uint32_t qxy = hmul2(rxy, rxy), qz = hmul2(rz, rz);
    float ss = rbf((bf_lo(qxy) + bf_hi(qxy)) + bf_lo(qz));
    float s2 = rbf(ss + 1e-8f);
    float d;
    asm("sqrt.approx.ftz.f32 %0, %1;" : "=f"(d) : "f"(s2));
    return pack_bf(d, 0.f) & 0xffffu;
}

__device__ __forceinline__ void load_pos(uint32_t sm_pos, int i, uint32_t& xy, uint32_t& z) {
    uint32_t a  = (sm_pos + 6u * (uint32_t)i) & ~3u;
    uint32_t w0 = lds32(a), w1 = lds32(a + 4);
    uint32_t sh = (uint32_t)i << 4;
    xy = __funnelshift_r(w0, w1, sh);
    z  = __funnelshift_r(w1, w1, sh);
}

__device__ __noinline__ float radial_value(float d, float f) {
    float arg = rbf(d * f);
    float sn  = rbf(sinf(arg));
    float rb  = rbf(__fdiv_rn(sn, d));
    float c   = rbf(cosf(rbf(__fdiv_rn(rbf(d * 3.14159265358979323846f), 5.0f))));
    float fc  = rbf(0.5f * rbf(c + 1.0f));
    return rb * fc;
}

__global__ void __launch_bounds__(NT, 1)
painn_kernel(const Params p, const __grid_constant__ CUtensorMap tmF, const __grid_constant__ CUtensorMap tmFs) {
    extern __shared__ __align__(1024) uint8_t smem[];
    const uint32_t sb   = smem_u32(smem);
    const int tid  = threadIdx.x, lane = tid & 31, warp = __shfl_sync(0xffffffffu, tid >> 5, 0);
    const int cta  = blockIdx.x;
    const int g    = lane >> 2, t = lane & 3;
    int* binCnt = (int*)(smem + SM_BINCNT);
    int* binOff = (int*)(smem + SM_BINOFF);
    int* nCnt   = (int*)(smem + SM_NCNT);
    uint32_t* nInfo = (uint32_t*)(smem + SM_NINFO);
    volatile int* ctrl = (volatile int*)(smem + SM_CTRL);
    const uint32_t bar_pos = sb + SM_BARS, bar_mlp = bar_pos + 8, bar_rec = bar_pos + 16;
    const uint32_t bar_full = bar_pos + 32, bar_empty = bar_full + NCWG * MAX_STAGE * 8;
    const uint32_t bar_hfull = bar_empty + NCWG * MAX_STAGE * 8, bar_hempty = bar_hfull + 16;

    const int node0  = cta * p.npc;
    const int nnodes = max(0, min(p.npc, p.N - node0));

    STAMP(0);
    if (tid == 32) {
        mbar_init(bar_pos, 1);
        asm volatile("fence.mbarrier_init.release.cluster;" ::: "memory");
        uint32_t pos_bytes = (uint32_t)(p.N * 6 + 15) & ~15u;
        mbar_expect_tx(bar_pos, pos_bytes);
        bulk_g2s(sb + P1_POS, p.pos, pos_bytes, bar_pos);
    } else if (tid == 64) {
        mbar_init(bar_rec, 1);
        mbar_init(bar_hfull, 4); mbar_init(bar_hfull + 8, 4); mbar_init(bar_hempty, 4); mbar_init(bar_hempty + 8, 4);
        asm volatile("prefetch.tensormap [%0];" ::"l"(&tmF) : "memory");
        asm volatile("prefetch.tensormap [%0];" ::"l"(&tmFs) : "memory");
    } else if (tid >= 96 && tid < 96 + NCWG * MAX_STAGE) {
        mbar_init(bar_full + 8 * (tid - 96), 2);
        mbar_init(bar_empty + 8 * (tid - 96), 4);
    }
    unsigned bar_seen = 0;
    if (tid == 0 || tid == 32) asm volatile("ld.relaxed.gpu.global.u32 %0, [%1];" : "=r"(bar_seen) : "l"(&g_bar[tid >> 5]) : "memory");
    const bool mlp_warp = warp >= 6;
    int4 s4[3], d4[3];
    const int q0 = cta * p.quads_per_cta;
    const int qend = min(q0 + p.quads_per_cta, p.E >> 2);
#pragma unroll
    for (int k = 0; k < 3; k++) {
        const int q = q0 + (k < 2 ? warp + 16 * k : 32 + warp) * 32 + lane;
        const bool ok = q < qend && (k < 2 || !mlp_warp);
        s4[k] = ok ? __ldg((const int4*)p.src + q) : make_int4(-1, -1, -1, -1);
        d4[k] = ok ? __ldg((const int4*)p.dst + q) : make_int4(0, 0, 0, 0);
    }
    for (int i = tid; i < nnodes * 32; i += NT) {
        const int r = i >> 5, b = (i >> 3) & 3, c = i & 7;
        cp_async16(sb + P1_SV + b * (MAX_NPC * 128) + r * 128 + ((c ^ (r & 7)) << 4), (const uint8_t*)p.sv + (size_t)node0 * 512 + i * 16);
    }
    for (int i = tid; i < 1024; i += NT) {
        const int m = i >> 9, k = (i >> 3) & 63, c = i & 7;
        cp_async16(sb + P1_W1 + m * 8192 + k * 128 + ((c ^ (k & 7)) << 4),
                   m == 0 ? (const uint8_t*)p.w1 + k * 128 + c * 16 : (const uint8_t*)p.w2 + k * 384 + 128 + c * 16);
    }
    asm volatile("cp.async.commit_group;" ::: "memory");
    if (tid < MAX_CTA) binCnt[tid] = 0;
    if (tid < MAX_NPC) nCnt[tid] = 0;
    if (tid < 16) ctrl[tid] = 0;
    if (tid >= 256 && tid < 256 + 240) {
        const int i = tid - 256;
        asm volatile("prefetch.global.L2 [%0];" ::"l"(i < 48 ? (const uint8_t*)p.wr + i * 128 : (const uint8_t*)p.w2 + (i - 48) * 128));
    }
    for (int i = P1_SEGA / 16 + tid; i < P1_SV / 16; i += NT) sts128(sb + i * 16, make_uint4(0u, 0u, 0u, 0u));
    for (int i = tid; i < 4 * (MAX_NPC - nnodes) * 8; i += NT)
        sts128(sb + P1_SV + (i / ((MAX_NPC - nnodes) * 8)) * (MAX_NPC * 128) + nnodes * 128 + (i % ((MAX_NPC - nnodes) * 8)) * 16, make_uint4(0u, 0u, 0u, 0u));
    __syncthreads();

    mbar_wait(bar_pos, 0);
    STAMP(1);
#pragma unroll
    for (int k = 0; k < 3; k++) {
        const int ss[4] = {s4[k].x, s4[k].y, s4[k].z, s4[k].w};
        const int dd[4] = {d4[k].x, d4[k].y, d4[k].z, d4[k].w};
        if (ss[0] >= 0) {
            uint32_t w0[4], w1[4], v0[4], v1[4], r0[4], r1[4], r2[4], bin[4], rank[4];
#pragma unroll
            for (int j = 0; j < 4; j++) {
                const uint32_t a = (sb + P1_POS + 6u * (uint32_t)ss[j]) & ~3u, c = (sb + P1_POS + 6u * (uint32_t)dd[j]) & ~3u;
                w0[j] = lds32(a); w1[j] = lds32(a + 4); v0[j] = lds32(c); v1[j] = lds32(c + 4);
            }
#pragma unroll
            for (int j = 0; j < 4; j++) {
                const uint32_t sh = (uint32_t)ss[j] << 4, dh = (uint32_t)dd[j] << 4;
                uint32_t rxy, rz;
                const uint32_t db = edge_dist(__funnelshift_r(w0[j], w1[j], sh), __funnelshift_r(w1[j], w1[j], sh),
                                              __funnelshift_r(v0[j], v1[j], dh), __funnelshift_r(v1[j], v1[j], dh), rxy, rz);
                float inv;
                asm("rcp.approx.ftz.f32 %0, %1;" : "=f"(inv) : "f"(__uint_as_float(db << 16)));
                bin[j] = __umulhi((uint32_t)dd[j], p.npc_magic);
                r0[j] = (uint32_t)ss[j] | ((db - D_MIN_BITS) << 16);
                r1[j] = pack_bf(bf_lo(rxy) * inv, bf_hi(rxy) * inv);
                r2[j] = __byte_perm(pack_bf(bf_lo(rz) * inv, 0.f), (uint32_t)dd[j] - bin[j] * (uint32_t)p.npc, 0x5410);
                rank[j] = db <= D_MAX_BITS ? (uint32_t)atomicAdd(&binCnt[bin[j]], 1) : 0xffffu;
            }
#pragma unroll
            for (int j = 0; j < 4; j++) {
                if (rank[j] < SEG_CAP) {
                    const uint32_t slot = bin[j] * SEG_CAP + rank[j];
                    asm volatile("st.shared.v2.u32 [%0], {%1, %2};" ::"r"(sb + P1_SEGA + slot * 8), "r"(r0[j]), "r"(r1[j]) : "memory");
                    sts32(sb + P1_SEGB + slot * 4, r2[j]);
                }
            }
        }
    }
    asm volatile("cp.async.wait_group 0;" ::: "memory");
    __syncthreads();
    STAMP(2);
    {
        constexpr int IT = (MAX_CTA + 31) / 32;
        uint2 ca[IT][2];
        uint32_t cb[IT][2];
        int cn[IT];
#pragma unroll
        for (int it = 0; it < IT; it++) {
            const int b = min(2 * warp + (lane >> 4) + 32 * it, MAX_CTA - 1);
            cn[it] = binCnt[b];
#pragma unroll
            for (int u = 0; u < 2; u++) {
                const int j = (lane & 15) + 16 * u;
                ca[it][u] = lds64(sb + P1_SEGA + (b * SEG_CAP + j) * 8);
                cb[it][u] = lds32(sb + P1_SEGB + (b * SEG_CAP + j) * 4);
            }
        }
#pragma unroll
        for (int it = 0; it < IT; it++) {
            const int b = 2 * warp + (lane >> 4) + 32 * it;
            if (b < p.ncta) {
                uint32_t* dstp = g_seg + ((size_t)cta * MAX_CTA + b) * (SEG_CAP * 3);
                const uint32_t tag = (uint32_t)min(cn[it], 511) << 23;
#pragma unroll
                for (int u = 0; u < 2; u++) {
                    const int j = (lane & 15) + 16 * u;
                    *(uint2*)(dstp + 2 * j) = ca[it][u];
                    dstp[2 * SEG_CAP + j] = cb[it][u] | tag;
                }
                for (int j = 32 + (lane & 15); j < ((min(cn[it], SEG_CAP) + 7) & ~7); j += 16) {
                    *(uint2*)(dstp + 2 * j) = lds64(sb + P1_SEGA + (b * SEG_CAP + j) * 8);
                    dstp[2 * SEG_CAP + j] = lds32(sb + P1_SEGB + (b * SEG_CAP + j) * 4);
                }
            }
        }
    }
    __syncthreads();
    STAMP(3);
    if (tid == 64) asm volatile("red.add.release.gpu.global.u32 [%0], 1;" ::"l"(&g_bar[0]) : "memory");

    if (!mlp_warp) {
        const int rows_per = (TAB_ROWS + 1 + p.ncta - 1) / p.ncta;
        for (int i = tid; i < rows_per * 8; i += 6 * 32) {
            int row = cta * rows_per + (i >> 3), kp = i & 7;
            if (row <= TAB_ROWS) {
                uint32_t val = 0;
                if (row < TAB_ROWS) {
                    float d = __uint_as_float((D_MIN_BITS + row) << 16);
                    uint32_t f2 = __ldg((const uint32_t*)p.freqs + kp);
                    val = pack_bf(radial_value(d, bf_lo(f2)), radial_value(d, bf_hi(f2)));
                }
                ((uint32_t*)g_table)[row * 8 + kp] = val;
            }
        }
    } else {
        const int mt = (warp - 6) >> 1, hf = (warp - 6) & 1;
        if (mt * 16 < nnodes) {
            STAMPT(10, 6 * 32);
            const int lrow = lane & 15, lch = lane >> 4;
            const uint32_t rowb = sb + P1_SV + (mt * 16 + lrow) * 128;
            const uint32_t key0 = lrow & 7;
            float acc[4][4];
#pragma unroll
            for (int i = 0; i < 4; i++) { acc[i][0] = acc[i][1] = acc[i][2] = acc[i][3] = 0.f; }
#pragma unroll
            for (int ks = 0; ks < 4; ks++) {
                uint32_t a[4];
                ldsm4(a, rowb + (((2 * ks + lch) ^ key0) << 4));
                const int kk = 16 * ks + lrow;
#pragma unroll
                for (int nt = 0; nt < 4; nt += 2) {
                    uint32_t b[4];
                    ldsm4t(b, sb + P1_W1 + kk * 128 + (((4 * hf + nt + lch) ^ (kk & 7)) << 4));
                    mma16816(acc[nt], a, b[0], b[1]);
                    mma16816(acc[nt + 1], a, b[2], b[3]);
                }
            }
            uint32_t hp[4][2];
#pragma unroll
            for (int i = 0; i < 4; i++) {
                float h[4];
#pragma unroll
                for (int q = 0; q < 4; q++) {
                    float x = rbf(acc[i][q]);
                    h[q] = __fdividef(x, 1.0f + __expf(-x));
                    acc[i][q] = 0.f;
                }
                hp[i][0] = pack_bf(h[0], h[1]);
                hp[i][1] = pack_bf(h[2], h[3]);
            }
            asm volatile("bar.sync %0, 64;" ::"r"(4 + mt) : "memory");
#pragma unroll
            for (int i = 0; i < 4; i += 2)
                stsm4(rowb + (((4 * hf + i + lch) ^ key0) << 4), hp[i][0], hp[i][1], hp[i + 1][0], hp[i + 1][1]);
            asm volatile("bar.sync %0, 64;" ::"r"(4 + mt) : "memory");
#pragma unroll
            for (int ks = 0; ks < 4; ks++) {
                uint32_t a[4];
                ldsm4(a, rowb + (((2 * ks + lch) ^ key0) << 4));
                const int kk = 16 * ks + lrow;
#pragma unroll
                for (int nt = 0; nt < 4; nt += 2) {
                    uint32_t b[4];
                    ldsm4t(b, sb + P1_W2 + kk * 128 + (((4 * hf + nt + lch) ^ (kk & 7)) << 4));
                    mma16816(acc[nt], a, b[0], b[1]);
                    mma16816(acc[nt + 1], a, b[2], b[3]);
                }
            }
            uint32_t vq[2][3][4];
            const uint32_t vb = sb + P1_SV + (mt * 16 + g) * 128 + 4 * t;
#pragma unroll
            for (int rh = 0; rh < 2; rh++)
#pragma unroll
                for (int a = 0; a < 3; a++)
#pragma unroll
                    for (int i = 0; i < 4; i++) vq[rh][a][i] = lds32(vb + (a + 1) * (MAX_NPC * 128) + rh * 1024 + (((4 * hf + i) ^ g) << 4));
#pragma unroll
            for (int rh = 0; rh < 2; rh++)
#pragma unroll
                for (int a = 0; a < 3; a++)
#pragma unroll
                    for (int i = 0; i < 4; i++)
                        sts32(vb + (a + 1) * (MAX_NPC * 128) + rh * 1024 + (((4 * hf + i) ^ g) << 4),
                              hmul2(pack_bf(acc[i][2 * rh], acc[i][2 * rh + 1]), vq[rh][a][i]));
            fence_async_smem();
            asm volatile("bar.sync %0, 64;" ::"r"(4 + mt) : "memory");
            {
                const int r4 = mt * 16 + 8 * hf + 4 * (lane >> 2), comp = lane & 3;
                if (lane < 8 && r4 < nnodes) tma_store3(&tmFs, comp, node0 + r4, sb + P1_SV + comp * (MAX_NPC * 128) + r4 * 128);
            }
            asm volatile("cp.async.bulk.commit_group;" ::: "memory");
        }
        STAMPT(11, 6 * 32);
    }
    if (tid == 0) {
        const unsigned target = (bar_seen / (unsigned)p.ncta + 1u) * (unsigned)p.ncta;
        unsigned cur;
        int spins = 0;
        do {
            asm volatile("ld.acquire.gpu.global.u32 %0, [%1];" : "=r"(cur) : "l"(&g_bar[0]) : "memory");
        } while ((int)(cur - target) < 0 && ++spins < (1 << 24));
    }
    STAMP(4);
    __syncthreads();
    STAMP(5);

    constexpr int SEG_IT = (MAX_CTA + 31) / 32;
    uint2 ra[SEG_IT][2];
    uint32_t rb[SEG_IT][2], rr[SEG_IT][2];
#pragma unroll
    for (int it = 0; it < SEG_IT; it++) {
        const int b = 2 * warp + (lane >> 4) + 32 * it;
        const uint32_t* sp = g_seg + ((size_t)b * MAX_CTA + cta) * (SEG_CAP * 3);
#pragma unroll
        for (int u = 0; u < 2; u++) {
            const int j = (lane & 15) + 16 * u;
            ra[it][u] = b < p.ncta ? __ldcg((const uint2*)(sp + 2 * j)) : make_uint2(0u, 0u);
            rb[it][u] = b < p.ncta ? __ldcg(sp + 2 * SEG_CAP + j) : 0u;
        }
    }
    uint2 xa[SEG_IT];
    uint32_t xb[SEG_IT];
#pragma unroll
    for (int it = 0; it < SEG_IT; it++) {
        const int cnt = rb[it][0] >> 23;
        const int b = 2 * warp + (lane >> 4) + 32 * it;
        const uint32_t* sp = g_seg + ((size_t)b * MAX_CTA + cta) * (SEG_CAP * 3);
        const bool has = 32 + (lane & 15) < cnt;
        xa[it] = has ? __ldcg((const uint2*)(sp + 2 * (32 + (lane & 15)))) : make_uint2(0u, 0u);
        xb[it] = has ? __ldcg(sp + 2 * SEG_CAP + 32 + (lane & 15)) : 0u;
    }
#pragma unroll
    for (int it = 0; it < SEG_IT; it++) {
        const int cnt = rb[it][0] >> 23;
        if (cnt > SEG_CAP) ctrl[1] = 1;
#pragma unroll
        for (int u = 0; u < 2; u++)
            rr[it][u] = (lane & 15) + 16 * u < cnt ? (uint32_t)atomicAdd(&nCnt[(rb[it][u] >> 16) & 0x7fu], 1) : 0xffffffffu;
    }
#pragma unroll
    for (int it = 0; it < SEG_IT; it++) {
        const int cnt = rb[it][0] >> 23;
        if (32 + (lane & 15) < cnt) {
            const int pos = atomicAdd((int*)&ctrl[8], 1);
            const uint32_t rank = (uint32_t)atomicAdd(&nCnt[(xb[it] >> 16) & 0x7fu], 1);
            if (pos < STAGE_CAP) sts128(sb + P1_REC + pos * 16, make_uint4(xa[it].x, xa[it].y, xb[it], rank));
        }
        if (cnt > 48) {
            const int b = 2 * warp + (lane >> 4) + 32 * it;
            const uint32_t* sp = g_seg + ((size_t)b * MAX_CTA + cta) * (SEG_CAP * 3);
            const int j = 48 + (lane & 15);
            if (j < min(cnt, SEG_CAP)) {
                const uint2 a = __ldcg((const uint2*)(sp + 2 * j));
                const uint32_t c = __ldcg(sp + 2 * SEG_CAP + j);
                const int pos = atomicAdd((int*)&ctrl[8], 1);
                const uint32_t rank = (uint32_t)atomicAdd(&nCnt[(c >> 16) & 0x7fu], 1);
                if (pos < STAGE_CAP) sts128(sb + P1_REC + pos * 16, make_uint4(a.x, a.y, c, rank));
            }
        }
    }
    STAMP(13);
    if (mlp_warp && lane < 8) {
        asm volatile("cp.async.bulk.wait_group 0;" ::: "memory");
        asm volatile("fence.proxy.async;" ::: "memory");
    }
    __syncthreads();
    if (tid == 64) asm volatile("red.add.release.gpu.global.u32 [%0], 1;" ::"l"(&g_bar[1]) : "memory");
    const int total = ctrl[8];
    if (tid == 0 && total > STAGE_CAP) ctrl[1] = 1;
    if (warp == 0) {
        int c[3], s = 0;
#pragma unroll
        for (int i = 0; i < 3; i++) {
            int b = lane * 3 + i;
            c[i] = b < nnodes ? max(16, (nCnt[b] + 15) & ~15) : 0;
            s += c[i];
        }
        int x = s;
#pragma unroll
        for (int o = 1; o < 32; o <<= 1) { int y = __shfl_up_sync(0xffffffffu, x, o); if (lane >= o) x += y; }
        const int slots = __shfl_sync(0xffffffffu, x, 31);
        int off = x - s, below = 0;
#pragma unroll
        for (int i = 0; i < 3; i++) {
            int b = lane * 3 + i;
            if (b < nnodes) {
                nInfo[b] = (uint32_t)off | ((uint32_t)c[i] << 16);
                below += (2 * off + c[i] < slots);
            }
            off += c[i];
        }
        below = __reduce_add_sync(0xffffffffu, below);
        if (lane == 0) {
            ctrl[2] = below;
            ctrl[4] = slots;
            if (slots > SLOT_CAP) ctrl[1] = 1;
        }
    }
    __syncthreads();
    if (ctrl[1] == 0) {
        uint16_t* sid = (uint16_t*)(smem + SM_SID);
        uint2* meta = (uint2*)(smem + SM_META);
#pragma unroll
        for (int it = 0; it < SEG_IT; it++)
#pragma unroll
            for (int u = 0; u < 2; u++)
                if (rr[it][u] != 0xffffffffu) rr[it][u] += lds32(sb + SM_NINFO + ((rb[it][u] >> 16) & 0x7fu) * 4) & 0xffffu;
#pragma unroll
        for (int it = 0; it < SEG_IT; it++)
#pragma unroll
            for (int u = 0; u < 2; u++)
                if (rr[it][u] != 0xffffffffu) {
                    sid[rr[it][u]]  = (uint16_t)((ra[it][u].x & 0xffffu) << 2);
                    meta[rr[it][u]] = make_uint2(((ra[it][u].x >> 16) << 5) | (rb[it][u] << 16), ra[it][u].y);
                }
        for (int i = tid; i < total; i += NT) {
            const uint4 r = lds128(sb + P1_REC + i * 16);
            const int pos = (int)(lds32(sb + SM_NINFO + ((r.z >> 16) & 0x7fu) * 4) & 0xffffu) + (int)r.w;
            sid[pos]  = (uint16_t)((r.x & 0xffffu) << 2);
            meta[pos] = make_uint2(((r.x >> 16) << 5) | (r.z << 16), r.y);
        }
        if (tid >= NT - 128 && tid - (NT - 128) < nnodes) {
            const int b = tid - (NT - 128), split = ctrl[2];
            const int mid = split < nnodes ? (int)(nInfo[split] & 0xffffu) : ctrl[4];
            const int st = b >= split;
            const int mine = (int)(nInfo[b] & 0xffffu) + (int)(nInfo[b] >> 16) - (st ? mid : 0);
            int lo = st ? 0 : split, hi = st ? split : nnodes;
            const int first = lo;
            while (lo < hi) {
                const int o = (lo + hi) >> 1;
                const int other = (int)(nInfo[o] & 0xffffu) + (int)(nInfo[o] >> 16) - (st ? 0 : mid);
                if (st ? (other <= mine) : (other < mine)) lo = o + 1; else hi = o;
            }
            const int rank = (st ? b - split : b) + lo - first;
            smem[SM_ORDER + rank] = (uint8_t)(b | (st << 7));
        }
        for (int i = tid; i < nnodes * 16; i += NT) {
            int nl = i >> 4, c = nCnt[nl];
            int j = (c & ~15) + (i & 15);
            if (j >= c && (j < 16 || (c & 15))) {
                int pos = (int)(nInfo[nl] & 0xffffu) + j;
                sid[pos]  = 0xffffu;
                meta[pos] = make_uint2((uint32_t)TAB_ZERO << 5, 0u);
            }
        }
    }
    if (tid == 32) {
        const unsigned target = (bar_seen / (unsigned)p.ncta + 1u) * (unsigned)p.ncta;
        unsigned cur;
        int spins = 0;
        do {
            asm volatile("ld.acquire.gpu.global.u32 %0, [%1];" : "=r"(cur) : "l"(&g_bar[1]) : "memory");
        } while ((int)(cur - target) < 0 && ++spins < (1 << 24));
    }
    fence_async_smem();
    __syncthreads();
    STAMP(6);

    if (__shfl_sync(0xffffffffu, ctrl[1], 0) != 0) {
        float* acc = (float*)(smem + P1_POS);
        for (int i = tid; i < nnodes * 256; i += NT) acc[i] = 0.f;
        __syncthreads();
        const uint16_t* posu = (const uint16_t*)p.pos;
        const uint32_t* tabg = (const uint32_t*)g_table;
        const uint32_t* Fw = (const uint32_t*)g_F;
        for (int e0 = warp * 32; e0 < p.E; e0 += NT) {
            int e = e0 + lane;
            int s = 0, d = 0;
            uint32_t db = 0xffff, rxy = 0, rz = 0;
            bool act = false;
            if (e < p.E) {
                s = p.src[e]; d = p.dst[e];
                if (d >= node0 && d < node0 + nnodes) {
                    uint32_t sxy = posu[s * 3] | ((uint32_t)posu[s * 3 + 1] << 16), sz = posu[s * 3 + 2];
                    uint32_t dxy = posu[d * 3] | ((uint32_t)posu[d * 3 + 1] << 16), dz = posu[d * 3 + 2];
                    db  = edge_dist(sxy, sz, dxy, dz, rxy, rz);
                    act = db <= D_MAX_BITS;
                }
            }
            unsigned m = __ballot_sync(0xffffffffu, act);
            while (m) {
                int l = __ffs(m) - 1;
                m &= m - 1;
                int es = __shfl_sync(0xffffffffu, s, l), ed = __shfl_sync(0xffffffffu, d, l);
                uint32_t edb = __shfl_sync(0xffffffffu, db, l), exy = __shfl_sync(0xffffffffu, rxy, l), ez = __shfl_sync(0xffffffffu, rz, l);
                float inv = 1.0f / __uint_as_float(edb << 16);
                float rh[3] = {rbf(bf_lo(exy) * inv), rbf(bf_hi(exy) * inv), rbf(bf_lo(ez) * inv)};
                const uint32_t* fr = Fw + (size_t)es * 128 + lane;
                const uint32_t fh = __ldcg(fr);
                const uint32_t q[3] = {__ldcg(fr + 32), __ldcg(fr + 64), __ldcg(fr + 96)};
                float ps0 = 0.f, ps1 = 0.f, pr0 = 0.f, pr1 = 0.f;
                for (int j2 = 0; j2 < 32; j2++) {
                    uint32_t hj = __shfl_sync(0xffffffffu, fh, j2);
                    uint32_t a0 = *(const uint32_t*)(p.w2 + (2 * j2) * 192 + 2 * lane), a1 = *(const uint32_t*)(p.w2 + (2 * j2 + 1) * 192 + 2 * lane);
                    uint32_t b0 = *(const uint32_t*)(p.w2 + (2 * j2) * 192 + 128 + 2 * lane), b1 = *(const uint32_t*)(p.w2 + (2 * j2 + 1) * 192 + 128 + 2 * lane);
                    ps0 += bf_lo(hj) * bf_lo(a0) + bf_hi(hj) * bf_lo(a1);
                    ps1 += bf_lo(hj) * bf_hi(a0) + bf_hi(hj) * bf_hi(a1);
                    pr0 += bf_lo(hj) * bf_lo(b0) + bf_hi(hj) * bf_lo(b1);
                    pr1 += bf_lo(hj) * bf_hi(b0) + bf_hi(hj) * bf_hi(b1);
                }
                float ws0 = 0.f, ws1 = 0.f, wv0 = 0.f, wv1 = 0.f, wr0 = 0.f, wr1 = 0.f;
                for (int k2 = 0; k2 < 8; k2++) {
                    uint32_t rk2 = __ldcg(tabg + (edb - D_MIN_BITS) * 8 + k2);
#pragma unroll
                    for (int h = 0; h < 2; h++) {
                        float rv = h ? bf_hi(rk2) : bf_lo(rk2);
                        const __nv_bfloat16* wrow = p.wr + (2 * k2 + h) * 192 + 2 * lane;
                        uint32_t a = *(const uint32_t*)wrow, b = *(const uint32_t*)(wrow + 64), c = *(const uint32_t*)(wrow + 128);
                        ws0 += rv * bf_lo(a); ws1 += rv * bf_hi(a);
                        wv0 += rv * bf_lo(b); wv1 += rv * bf_hi(b);
                        wr0 += rv * bf_lo(c); wr1 += rv * bf_hi(c);
                    }
                }
                float* a = acc + (ed - node0) * 256 + 2 * lane;
                atomicAdd(a, ps0 * ws0); atomicAdd(a + 1, ps1 * ws1);
#pragma unroll
                for (int c = 0; c < 3; c++) {
                    atomicAdd(a + 64 * (c + 1), wv0 * bf_lo(q[c]) + pr0 * wr0 * rh[c]);
                    atomicAdd(a + 64 * (c + 1) + 1, wv1 * bf_hi(q[c]) + pr1 * wr1 * rh[c]);
                }
            }
        }
        __syncthreads();
        for (int i = tid; i < nnodes * 128; i += NT) {
            uint32_t r = *(const uint32_t*)(p.sv + (size_t)node0 * 256 + 2 * i);
            *(uint32_t*)(p.out + (size_t)node0 * 256 + 2 * i) = pack_bf(bf_lo(r) + acc[2 * i], bf_hi(r) + acc[2 * i + 1]);
        }
        return;
    }

    const int slots = __reduce_max_sync(0xffffffffu, ctrl[4]);
    const int split = __reduce_max_sync(0xffffffffu, ctrl[2]);
    const int nstage = slots <= SLOT_CAP4 ? 6 : 5;
    const uint32_t ring = sb + (nstage == 6 ? SM_RING4 : SM_RING3);
    const int mid = __reduce_max_sync(0xffffffffu, split < nnodes ? (int)(nInfo[split] & 0xffffu) : slots) >> 4;
    const int wgi = warp >> 2, w = warp & 3;
    uint32_t wp[3][4];
    if (wgi < 3) {
        const uint16_t* wr = (const uint16_t*)p.wr + 16 * w + g;
#pragma unroll
        for (int ty = 0; ty < 3; ty++) {
#pragma unroll
            for (int i = 0; i < 4; i++) {
                const uint16_t* q = wr + (8 * (i >> 1) + 2 * t) * 192 + ty * 64 + 8 * (i & 1);
                wp[ty][i] = (uint32_t)__ldg(q) | ((uint32_t)__ldg(q + 192) << 16);
            }
        }
    }
    constexpr uint32_t EMPTY_OFF = NCWG * MAX_STAGE * 8;
    if (wgi == 3) {
        const int sc = w >> 1, r = w & 1;
        const int g0 = (sc == 0 ? 0 : mid) + r, g1 = sc == 0 ? mid : slots >> 4;
        const uint32_t ring_wg = ring + sc * nstage * STAGE_B, full_wg = bar_full + sc * MAX_STAGE * 8;
        const int e = lane >> 1, half = lane & 1;
        const uint32_t coef_off = e * 128 + ((half ^ (e & 7)) << 4);
        const int vrot = (e & 3) ^ ((e >> 1) & 3);
        const uint8_t* tab = (const uint8_t*)g_table + half * 16;
        int stage = r;
        uint32_t phase = 1;
        uint32_t ma = sb + SM_META + (g0 * 16 + e) * 8, ida = sb + SM_SID + g0 * 32;
        uint2 m = make_uint2(0u, 0u);
        uint4 tv = make_uint4(0u, 0u, 0u, 0u), ia = tv, ib = tv;
        if (g0 < g1) {
            m  = lds64(ma);
            ia = lds128(ida);
            ib = lds128(ida + 16);
            tv = __ldg((const uint4*)(tab + (m.x & 0xffffu)));
        }
        for (int left = (g1 - g0 + 1) >> 1; left > 0; left--) {
            const uint32_t st = ring_wg + stage * STAGE_B, fb = full_wg + stage * 8;
            uint4 o[4];
            {
                const uint32_t mul[4] = {0x3f803f80u, __byte_perm(m.y, 0, 0x1010), __byte_perm(m.y, 0, 0x3232), __byte_perm(m.x, 0, 0x3232)};
#pragma unroll
                for (int j = 0; j < 4; j++) {
                    const int v = j ^ vrot;
                    const uint32_t lo = (v & 1) ? mul[1] : mul[0], hi = (v & 1) ? mul[3] : mul[2];
                    const uint32_t mm = (v & 2) ? hi : lo;
                    o[j] = make_uint4(hmul2(tv.x, mm), hmul2(tv.y, mm), hmul2(tv.z, mm), hmul2(tv.w, mm));
                }
            }
            ma += 256; ida += 64;
            if (left > 1) m = lds64(ma);
            mbar_wait(fb + EMPTY_OFF, phase);
            uint32_t leader;
            asm volatile("{\n.reg .pred p;\nelect.sync _|p, 0xffffffff;\nselp.u32 %0, 1, 0, p;\n}" : "=r"(leader));
            if (leader) {
                const uint32_t id2[8] = {ia.x, ia.y, ia.z, ia.w, ib.x, ib.y, ib.z, ib.w};
                const uint32_t rows = st + 2048;
                if ((ib.w >> 16) != 0xffffu) {
                    mbar_expect_tx(fb, 16 * 512);
#pragma unroll
                    for (int i = 0; i < 8; i++) {
                        tma_load(rows + (2 * i) * 640, &tmF, (int)(id2[i] & 0xffffu), fb);
                        tma_load(rows + (2 * i + 1) * 640, &tmF, (int)(id2[i] >> 16), fb);
                    }
                } else {
                    int nv = 0;
#pragma unroll
                    for (int i = 0; i < 8; i++) nv += ((id2[i] & 0xffffu) != 0xffffu) + ((id2[i] >> 16) != 0xffffu);
                    mbar_expect_tx(fb, (uint32_t)nv * 512u);
#pragma unroll
                    for (int q = 0; q < 4; q++) {
                        if (4 * q + 4 <= nv) {
                            tma_load(rows + (4 * q) * 640, &tmF, (int)(id2[2 * q] & 0xffffu), fb);
                            tma_load(rows + (4 * q + 1) * 640, &tmF, (int)(id2[2 * q] >> 16), fb);
                            tma_load(rows + (4 * q + 2) * 640, &tmF, (int)(id2[2 * q + 1] & 0xffffu), fb);
                            tma_load(rows + (4 * q + 3) * 640, &tmF, (int)(id2[2 * q + 1] >> 16), fb);
                        } else {
                            if (4 * q < nv)     tma_load(rows + (4 * q) * 640, &tmF, (int)(id2[2 * q] & 0xffffu), fb);
                            if (4 * q + 1 < nv) tma_load(rows + (4 * q + 1) * 640, &tmF, (int)(id2[2 * q] >> 16), fb);
                            if (4 * q + 2 < nv) tma_load(rows + (4 * q + 2) * 640, &tmF, (int)(id2[2 * q + 1] & 0xffffu), fb);
                        }
                    }
                }
            }
            __syncwarp();
            if (left > 1) {
                ia = lds128(ida);
                ib = lds128(ida + 16);
                tv = __ldg((const uint4*)(tab + (m.x & 0xffffu)));
            }
            const uint32_t a = st + coef_off;
#pragma unroll
            for (int j = 0; j < 4; j++) sts128(a ^ ((j ^ vrot) << 5), o[j]);
            fence_async_smem();
            __syncwarp();
            mbar_arrive_elected(fb);
            stage += 2;
            if (stage >= nstage) { stage -= nstage; phase ^= 1; }
        }
    } else if (wgi == 2) {
        mbar_arrive_elected(bar_hempty);
        mbar_arrive_elected(bar_hempty + 8);
        uint32_t wA[2][4][4];
        {
            const uint16_t* w2 = (const uint16_t*)p.w2 + 16 * w + g;
#pragma unroll
            for (int mk = 0; mk < 8; mk++) {
#pragma unroll
                for (int i = 0; i < 4; i++) {
                    const uint16_t* q = w2 + (16 * (mk & 3) + 2 * t + 8 * (i >> 1)) * 192 + (mk >> 2) * 128 + 8 * (i & 1);
                    wA[mk >> 2][mk & 3][i] = (uint32_t)__ldg(q) | ((uint32_t)__ldg(q + 192) << 16);
                }
            }
        }
        const uint32_t lane_off = (uint32_t)node0 * 512u + t * 128 + w * 32 + (g & 1) * 16 + (g >> 1) * 4;
        uint32_t hpar = 0;
        float zs[8], zv[24], pvv[6], pr[4][2];
        auto start = [&](int ent) {
            const int c = ent >> 7;
            mbar_wait(bar_hfull + c * 8, (hpar >> c) & 1);
            hpar ^= 1u << c;
            const uint32_t dht = desc_lo(sb + SM_HT + c * 8192);
            wg_fence();
            wgmma_n16_first(zs, wA[0][0], dht);
            wgmma_n48_first(zv, wA[1][0], dht + 2);
#pragma unroll
            for (int ks = 1; ks < 4; ks++) {
                wgmma_n16(zs, wA[0][ks], dht + ks * 128);
                wgmma_n48(zv, wA[1][ks], dht + ks * 128 + 2);
            }
            wg_commit();
        };
        auto side = [&](int ent) {
            const int c = ent >> 7;
            const uint32_t pa = sb + SM_PV + c * 3072 + (tid & 127) * 8;
            const uint2 a0 = lds64(pa), a1 = lds64(pa + 1024), a2 = lds64(pa + 2048);
            pvv[0] = __uint_as_float(a0.x); pvv[1] = __uint_as_float(a0.y); pvv[2] = __uint_as_float(a1.x);
            pvv[3] = __uint_as_float(a1.y); pvv[4] = __uint_as_float(a2.x); pvv[5] = __uint_as_float(a2.y);
            __syncwarp();
            mbar_arrive_elected(bar_hempty + c * 8);
        };
        auto weigh = [&]() {
#pragma unroll
            for (int i = 0; i < 12; i++) asm volatile("" : "+r"(wp[i >> 2][i & 3]));
            pr[0][0] = bf_lo(wp[0][0]) * zs[0] + bf_hi(wp[0][0]) * zs[1] + bf_lo(wp[0][2]) * zs[4] + bf_hi(wp[0][2]) * zs[5];
            pr[0][1] = bf_lo(wp[0][1]) * zs[2] + bf_hi(wp[0][1]) * zs[3] + bf_lo(wp[0][3]) * zs[6] + bf_hi(wp[0][3]) * zs[7];
#pragma unroll
            for (int a = 0; a < 3; a++) {
                const float* y = zv + 8 * a;
                pr[a + 1][0] = pvv[2 * a] + bf_lo(wp[2][0]) * y[0] + bf_hi(wp[2][0]) * y[1] + bf_lo(wp[2][2]) * y[4] + bf_hi(wp[2][2]) * y[5];
                pr[a + 1][1] = pvv[2 * a + 1] + bf_lo(wp[2][1]) * y[2] + bf_hi(wp[2][1]) * y[3] + bf_lo(wp[2][3]) * y[6] + bf_hi(wp[2][3]) * y[7];
            }
            asm volatile("" : "+f"(pr[0][0]), "+f"(pr[0][1]), "+f"(pr[1][0]), "+f"(pr[1][1]), "+f"(pr[2][0]), "+f"(pr[2][1]), "+f"(pr[3][0]), "+f"(pr[3][1]) :: "memory");
        };
        auto finish = [&](int ent, uint32_t resid) {
            const bool hi2 = t & 2, hi1 = t & 1, odd = g & 1;
            float ka0 = hi2 ? pr[2][0] : pr[0][0], ka1 = hi2 ? pr[2][1] : pr[0][1];
            float kb0 = hi2 ? pr[3][0] : pr[1][0], kb1 = hi2 ? pr[3][1] : pr[1][1];
            float sa0 = hi2 ? pr[0][0] : pr[2][0], sa1 = hi2 ? pr[0][1] : pr[2][1];
            float sb0 = hi2 ? pr[1][0] : pr[3][0], sb1 = hi2 ? pr[1][1] : pr[3][1];
            ka0 += __shfl_xor_sync(0xffffffffu, sa0, 2); ka1 += __shfl_xor_sync(0xffffffffu, sa1, 2);
            kb0 += __shfl_xor_sync(0xffffffffu, sb0, 2); kb1 += __shfl_xor_sync(0xffffffffu, sb1, 2);
            float k0 = hi1 ? kb0 : ka0, k1 = hi1 ? kb1 : ka1;
            float s0 = hi1 ? ka0 : kb0, s1 = hi1 ? ka1 : kb1;
            k0 += __shfl_xor_sync(0xffffffffu, s0, 1);
            k1 += __shfl_xor_sync(0xffffffffu, s1, 1);
            const float other = __shfl_xor_sync(0xffffffffu, odd ? k0 : k1, 4);
            const float lo = odd ? other : k0, hi = odd ? k1 : other;
            *(uint32_t*)((uint8_t*)p.out + (lane_off + (uint32_t)(ent & 127) * 512u)) = pack_bf(bf_lo(resid) + lo, bf_hi(resid) + hi);
        };
        auto entry = [&](int i) -> int { return __reduce_max_sync(0xffffffffu, (int)smem[SM_ORDER + i]); };
        auto load_resid = [&](int ent) -> uint32_t { return __ldg((const uint32_t*)((const uint8_t*)p.sv + (lane_off + (uint32_t)(ent & 127) * 512u))); };
        if (nnodes > 0) {
            int cur = entry(0), nxt = entry(1);
            uint32_t resid = load_resid(cur);
            start(cur);
#pragma unroll 1
            for (int i = 1; i < nnodes; i++) {
                wg_wait0();
                side(cur);
                weigh();
                start(nxt);
                finish(cur, resid);
                cur = nxt;
                resid = load_resid(cur);
                nxt = entry(i + 1);
            }
            wg_wait0();
            side(cur);
            weigh();
            finish(cur, resid);
        }
    } else {
        const int wg = wgi;
        uint32_t aoff[4];
        {
            const int e = (lane & 7) + 8 * (lane >> 4), ch = 2 * w + ((lane >> 3) & 1);
#pragma unroll
            for (int b = 0; b < 4; b++) aoff[b] = 2048 + e * 640 + b * 128 + ((ch ^ ((5 * e + b) & 7)) << 4);
        }
        const uint32_t stsm_a = sb + SM_HT + wg * 8192 + (16 * w + (lane & 15)) * 128 + (((lane >> 4) ^ (lane & 7)) << 4);
        const uint32_t pv_a = sb + SM_PV + wg * 3072 + (tid & 127) * 8;
        const uint32_t ring_wg = ring + wg * nstage * STAGE_B;
        const uint32_t full_wg = bar_full + wg * MAX_STAGE * 8;

        float ys[8], yv[24], dQ[3][8];
        uint32_t A0[4][4], A1[4][4];
#pragma unroll
        for (int i = 0; i < 24; i++) yv[i] = 0.f;
#pragma unroll
        for (int i = 0; i < 8; i++) { ys[i] = 0.f; dQ[0][i] = 0.f; dQ[1][i] = 0.f; dQ[2][i] = 0.f; }
        int left = wg == 0 ? mid : (slots >> 4) - mid;
        int fstage = 0;
        uint32_t fphase = 0, fst = ring_wg, fbar = full_wg, hphase = 0;
        uint32_t ninfo_a = sb + SM_NINFO + (wg == 0 ? 0 : split) * 4;
        int gi = 0, G = __reduce_max_sync(0xffffffffu, (int)(lds32(ninfo_a) >> 20));

        auto fetch = [&](uint32_t (&A)[4][4], uint32_t& bd, uint32_t& eb) {
            mbar_wait(fbar, fphase);
#pragma unroll
            for (int b = 0; b < 4; b++) ldsm4t(A[b], fst + aoff[b]);
            bd = desc_lo(fst);
            eb = fbar + EMPTY_OFF;
            fst += STAGE_B; fbar += 8;
            if (++fstage == nstage) { fstage = 0; fphase ^= 1; fst = ring_wg; fbar = full_wg; }
        };
        auto step = [&](uint32_t (&Ac)[4][4], uint32_t bdc, uint32_t ebc, uint32_t (&An)[4][4], uint32_t& bdn, uint32_t& ebn) {
            wg_fence();
            wgmma_n64_p(ys, yv, Ac[0], bdc, gi);
            wgmma_n16_p(dQ[0], Ac[1], bdc, gi);
            wgmma_n16_p(dQ[1], Ac[2], bdc, gi);
            wgmma_n16_p(dQ[2], Ac[3], bdc, gi);
            wg_commit();
            if (--left > 0) fetch(An, bdn, ebn);
            const bool last = ++gi == G;
            uint32_t info_next = 0;
            if (last) { ninfo_a += 4; info_next = lds32(ninfo_a); }
            wg_wait0();
            mbar_arrive_elected(ebc);
            if (last) {
                mbar_wait(bar_hempty + wg * 8, hphase);
                hphase ^= 1;
                stsm4(stsm_a, pack_bf(ys[0], ys[1]), pack_bf(ys[2], ys[3]), pack_bf(ys[4], ys[5]), pack_bf(ys[6], ys[7]));
#pragma unroll
                for (int i = 0; i < 6; i += 2) {
                    stsm4(stsm_a ^ ((i + 2) << 4),
                          pack_bf(yv[4 * i], yv[4 * i + 1]), pack_bf(yv[4 * i + 2], yv[4 * i + 3]),
                          pack_bf(yv[4 * i + 4], yv[4 * i + 5]), pack_bf(yv[4 * i + 6], yv[4 * i + 7]));
                }
#pragma unroll
                for (int i = 0; i < 4; i++) asm volatile("" : "+r"(wp[1][i]));
#pragma unroll
                for (int a = 0; a < 3; a++) {
                    const float* q = dQ[a];
                    const float p0 = bf_lo(wp[1][0]) * q[0] + bf_hi(wp[1][0]) * q[1] + bf_lo(wp[1][2]) * q[4] + bf_hi(wp[1][2]) * q[5];
                    const float p1 = bf_lo(wp[1][1]) * q[2] + bf_hi(wp[1][1]) * q[3] + bf_lo(wp[1][3]) * q[6] + bf_hi(wp[1][3]) * q[7];
                    asm volatile("st.shared.v2.f32 [%0], {%1, %2};" ::"r"(pv_a + a * 1024), "f"(p0), "f"(p1) : "memory");
                }
                fence_async_smem();
                __syncwarp();
                mbar_arrive_elected(bar_hfull + wg * 8);
                G = __reduce_max_sync(0xffffffffu, (int)(info_next >> 20));
                gi = 0;
            }
        };
        if (left > 0) {
            uint32_t bd0, eb0, bd1 = 0, eb1 = 0;
            fetch(A0, bd0, eb0);
            while (true) {
                step(A0, bd0, eb0, A1, bd1, eb1);
                if (left <= 0) break;
                step(A1, bd1, eb1, A0, bd0, eb0);
                if (left <= 0) break;
            }
        }
    }
    STAMP(8);
}

typedef CUresult (*EncodeFn)(CUtensorMap*, CUtensorMapDataType, cuuint32_t, void*, const cuuint64_t*, const cuuint64_t*,
                             const cuuint32_t*, const cuuint32_t*, CUtensorMapInterleave, CUtensorMapSwizzle,
                             CUtensorMapL2promotion, CUtensorMapFloatOOBfill);

void make_map(EncodeFn enc, CUtensorMap* tm, const void* base, uint64_t lines, uint32_t box) {
    cuuint64_t gd[2] = {64, lines};
    cuuint64_t gs[1] = {128};
    cuuint32_t bd[2] = {64, box};
    cuuint32_t es[2] = {1, 1};
    enc(tm, CU_TENSOR_MAP_DATA_TYPE_BFLOAT16, 2, const_cast<void*>(base), gd, gs, bd, es, CU_TENSOR_MAP_INTERLEAVE_NONE,
        CU_TENSOR_MAP_SWIZZLE_128B, CU_TENSOR_MAP_L2_PROMOTION_L2_128B, CU_TENSOR_MAP_FLOAT_OOB_FILL_NONE);
}

void make_map3(EncodeFn enc, CUtensorMap* tm, const void* base, uint64_t nodes, uint32_t box) {
    cuuint64_t gd[3] = {64, 4, nodes};
    cuuint64_t gs[2] = {128, 512};
    cuuint32_t bd[3] = {64, 1, box};
    cuuint32_t es[3] = {1, 1, 1};
    enc(tm, CU_TENSOR_MAP_DATA_TYPE_BFLOAT16, 3, const_cast<void*>(base), gd, gs, bd, es, CU_TENSOR_MAP_INTERLEAVE_NONE,
        CU_TENSOR_MAP_SWIZZLE_128B, CU_TENSOR_MAP_L2_PROMOTION_L2_128B, CU_TENSOR_MAP_FLOAT_OOB_FILL_NONE);
}

}

extern "C" void kernel_launch(void* const* d_in, const int* in_sizes, int n_in, void* d_out, int out_size) {
    (void)n_in; (void)out_size;
    static int n_sm = 0;
    static EncodeFn enc = nullptr;
    static void* f_ptr = nullptr;
    if (n_sm == 0) {
        int dev = 0;
        cudaGetDevice(&dev);
        cudaDeviceGetAttribute(&n_sm, cudaDevAttrMultiProcessorCount, dev);
        cudaFuncSetAttribute(painn_kernel, cudaFuncAttributeMaxDynamicSharedMemorySize, SM_TOTAL);
        void* fn = nullptr;
        cudaDriverEntryPointQueryResult qr;
        cudaGetDriverEntryPoint("cuTensorMapEncodeTiled", &fn, cudaEnableDefault, &qr);
        enc = (EncodeFn)fn;
        cudaGetSymbolAddress(&f_ptr, g_F);
    }
    Params p;
    p.sv    = (const __nv_bfloat16*)d_in[0];
    p.pos   = (const __nv_bfloat16*)d_in[1];
    p.src   = (const int*)d_in[2];
    p.dst   = (const int*)d_in[3];
    p.freqs = (const __nv_bfloat16*)d_in[4];
    p.w1    = (const __nv_bfloat16*)d_in[5];
    p.w2    = (const __nv_bfloat16*)d_in[6];
    p.wr    = (const __nv_bfloat16*)d_in[7];
    p.out   = (__nv_bfloat16*)d_out;
    p.N = in_sizes[1] / 3;
    p.E = in_sizes[2];
    p.ncta = n_sm < MAX_CTA ? n_sm : MAX_CTA;
    p.npc = ((p.N + p.ncta - 1) / p.ncta + 3) & ~3;
    p.npc_magic = (uint32_t)(0x100000000ull / (uint32_t)p.npc) + 1u;
    p.quads_per_cta = ((p.E >> 2) + p.ncta - 1) / p.ncta;
    if (!enc || p.N > MAX_N || p.npc > MAX_NPC || (p.E & 3) || p.quads_per_cta > MAX_ROUNDS * 32) return;

    CUtensorMap tmF, tmFs;
    make_map(enc, &tmF, f_ptr, (uint64_t)p.N * 4, 4);
    make_map3(enc, &tmFs, f_ptr, (uint64_t)p.N, 4);

    cudaLaunchConfig_t cfg = {};
    cfg.gridDim = dim3(p.ncta);
    cfg.blockDim = dim3(NT);
    cfg.dynamicSmemBytes = SM_TOTAL;
    cfg.stream = cudaStreamPerThread;
    cudaLaunchAttribute attr[1];
    attr[0].id = cudaLaunchAttributeCooperative;
    attr[0].val.cooperative = 1;
    cfg.attrs = attr;
    cfg.numAttrs = 1;
    cudaLaunchKernelEx(&cfg, painn_kernel, p, tmF, tmFs);
}
```

```cpp
#include <cuda_runtime.h>
#include <cuda.h>
#include <cuda_bf16.h>
#include <stdint.h>

namespace {

constexpr int NT        = 512;
constexpr int NCWG      = 2;
constexpr int MAX_N     = 10240;
constexpr int MAX_CTA   = 136;
constexpr int MAX_NPC   = 80;
constexpr int MAX_ROUNDS = 38;
constexpr int REC_CAP   = MAX_ROUNDS * 128;
constexpr int SEG_CAP   = 64;
constexpr int SLOT_CAP  = 6144;
constexpr int MAX_STAGE = 6;
constexpr int STAGE_B   = 12288;

constexpr uint32_t D_MIN_BITS = 0x38D2;
constexpr uint32_t D_MAX_BITS = 0x409C;
constexpr int TAB_ROWS  = (int)(D_MAX_BITS - D_MIN_BITS) + 1;
constexpr int TAB_ZERO  = TAB_ROWS;
constexpr int TAB_BYTES = (TAB_ROWS + 1) * 32;

constexpr int SM_BINCNT = 0;
constexpr int SM_BINOFF = SM_BINCNT + MAX_CTA * 4;
constexpr int SM_NCNT   = SM_BINOFF + MAX_CTA * 4;
constexpr int SM_NINFO  = SM_NCNT + MAX_NPC * 4;
constexpr int SM_ORDER  = SM_NINFO + (MAX_NPC + 1) * 4;
constexpr int SM_CTRL   = SM_ORDER + MAX_NPC + 12;
constexpr int SM_BARS   = SM_CTRL + 64;
constexpr int SM_SID    = 2048 + 256;
constexpr int SM_META   = SM_SID + SLOT_CAP * 2;
constexpr int SM_TOTAL  = 232448;
constexpr int SM_HT     = (SM_TOTAL - 3 * 8192) / 1024 * 1024;
constexpr int SM_PV     = SM_HT + 2 * 8192;
constexpr int SM_RING4  = SM_HT - NCWG * 6 * STAGE_B;
constexpr int SM_RING3  = SM_HT - NCWG * 5 * STAGE_B;
constexpr int SLOT_CAP4 = (SM_RING4 - SM_META) / 8;
constexpr int P1_POS    = 3072;
constexpr int P1_SEGA   = P1_POS + 61440;
constexpr int P1_SEGB   = P1_SEGA + MAX_CTA * SEG_CAP * 8;
constexpr int P1_SV     = P1_SEGB + MAX_CTA * SEG_CAP * 4;
constexpr int P1_W1     = P1_SV + 4 * MAX_NPC * 128;
constexpr int P1_W2     = P1_W1 + 8192;
constexpr int P1_END    = P1_W2 + 8192;
constexpr int P1_REC    = P1_SEGA;
constexpr int STAGE_CAP = (P1_SV - P1_REC) / 16;
static_assert(SM_BARS + (8 + 2 * NCWG * MAX_STAGE) * 8 <= SM_SID, "misc block");
static_assert(SM_BARS + 256 <= P1_POS, "misc block");
static_assert(P1_END <= SM_TOTAL && P1_SV % 1024 == 0 && P1_REC % 16 == 0, "phase 1 overlay");
static_assert(SM_META + SLOT_CAP * 8 <= SM_RING3, "CSR");
static_assert(SM_RING4 % 1024 == 0 && SM_RING3 % 1024 == 0 && SM_HT % 1024 == 0, "alignment");
static_assert(SM_BARS % 8 == 0 && SM_META % 8 == 0 && SM_CTRL % 4 == 0, "alignment");
static_assert(MAX_N * 6 <= 61440, "pos");
static_assert(SM_SID + MAX_NPC * 1024 <= SM_TOTAL, "slow path accumulators");

__device__ __align__(1024) uint4 g_F[MAX_N * 32];
__device__ __align__(128) uint32_t g_seg[MAX_CTA * MAX_CTA * SEG_CAP * 3];
__device__ uint4    g_table[(TAB_BYTES + 15) / 16];
__device__ unsigned g_bar[2];
#define STAMP(k)
#define STAMPT(k, T)
#define ITS(k)

struct Params {
    const __nv_bfloat16* sv;
    const __nv_bfloat16* pos;
    const int*           src;
    const int*           dst;
    const __nv_bfloat16* freqs;
    const __nv_bfloat16* w1;
    const __nv_bfloat16* w2;
    const __nv_bfloat16* wr;
    __nv_bfloat16*       out;
    int N, E, ncta, npc;
    uint32_t npc_magic;
    int quads_per_cta;
};

__device__ __forceinline__ uint32_t smem_u32(const void* p) { return (uint32_t)__cvta_generic_to_shared(p); }
__device__ __forceinline__ float bf_lo(uint32_t v) { return __uint_as_float(v << 16); }
__device__ __forceinline__ float bf_hi(uint32_t v) { return __uint_as_float(v & 0xffff0000u); }
__device__ __forceinline__ float bf_u16(uint16_t v) { return __uint_as_float((uint32_t)v << 16); }
__device__ __forceinline__ uint32_t pack_bf(float lo, float hi) {
    uint32_t r;
    asm("cvt.rn.bf16x2.f32 %0, %1, %2;" : "=r"(r) : "f"(hi), "f"(lo));
    return r;
}
__device__ __forceinline__ float rbf(float x) { return bf_lo(pack_bf(x, 0.f)); }
__device__ __forceinline__ uint32_t hmul2(uint32_t a, uint32_t b) {
    uint32_t r;
    asm("mul.rn.bf16x2 %0, %1, %2;" : "=r"(r) : "r"(a), "r"(b));
    return r;
}
__device__ __forceinline__ uint32_t hsub2(uint32_t a, uint32_t b) {
    uint32_t r;
    asm("sub.rn.bf16x2 %0, %1, %2;" : "=r"(r) : "r"(a), "r"(b));
    return r;
}
__device__ __forceinline__ uint32_t lds32(uint32_t a) { uint32_t v; asm volatile("ld.shared.u32 %0, [%1];" : "=r"(v) : "r"(a)); return v; }
__device__ __forceinline__ uint32_t lds16(uint32_t a) { uint16_t v; asm volatile("ld.shared.u16 %0, [%1];" : "=h"(v) : "r"(a)); return v; }
__device__ __forceinline__ uint2 lds64(uint32_t a) { uint2 v; asm volatile("ld.shared.v2.u32 {%0,%1}, [%2];" : "=r"(v.x), "=r"(v.y) : "r"(a)); return v; }
__device__ __forceinline__ uint4 lds128(uint32_t a) { uint4 v; asm volatile("ld.shared.v4.u32 {%0,%1,%2,%3}, [%4];" : "=r"(v.x), "=r"(v.y), "=r"(v.z), "=r"(v.w) : "r"(a)); return v; }
__device__ __forceinline__ void sts32(uint32_t a, uint32_t v) { asm volatile("st.shared.u32 [%0], %1;" ::"r"(a), "r"(v) : "memory"); }
__device__ __forceinline__ void sts128(uint32_t a, uint4 v) { asm volatile("st.shared.v4.u32 [%0], {%1,%2,%3,%4};" ::"r"(a), "r"(v.x), "r"(v.y), "r"(v.z), "r"(v.w) : "memory"); }
__device__ __forceinline__ void mbar_init(uint32_t bar, int cnt) { asm volatile("mbarrier.init.shared::cta.b64 [%0], %1;" ::"r"(bar), "r"(cnt) : "memory"); }
__device__ __forceinline__ void mbar_expect_tx(uint32_t bar, uint32_t bytes) { asm volatile("mbarrier.arrive.expect_tx.shared::cta.b64 _, [%0], %1;" ::"r"(bar), "r"(bytes) : "memory"); }
__device__ __forceinline__ void mbar_arrive(uint32_t bar) { asm volatile("mbarrier.arrive.shared::cta.b64 _, [%0];" ::"r"(bar) : "memory"); }
__device__ __forceinline__ void mbar_wait(uint32_t bar, uint32_t parity) {
    asm volatile("{\n.reg .pred p;\n.reg .u32 c;\n"
                 "mbarrier.try_wait.parity.shared::cta.b64 p, [%0], %1;\n"
                 "@p bra DONE_%=;\n"
                 "mov.u32 c, 0;\n"
                 "LOOP_%=:\n"
                 "mbarrier.try_wait.parity.shared::cta.b64 p, [%0], %1;\n"
                 "@p bra DONE_%=;\n"
                 "add.u32 c, c, 1;\n"
                 "setp.lt.u32 p, c, 4194304;\n"
                 "@p bra LOOP_%=;\n"
                 "DONE_%=:\n}"
                 ::"r"(bar), "r"(parity) : "memory");
}
__device__ __forceinline__ void mbar_arrive_elected(uint32_t bar) {
    asm volatile("{\n.reg .pred p;\nelect.sync _|p, 0xffffffff;\n@p mbarrier.arrive.shared::cta.b64 _, [%0];\n}" ::"r"(bar) : "memory");
}
__device__ __forceinline__ void bulk_g2s(uint32_t dst, const void* src, uint32_t bytes, uint32_t bar) {
    asm volatile("cp.async.bulk.shared::cluster.global.mbarrier::complete_tx::bytes [%0], [%1], %2, [%3];"
                 ::"r"(dst), "l"(src), "r"(bytes), "r"(bar) : "memory");
}
__device__ __forceinline__ void cp_async16(uint32_t dst, const void* src) {
    asm volatile("cp.async.cg.shared.global [%0], [%1], 16;" ::"r"(dst), "l"(src) : "memory");
}
__device__ __forceinline__ void tma_load(uint32_t dst, const CUtensorMap* tm, int line, uint32_t bar) {
    asm volatile("cp.async.bulk.tensor.2d.shared::cluster.global.mbarrier::complete_tx::bytes [%0], [%1, {%3, %4}], [%2];"
                 ::"r"(dst), "l"(tm), "r"(bar), "r"(0), "r"(line) : "memory");
}
__device__ __forceinline__ void tma_load3(uint32_t dst, const CUtensorMap* tm, int comp, int node, uint32_t bar) {
    asm volatile("cp.async.bulk.tensor.3d.shared::cluster.global.mbarrier::complete_tx::bytes [%0], [%1, {%3, %4, %5}], [%2];"
                 ::"r"(dst), "l"(tm), "r"(bar), "r"(0), "r"(comp), "r"(node) : "memory");
}
__device__ __forceinline__ void tma_store3(const CUtensorMap* tm, int comp, int node, uint32_t src) {
    asm volatile("cp.async.bulk.tensor.3d.global.shared::cta.bulk_group [%0, {%2, %3, %4}], [%1];"
                 ::"l"(tm), "r"(src), "r"(0), "r"(comp), "r"(node) : "memory");
}
__device__ __forceinline__ void fence_async_smem() { asm volatile("fence.proxy.async.shared::cta;" ::: "memory"); }
__device__ __forceinline__ void named_barrier(int id) { asm volatile("bar.sync %0, 128;" ::"r"(id) : "memory"); }
__device__ __forceinline__ void ldsm4(uint32_t (&r)[4], uint32_t a) {
    asm volatile("ldmatrix.sync.aligned.m8n8.x4.shared.b16 {%0,%1,%2,%3}, [%4];" : "=r"(r[0]), "=r"(r[1]), "=r"(r[2]), "=r"(r[3]) : "r"(a) : "memory");
}
__device__ __forceinline__ void ldsm4t(uint32_t (&r)[4], uint32_t a) {
    asm volatile("ldmatrix.sync.aligned.m8n8.x4.trans.shared.b16 {%0,%1,%2,%3}, [%4];" : "=r"(r[0]), "=r"(r[1]), "=r"(r[2]), "=r"(r[3]) : "r"(a) : "memory");
}
__device__ __forceinline__ void stsm4(uint32_t a, uint32_t r0, uint32_t r1, uint32_t r2, uint32_t r3) {
    asm volatile("stmatrix.sync.aligned.m8n8.x4.shared.b16 [%0], {%1,%2,%3,%4};" ::"r"(a), "r"(r0), "r"(r1), "r"(r2), "r"(r3) : "memory");
}
__device__ __forceinline__ void mma16816(float (&c)[4], const uint32_t (&a)[4], uint32_t b0, uint32_t b1) {
    asm volatile("mma.sync.aligned.m16n8k16.row.col.f32.bf16.bf16.f32 {%0,%1,%2,%3}, {%4,%5,%6,%7}, {%8,%9}, {%0,%1,%2,%3};"
                 : "+f"(c[0]), "+f"(c[1]), "+f"(c[2]), "+f"(c[3])
                 : "r"(a[0]), "r"(a[1]), "r"(a[2]), "r"(a[3]), "r"(b0), "r"(b1));
}

__device__ __forceinline__ uint32_t desc_lo(uint32_t saddr) { return ((saddr & 0x3FFFF) >> 4) | (1u << 16); }
#define DESC_HI "0x40000040"
__device__ __forceinline__ void wg_fence() { asm volatile("wgmma.fence.sync.aligned;" ::: "memory"); }
__device__ __forceinline__ void wg_commit() { asm volatile("wgmma.commit_group.sync.aligned;" ::: "memory"); }
__device__ __forceinline__ void wg_wait0() { asm volatile("wgmma.wait_group.sync.aligned 0;" ::: "memory"); }
__device__ __forceinline__ void wg_wait1() { asm volatile("wgmma.wait_group.sync.aligned 1;" ::: "memory"); }

__device__ __forceinline__ void wgmma_n64_first(float (&d)[8], float (&e)[24], const uint32_t (&a)[4], uint32_t bdesc) {
    asm volatile("{\n.reg .b64 b;\nmov.b64 b, {%36, " DESC_HI "};\n"
                 "wgmma.mma_async.sync.aligned.m64n64k16.f32.bf16.bf16 {%0,%1,%2,%3,%4,%5,%6,%7,%8,%9,%10,%11,%12,%13,%14,%15,%16,%17,%18,%19,%20,%21,%22,%23,%24,%25,%26,%27,%28,%29,%30,%31}, {%32,%33,%34,%35}, b, 0, 1, 1, 1;\n}"
                 : "=f"(d[0]), "=f"(d[1]), "=f"(d[2]), "=f"(d[3]), "=f"(d[4]), "=f"(d[5]), "=f"(d[6]), "=f"(d[7]),
                   "=f"(e[0]), "=f"(e[1]), "=f"(e[2]), "=f"(e[3]), "=f"(e[4]), "=f"(e[5]), "=f"(e[6]), "=f"(e[7]), "=f"(e[8]), "=f"(e[9]), "=f"(e[10]), "=f"(e[11]), "=f"(e[12]), "=f"(e[13]), "=f"(e[14]), "=f"(e[15]), "=f"(e[16]), "=f"(e[17]), "=f"(e[18]), "=f"(e[19]), "=f"(e[20]), "=f"(e[21]), "=f"(e[22]), "=f"(e[23])
                 : "r"(a[0]), "r"(a[1]), "r"(a[2]), "r"(a[3]), "r"(bdesc));
}
__device__ __forceinline__ void wgmma_n64(float (&d)[8], float (&e)[24], const uint32_t (&a)[4], uint32_t bdesc) {
    asm volatile("{\n.reg .b64 b;\nmov.b64 b, {%36, " DESC_HI "};\n"
                 "wgmma.mma_async.sync.aligned.m64n64k16.f32.bf16.bf16 {%0,%1,%2,%3,%4,%5,%6,%7,%8,%9,%10,%11,%12,%13,%14,%15,%16,%17,%18,%19,%20,%21,%22,%23,%24,%25,%26,%27,%28,%29,%30,%31}, {%32,%33,%34,%35}, b, 1, 1, 1, 1;\n}"
                 : "+f"(d[0]), "+f"(d[1]), "+f"(d[2]), "+f"(d[3]), "+f"(d[4]), "+f"(d[5]), "+f"(d[6]), "+f"(d[7]),
                   "+f"(e[0]), "+f"(e[1]), "+f"(e[2]), "+f"(e[3]), "+f"(e[4]), "+f"(e[5]), "+f"(e[6]), "+f"(e[7]), "+f"(e[8]), "+f"(e[9]), "+f"(e[10]), "+f"(e[11]), "+f"(e[12]), "+f"(e[13]), "+f"(e[14]), "+f"(e[15]), "+f"(e[16]), "+f"(e[17]), "+f"(e[18]), "+f"(e[19]), "+f"(e[20]), "+f"(e[21]), "+f"(e[22]), "+f"(e[23])
                 : "r"(a[0]), "r"(a[1]), "r"(a[2]), "r"(a[3]), "r"(bdesc));
}
__device__ __forceinline__ void wgmma_n48_first(float (&e)[24], const uint32_t (&a)[4], uint32_t bdesc) {
    asm volatile("{\n.reg .b64 b;\nmov.b64 b, {%28, " DESC_HI "};\n"
                 "wgmma.mma_async.sync.aligned.m64n48k16.f32.bf16.bf16 {%0,%1,%2,%3,%4,%5,%6,%7,%8,%9,%10,%11,%12,%13,%14,%15,%16,%17,%18,%19,%20,%21,%22,%23}, {%24,%25,%26,%27}, b, 0, 1, 1, 1;\n}"
                 : "=f"(e[0]), "=f"(e[1]), "=f"(e[2]), "=f"(e[3]), "=f"(e[4]), "=f"(e[5]), "=f"(e[6]), "=f"(e[7]), "=f"(e[8]), "=f"(e[9]), "=f"(e[10]), "=f"(e[11]), "=f"(e[12]), "=f"(e[13]), "=f"(e[14]), "=f"(e[15]), "=f"(e[16]), "=f"(e[17]), "=f"(e[18]), "=f"(e[19]), "=f"(e[20]), "=f"(e[21]), "=f"(e[22]), "=f"(e[23])
                 : "r"(a[0]), "r"(a[1]), "r"(a[2]), "r"(a[3]), "r"(bdesc));
}
__device__ __forceinline__ void wgmma_n48(float (&e)[24], const uint32_t (&a)[4], uint32_t bdesc) {
    asm volatile("{\n.reg .b64 b;\nmov.b64 b, {%28, " DESC_HI "};\n"
                 "wgmma.mma_async.sync.aligned.m64n48k16.f32.bf16.bf16 {%0,%1,%2,%3,%4,%5,%6,%7,%8,%9,%10,%11,%12,%13,%14,%15,%16,%17,%18,%19,%20,%21,%22,%23}, {%24,%25,%26,%27}, b, 1, 1, 1, 1;\n}"
                 : "+f"(e[0]), "+f"(e[1]), "+f"(e[2]), "+f"(e[3]), "+f"(e[4]), "+f"(e[5]), "+f"(e[6]), "+f"(e[7]), "+f"(e[8]), "+f"(e[9]), "+f"(e[10]), "+f"(e[11]), "+f"(e[12]), "+f"(e[13]), "+f"(e[14]), "+f"(e[15]), "+f"(e[16]), "+f"(e[17]), "+f"(e[18]), "+f"(e[19]), "+f"(e[20]), "+f"(e[21]), "+f"(e[22]), "+f"(e[23])
                 : "r"(a[0]), "r"(a[1]), "r"(a[2]), "r"(a[3]), "r"(bdesc));
}
__device__ __forceinline__ void wgmma_n16_first(float (&d)[8], const uint32_t (&a)[4], uint32_t bdesc) {
    asm volatile("{\n.reg .b64 b;\nmov.b64 b, {%12, " DESC_HI "};\n"
                 "wgmma.mma_async.sync.aligned.m64n16k16.f32.bf16.bf16 {%0,%1,%2,%3,%4,%5,%6,%7}, {%8,%9,%10,%11}, b, 0, 1, 1, 1;\n}"
                 : "=f"(d[0]), "=f"(d[1]), "=f"(d[2]), "=f"(d[3]), "=f"(d[4]), "=f"(d[5]), "=f"(d[6]), "=f"(d[7])
                 : "r"(a[0]), "r"(a[1]), "r"(a[2]), "r"(a[3]), "r"(bdesc));
}
__device__ __forceinline__ void wgmma_n16(float (&d)[8], const uint32_t (&a)[4], uint32_t bdesc) {
    asm volatile("{\n.reg .b64 b;\nmov.b64 b, {%12, " DESC_HI "};\n"
                 "wgmma.mma_async.sync.aligned.m64n16k16.f32.bf16.bf16 {%0,%1,%2,%3,%4,%5,%6,%7}, {%8,%9,%10,%11}, b, 1, 1, 1, 1;\n}"
                 : "+f"(d[0]), "+f"(d[1]), "+f"(d[2]), "+f"(d[3]), "+f"(d[4]), "+f"(d[5]), "+f"(d[6]), "+f"(d[7])
                 : "r"(a[0]), "r"(a[1]), "r"(a[2]), "r"(a[3]), "r"(bdesc));
}

__device__ __forceinline__ void wgmma_n64_p(float (&d)[8], float (&e)[24], const uint32_t (&a)[4], uint32_t bdesc, int acc) {
    asm volatile("{\n.reg .pred p;\n.reg .b64 b;\nsetp.ne.b32 p, %37, 0;\nmov.b64 b, {%36, " DESC_HI "};\n"
                 "wgmma.mma_async.sync.aligned.m64n64k16.f32.bf16.bf16 {%0,%1,%2,%3,%4,%5,%6,%7,%8,%9,%10,%11,%12,%13,%14,%15,%16,%17,%18,%19,%20,%21,%22,%23,%24,%25,%26,%27,%28,%29,%30,%31}, {%32,%33,%34,%35}, b, p, 1, 1, 1;\n}"
                 : "+f"(d[0]), "+f"(d[1]), "+f"(d[2]), "+f"(d[3]), "+f"(d[4]), "+f"(d[5]), "+f"(d[6]), "+f"(d[7]),
                   "+f"(e[0]), "+f"(e[1]), "+f"(e[2]), "+f"(e[3]), "+f"(e[4]), "+f"(e[5]), "+f"(e[6]), "+f"(e[7]), "+f"(e[8]), "+f"(e[9]), "+f"(e[10]), "+f"(e[11]), "+f"(e[12]), "+f"(e[13]), "+f"(e[14]), "+f"(e[15]), "+f"(e[16]), "+f"(e[17]), "+f"(e[18]), "+f"(e[19]), "+f"(e[20]), "+f"(e[21]), "+f"(e[22]), "+f"(e[23])
                 : "r"(a[0]), "r"(a[1]), "r"(a[2]), "r"(a[3]), "r"(bdesc), "r"(acc));
}
__device__ __forceinline__ void wgmma_n16_p(float (&d)[8], const uint32_t (&a)[4], uint32_t bdesc, int acc) {
    asm volatile("{\n.reg .pred p;\n.reg .b64 b;\nsetp.ne.b32 p, %13, 0;\nmov.b64 b, {%12, " DESC_HI "};\n"
                 "wgmma.mma_async.sync.aligned.m64n16k16.f32.bf16.bf16 {%0,%1,%2,%3,%4,%5,%6,%7}, {%8,%9,%10,%11}, b, p, 1, 1, 1;\n}"
                 : "+f"(d[0]), "+f"(d[1]), "+f"(d[2]), "+f"(d[3]), "+f"(d[4]), "+f"(d[5]), "+f"(d[6]), "+f"(d[7])
                 : "r"(a[0]), "r"(a[1]), "r"(a[2]), "r"(a[3]), "r"(bdesc), "r"(acc));
}

__device__ __forceinline__ uint32_t edge_dist(uint32_t sxy, uint32_t sz, uint32_t dxy, uint32_t dz, uint32_t& rxy, uint32_t& rz) {
    rxy = hsub2(sxy, dxy);
    rz  = hsub2(sz, dz);
    uint32_t qxy = hmul2(rxy, rxy), qz = hmul2(rz, rz);
    float ss = rbf((bf_lo(qxy) + bf_hi(qxy)) + bf_lo(qz));
    float s2 = rbf(ss + 1e-8f);
    float d;
    asm("sqrt.approx.ftz.f32 %0, %1;" : "=f"(d) : "f"(s2));
    return pack_bf(d, 0.f) & 0xffffu;
}

__device__ __forceinline__ void load_pos(uint32_t sm_pos, int i, uint32_t& xy, uint32_t& z) {
    uint32_t a  = (sm_pos + 6u * (uint32_t)i) & ~3u;
    uint32_t w0 = lds32(a), w1 = lds32(a + 4);
    uint32_t sh = (uint32_t)i << 4;
    xy = __funnelshift_r(w0, w1, sh);
    z  = __funnelshift_r(w1, w1, sh);
}

__device__ __noinline__ float radial_value(float d, float f) {
    float arg = rbf(d * f);
    float sn  = rbf(sinf(arg));
    float rb  = rbf(__fdiv_rn(sn, d));
    float c   = rbf(cosf(rbf(__fdiv_rn(rbf(d * 3.14159265358979323846f), 5.0f))));
    float fc  = rbf(0.5f * rbf(c + 1.0f));
    return rb * fc;
}

__global__ void __launch_bounds__(NT, 1)
painn_kernel(const Params p, const __grid_constant__ CUtensorMap tmF, const __grid_constant__ CUtensorMap tmFs) {
    extern __shared__ __align__(1024) uint8_t smem[];
    const uint32_t sb   = smem_u32(smem);
    const int tid  = threadIdx.x, lane = tid & 31, warp = __shfl_sync(0xffffffffu, tid >> 5, 0);
    const int cta  = blockIdx.x;
    const int g    = lane >> 2, t = lane & 3;
    int* binCnt = (int*)(smem + SM_BINCNT);
    int* binOff = (int*)(smem + SM_BINOFF);
    int* nCnt   = (int*)(smem + SM_NCNT);
    uint32_t* nInfo = (uint32_t*)(smem + SM_NINFO);
    volatile int* ctrl = (volatile int*)(smem + SM_CTRL);
    const uint32_t bar_pos = sb + SM_BARS, bar_mlp = bar_pos + 8, bar_rec = bar_pos + 16;
    const uint32_t bar_full = bar_pos + 32, bar_empty = bar_full + NCWG * MAX_STAGE * 8;
    const uint32_t bar_hfull = bar_empty + NCWG * MAX_STAGE * 8, bar_hempty = bar_hfull + 16;

    const int node0  = cta * p.npc;
    const int nnodes = max(0, min(p.npc, p.N - node0));

    STAMP(0);
    if (tid == 32) {
        mbar_init(bar_pos, 1);
        asm volatile("fence.mbarrier_init.release.cluster;" ::: "memory");
        uint32_t pos_bytes = (uint32_t)(p.N * 6 + 15) & ~15u;
        mbar_expect_tx(bar_pos, pos_bytes);
        bulk_g2s(sb + P1_POS, p.pos, pos_bytes, bar_pos);
    } else if (tid == 64) {
        mbar_init(bar_rec, 1);
        mbar_init(bar_hfull, 4); mbar_init(bar_hfull + 8, 4); mbar_init(bar_hempty, 4); mbar_init(bar_hempty + 8, 4);
        asm volatile("prefetch.tensormap [%0];" ::"l"(&tmF) : "memory");
        asm volatile("prefetch.tensormap [%0];" ::"l"(&tmFs) : "memory");
    } else if (tid >= 96 && tid < 96 + NCWG * MAX_STAGE) {
        mbar_init(bar_full + 8 * (tid - 96), 2);
        mbar_init(bar_empty + 8 * (tid - 96), 4);
    }
    unsigned bar_seen = 0;
    if (tid == 0 || tid == 32) asm volatile("ld.relaxed.gpu.global.u32 %0, [%1];" : "=r"(bar_seen) : "l"(&g_bar[tid >> 5]) : "memory");
    const bool mlp_warp = warp >= 6;
    int4 s4[3], d4[3];
    const int q0 = cta * p.quads_per_cta;
    const int qend = min(q0 + p.quads_per_cta, p.E >> 2);
#pragma unroll
    for (int k = 0; k < 3; k++) {
        const int q = q0 + (k < 2 ? warp + 16 * k : 32 + warp) * 32 + lane;
        const bool ok = q < qend && (k < 2 || !mlp_warp);
        s4[k] = ok ? __ldg((const int4*)p.src + q) : make_int4(-1, -1, -1, -1);
        d4[k] = ok ? __ldg((const int4*)p.dst + q) : make_int4(0, 0, 0, 0);
    }
    if (tid < MAX_CTA) binCnt[tid] = 0;
    if (tid < MAX_NPC) nCnt[tid] = 0;
    if (tid < 16) ctrl[tid] = 0;
    if (tid >= 256 && tid < 256 + 240) {
        const int i = tid - 256;
        asm volatile("prefetch.global.L2 [%0];" ::"l"(i < 48 ? (const uint8_t*)p.wr + i * 128 : (const uint8_t*)p.w2 + (i - 48) * 128));
    }
    for (int i = P1_SEGA / 16 + tid; i < P1_SV / 16; i += NT) sts128(sb + i * 16, make_uint4(0u, 0u, 0u, 0u));
    for (int i = tid; i < 4 * (MAX_NPC - nnodes) * 8; i += NT)
        sts128(sb + P1_SV + (i / ((MAX_NPC - nnodes) * 8)) * (MAX_NPC * 128) + nnodes * 128 + (i % ((MAX_NPC - nnodes) * 8)) * 16, make_uint4(0u, 0u, 0u, 0u));
    __syncthreads();

    mbar_wait(bar_pos, 0);
    if (s4[0].x == 0x7fffffff) ctrl[15] = 1;
    for (int i = tid; i < nnodes * 32; i += NT) {
        const int r = i >> 5, b = (i >> 3) & 3, c = i & 7;
        cp_async16(sb + P1_SV + b * (MAX_NPC * 128) + r * 128 + ((c ^ (r & 7)) << 4), (const uint8_t*)p.sv + (size_t)node0 * 512 + i * 16);
    }
    for (int i = tid; i < 1024; i += NT) {
        const int m = i >> 9, k = (i >> 3) & 63, c = i & 7;
        cp_async16(sb + P1_W1 + m * 8192 + k * 128 + ((c ^ (k & 7)) << 4),
                   m == 0 ? (const uint8_t*)p.w1 + k * 128 + c * 16 : (const uint8_t*)p.w2 + k * 384 + 128 + c * 16);
    }
    asm volatile("cp.async.commit_group;" ::: "memory");
    STAMP(1);
#pragma unroll
    for (int k = 0; k < 3; k++) {
        const int ss[4] = {s4[k].x, s4[k].y, s4[k].z, s4[k].w};
        const int dd[4] = {d4[k].x, d4[k].y, d4[k].z, d4[k].w};
        if (ss[0] >= 0) {
            uint32_t w0[4], w1[4], v0[4], v1[4], r0[4], r1[4], r2[4], bin[4], rank[4];
#pragma unroll
            for (int j = 0; j < 4; j++) {
                const uint32_t a = (sb + P1_POS + 6u * (uint32_t)ss[j]) & ~3u, c = (sb + P1_POS + 6u * (uint32_t)dd[j]) & ~3u;
                w0[j] = lds32(a); w1[j] = lds32(a + 4); v0[j] = lds32(c); v1[j] = lds32(c + 4);
            }
#pragma unroll
            for (int j = 0; j < 4; j++) {
                const uint32_t sh = (uint32_t)ss[j] << 4, dh = (uint32_t)dd[j] << 4;
                uint32_t rxy, rz;
                const uint32_t db = edge_dist(__funnelshift_r(w0[j], w1[j], sh), __funnelshift_r(w1[j], w1[j], sh),
                                              __funnelshift_r(v0[j], v1[j], dh), __funnelshift_r(v1[j], v1[j], dh), rxy, rz);
                float inv;
                asm("rcp.approx.ftz.f32 %0, %1;" : "=f"(inv) : "f"(__uint_as_float(db << 16)));
                bin[j] = __umulhi((uint32_t)dd[j], p.npc_magic);
                r0[j] = (uint32_t)ss[j] | ((db - D_MIN_BITS) << 16);
                r1[j] = pack_bf(bf_lo(rxy) * inv, bf_hi(rxy) * inv);
                r2[j] = __byte_perm(pack_bf(bf_lo(rz) * inv, 0.f), (uint32_t)dd[j] - bin[j] * (uint32_t)p.npc, 0x5410);
                rank[j] = db <= D_MAX_BITS ? (uint32_t)atomicAdd(&binCnt[bin[j]], 1) : 0xffffu;
            }
#pragma unroll
            for (int j = 0; j < 4; j++) {
                if (rank[j] < SEG_CAP) {
                    const uint32_t slot = bin[j] * SEG_CAP + rank[j];
                    asm volatile("st.shared.v2.u32 [%0], {%1, %2};" ::"r"(sb + P1_SEGA + slot * 8), "r"(r0[j]), "r"(r1[j]) : "memory");
                    sts32(sb + P1_SEGB + slot * 4, r2[j]);
                }
            }
        }
    }
    __syncthreads();
    STAMP(2);
    {
        constexpr int IT = (MAX_CTA + 31) / 32;
        uint2 ca[IT][2];
        uint32_t cb[IT][2];
        int cn[IT];
#pragma unroll
        for (int it = 0; it < IT; it++) {
            const int b = min(2 * warp + (lane >> 4) + 32 * it, MAX_CTA - 1);
            cn[it] = binCnt[b];
#pragma unroll
            for (int u = 0; u < 2; u++) {
                const int j = (lane & 15) + 16 * u;
                ca[it][u] = lds64(sb + P1_SEGA + (b * SEG_CAP + j) * 8);
                cb[it][u] = lds32(sb + P1_SEGB + (b * SEG_CAP + j) * 4);
            }
        }
#pragma unroll
        for (int it = 0; it < IT; it++) {
            const int b = 2 * warp + (lane >> 4) + 32 * it;
            if (b < p.ncta) {
                uint32_t* dstp = g_seg + ((size_t)cta * MAX_CTA + b) * (SEG_CAP * 3);
                const uint32_t tag = (uint32_t)min(cn[it], 511) << 23;
#pragma unroll
                for (int u = 0; u < 2; u++) {
                    const int j = (lane & 15) + 16 * u;
                    *(uint2*)(dstp + 2 * j) = ca[it][u];
                    dstp[2 * SEG_CAP + j] = cb[it][u] | tag;
                }
                for (int j = 32 + (lane & 15); j < ((min(cn[it], SEG_CAP) + 7) & ~7); j += 16) {
                    *(uint2*)(dstp + 2 * j) = lds64(sb + P1_SEGA + (b * SEG_CAP + j) * 8);
                    dstp[2 * SEG_CAP + j] = lds32(sb + P1_SEGB + (b * SEG_CAP + j) * 4);
                }
            }
        }
    }
    STAMP(7);
    asm volatile("cp.async.wait_group 0;" ::: "memory");
    __syncthreads();
    STAMP(3);
    if (tid == 64) asm volatile("red.add.release.gpu.global.u32 [%0], 1;" ::"l"(&g_bar[0]) : "memory");

    if (!mlp_warp) {
        const int rows_per = (TAB_ROWS + 1 + p.ncta - 1) / p.ncta;
        for (int i = tid; i < rows_per * 8; i += 6 * 32) {
            int row = cta * rows_per + (i >> 3), kp = i & 7;
            if (row <= TAB_ROWS) {
                uint32_t val = 0;
                if (row < TAB_ROWS) {
                    float d = __uint_as_float((D_MIN_BITS + row) << 16);
                    uint32_t f2 = __ldg((const uint32_t*)p.freqs + kp);
                    val = pack_bf(radial_value(d, bf_lo(f2)), radial_value(d, bf_hi(f2)));
                }
                ((uint32_t*)g_table)[row * 8 + kp] = val;
            }
        }
    } else {
        const int mt = (warp - 6) >> 1, hf = (warp - 6) & 1;
        if (mt * 16 < nnodes) {
            STAMPT(10, 6 * 32);
            const int lrow = lane & 15, lch = lane >> 4;
            const uint32_t rowb = sb + P1_SV + (mt * 16 + lrow) * 128;
            const uint32_t key0 = lrow & 7;
            float acc[4][4];
#pragma unroll
            for (int i = 0; i < 4; i++) { acc[i][0] = acc[i][1] = acc[i][2] = acc[i][3] = 0.f; }
#pragma unroll
            for (int ks = 0; ks < 4; ks++) {
                uint32_t a[4];
                ldsm4(a, rowb + (((2 * ks + lch) ^ key0) << 4));
                const int kk = 16 * ks + lrow;
#pragma unroll
                for (int nt = 0; nt < 4; nt += 2) {
                    uint32_t b[4];
                    ldsm4t(b, sb + P1_W1 + kk * 128 + (((4 * hf + nt + lch) ^ (kk & 7)) << 4));
                    mma16816(acc[nt], a, b[0], b[1]);
                    mma16816(acc[nt + 1], a, b[2], b[3]);
                }
            }
            uint32_t hp[4][2];
#pragma unroll
            for (int i = 0; i < 4; i++) {
                float h[4];
#pragma unroll
                for (int q = 0; q < 4; q++) {
                    float x = rbf(acc[i][q]);
                    h[q] = __fdividef(x, 1.0f + __expf(-x));
                    acc[i][q] = 0.f;
                }
                hp[i][0] = pack_bf(h[0], h[1]);
                hp[i][1] = pack_bf(h[2], h[3]);
            }
            asm volatile("bar.sync %0, 64;" ::"r"(4 + mt) : "memory");
#pragma unroll
            for (int i = 0; i < 4; i += 2)
                stsm4(rowb + (((4 * hf + i + lch) ^ key0) << 4), hp[i][0], hp[i][1], hp[i + 1][0], hp[i + 1][1]);
            asm volatile("bar.sync %0, 64;" ::"r"(4 + mt) : "memory");
#pragma unroll
            for (int ks = 0; ks < 4; ks++) {
                uint32_t a[4];
                ldsm4(a, rowb + (((2 * ks + lch) ^ key0) << 4));
                const int kk = 16 * ks + lrow;
#pragma unroll
                for (int nt = 0; nt < 4; nt += 2) {
                    uint32_t b[4];
                    ldsm4t(b, sb + P1_W2 + kk * 128 + (((4 * hf + nt + lch) ^ (kk & 7)) << 4));
                    mma16816(acc[nt], a, b[0], b[1]);
                    mma16816(acc[nt + 1], a, b[2], b[3]);
                }
            }
            uint32_t vq[2][3][4];
            const uint32_t vb = sb + P1_SV + (mt * 16 + g) * 128 + 4 * t;
#pragma unroll
            for (int rh = 0; rh < 2; rh++)
#pragma unroll
                for (int a = 0; a < 3; a++)
#pragma unroll
                    for (int i = 0; i < 4; i++) vq[rh][a][i] = lds32(vb + (a + 1) * (MAX_NPC * 128) + rh * 1024 + (((4 * hf + i) ^ g) << 4));
#pragma unroll
            for (int rh = 0; rh < 2; rh++)
#pragma unroll
                for (int a = 0; a < 3; a++)
#pragma unroll
                    for (int i = 0; i < 4; i++)
                        sts32(vb + (a + 1) * (MAX_NPC * 128) + rh * 1024 + (((4 * hf + i) ^ g) << 4),
                              hmul2(pack_bf(acc[i][2 * rh], acc[i][2 * rh + 1]), vq[rh][a][i]));
            fence_async_smem();
            asm volatile("bar.sync %0, 64;" ::"r"(4 + mt) : "memory");
            {
                const int r4 = mt * 16 + 8 * hf + 4 * (lane >> 2), comp = lane & 3;
                if (lane < 8 && r4 < nnodes) tma_store3(&tmFs, comp, node0 + r4, sb + P1_SV + comp * (MAX_NPC * 128) + r4 * 128);
            }
            asm volatile("cp.async.bulk.commit_group;" ::: "memory");
        }
        STAMPT(11, 6 * 32);
    }
    if (tid == 0) {
        const unsigned target = (bar_seen / (unsigned)p.ncta + 1u) * (unsigned)p.ncta;
        unsigned cur;
        int spins = 0;
        do {
            asm volatile("ld.acquire.gpu.global.u32 %0, [%1];" : "=r"(cur) : "l"(&g_bar[0]) : "memory");
        } while ((int)(cur - target) < 0 && ++spins < (1 << 24));
    }
    STAMP(4);
    __syncthreads();
    STAMP(5);

    constexpr int SEG_IT = (MAX_CTA + 31) / 32;
    uint2 ra[SEG_IT][2];
    uint32_t rb[SEG_IT][2], rr[SEG_IT][2];
#pragma unroll
    for (int it = 0; it < SEG_IT; it++) {
        const int b = 2 * warp + (lane >> 4) + 32 * it;
        const uint32_t* sp = g_seg + ((size_t)b * MAX_CTA + cta) * (SEG_CAP * 3);
#pragma unroll
        for (int u = 0; u < 2; u++) {
            const int j = (lane & 15) + 16 * u;
            ra[it][u] = b < p.ncta ? __ldcg((const uint2*)(sp + 2 * j)) : make_uint2(0u, 0u);
            rb[it][u] = b < p.ncta ? __ldcg(sp + 2 * SEG_CAP + j) : 0u;
        }
    }
    if (rb[0][0] == 0x12345678u) ctrl[15] = 1;
    STAMP(9);
    uint2 xa[SEG_IT];
    uint32_t xb[SEG_IT];
#pragma unroll
    for (int it = 0; it < SEG_IT; it++) {
        const int cnt = rb[it][0] >> 23;
        const int b = 2 * warp + (lane >> 4) + 32 * it;
        const uint32_t* sp = g_seg + ((size_t)b * MAX_CTA + cta) * (SEG_CAP * 3);
        const bool has = 32 + (lane & 15) < cnt;
        xa[it] = has ? __ldcg((const uint2*)(sp + 2 * (32 + (lane & 15)))) : make_uint2(0u, 0u);
        xb[it] = has ? __ldcg(sp + 2 * SEG_CAP + 32 + (lane & 15)) : 0u;
    }
#pragma unroll
    for (int it = 0; it < SEG_IT; it++) {
        const int cnt = rb[it][0] >> 23;
        if (cnt > SEG_CAP) ctrl[1] = 1;
#pragma unroll
        for (int u = 0; u < 2; u++)
            rr[it][u] = (lane & 15) + 16 * u < cnt ? (uint32_t)atomicAdd(&nCnt[(rb[it][u] >> 16) & 0x7fu], 1) : 0xffffffffu;
    }
#pragma unroll
    for (int it = 0; it < SEG_IT; it++) {
        const int cnt = rb[it][0] >> 23;
        if (32 + (lane & 15) < cnt) {
            const int pos = atomicAdd((int*)&ctrl[8], 1);
            const uint32_t rank = (uint32_t)atomicAdd(&nCnt[(xb[it] >> 16) & 0x7fu], 1);
            if (pos < STAGE_CAP) sts128(sb + P1_REC + pos * 16, make_uint4(xa[it].x, xa[it].y, xb[it], rank));
        }
        if (cnt > 48) {
            const int b = 2 * warp + (lane >> 4) + 32 * it;
            const uint32_t* sp = g_seg + ((size_t)b * MAX_CTA + cta) * (SEG_CAP * 3);
            const int j = 48 + (lane & 15);
            if (j < min(cnt, SEG_CAP)) {
                const uint2 a = __ldcg((const uint2*)(sp + 2 * j));
                const uint32_t c = __ldcg(sp + 2 * SEG_CAP + j);
                const int pos = atomicAdd((int*)&ctrl[8], 1);
                const uint32_t rank = (uint32_t)atomicAdd(&nCnt[(c >> 16) & 0x7fu], 1);
                if (pos < STAGE_CAP) sts128(sb + P1_REC + pos * 16, make_uint4(a.x, a.y, c, rank));
            }
        }
    }
    STAMP(13);
    if (mlp_warp && lane < 8) {
        asm volatile("cp.async.bulk.wait_group 0;" ::: "memory");
        asm volatile("fence.proxy.async;" ::: "memory");
    }
    __syncthreads();
    if (tid == 64) asm volatile("red.add.release.gpu.global.u32 [%0], 1;" ::"l"(&g_bar[1]) : "memory");
    STAMP(14);
    const int total = ctrl[8];
    if (tid == 0 && total > STAGE_CAP) ctrl[1] = 1;
    if (warp == 0) {
        int c[3], s = 0;
#pragma unroll
        for (int i = 0; i < 3; i++) {
            int b = lane * 3 + i;
            c[i] = b < nnodes ? max(16, (nCnt[b] + 15) & ~15) : 0;
            s += c[i];
        }
        int x = s;
#pragma unroll
        for (int o = 1; o < 32; o <<= 1) { int y = __shfl_up_sync(0xffffffffu, x, o); if (lane >= o) x += y; }
        const int slots = __shfl_sync(0xffffffffu, x, 31);
        int off = x - s, below = 0;
#pragma unroll
        for (int i = 0; i < 3; i++) {
            int b = lane * 3 + i;
            if (b < nnodes) {
                nInfo[b] = (uint32_t)off | ((uint32_t)c[i] << 16);
                below += (2 * off + c[i] < slots);
            }
            off += c[i];
        }
        below = __reduce_add_sync(0xffffffffu, below);
        if (lane == 0) {
            ctrl[2] = below;
            ctrl[4] = slots;
            if (slots > SLOT_CAP) ctrl[1] = 1;
        }
    }
    __syncthreads();
    if (ctrl[1] == 0) {
        uint16_t* sid = (uint16_t*)(smem + SM_SID);
        uint2* meta = (uint2*)(smem + SM_META);
#pragma unroll
        for (int it = 0; it < SEG_IT; it++)
#pragma unroll
            for (int u = 0; u < 2; u++)
                if (rr[it][u] != 0xffffffffu) rr[it][u] += lds32(sb + SM_NINFO + ((rb[it][u] >> 16) & 0x7fu) * 4) & 0xffffu;
#pragma unroll
        for (int it = 0; it < SEG_IT; it++)
#pragma unroll
            for (int u = 0; u < 2; u++)
                if (rr[it][u] != 0xffffffffu) {
                    sid[rr[it][u]]  = (uint16_t)((ra[it][u].x & 0xffffu) << 2);
                    meta[rr[it][u]] = make_uint2(((ra[it][u].x >> 16) << 5) | (rb[it][u] << 16), ra[it][u].y);
                }
        for (int i = tid; i < total; i += NT) {
            const uint4 r = lds128(sb + P1_REC + i * 16);
            const int pos = (int)(lds32(sb + SM_NINFO + ((r.z >> 16) & 0x7fu) * 4) & 0xffffu) + (int)r.w;
            sid[pos]  = (uint16_t)((r.x & 0xffffu) << 2);
            meta[pos] = make_uint2(((r.x >> 16) << 5) | (r.z << 16), r.y);
        }
        if (tid >= NT - 128 && tid - (NT - 128) < nnodes) {
            const int b = tid - (NT - 128), split = ctrl[2];
            const int mid = split < nnodes ? (int)(nInfo[split] & 0xffffu) : ctrl[4];
            const int st = b >= split;
            const int mine = (int)(nInfo[b] & 0xffffu) + (int)(nInfo[b] >> 16) - (st ? mid : 0);
            int lo = st ? 0 : split, hi = st ? split : nnodes;
            const int first = lo;
            while (lo < hi) {
                const int o = (lo + hi) >> 1;
                const int other = (int)(nInfo[o] & 0xffffu) + (int)(nInfo[o] >> 16) - (st ? 0 : mid);
                if (st ? (other <= mine) : (other < mine)) lo = o + 1; else hi = o;
            }
            const int rank = (st ? b - split : b) + lo - first;
            smem[SM_ORDER + rank] = (uint8_t)(b | (st << 7));
        }
        for (int i = tid; i < nnodes * 16; i += NT) {
            int nl = i >> 4, c = nCnt[nl];
            int j = (c & ~15) + (i & 15);
            if (j >= c && (j < 16 || (c & 15))) {
                int pos = (int)(nInfo[nl] & 0xffffu) + j;
                sid[pos]  = 0xffffu;
                meta[pos] = make_uint2((uint32_t)TAB_ZERO << 5, 0u);
            }
        }
    }
    STAMP(15);
    if (tid == 32) {
        const unsigned target = (bar_seen / (unsigned)p.ncta + 1u) * (unsigned)p.ncta;
        unsigned cur;
        int spins = 0;
        do {
            asm volatile("ld.acquire.gpu.global.u32 %0, [%1];" : "=r"(cur) : "l"(&g_bar[1]) : "memory");
        } while ((int)(cur - target) < 0 && ++spins < (1 << 24));
    }
    fence_async_smem();
    __syncthreads();
    STAMP(6);

    if (__shfl_sync(0xffffffffu, ctrl[1], 0) != 0) {
        float* acc = (float*)(smem + P1_POS);
        for (int i = tid; i < nnodes * 256; i += NT) acc[i] = 0.f;
        __syncthreads();
        const uint16_t* posu = (const uint16_t*)p.pos;
        const uint32_t* tabg = (const uint32_t*)g_table;
        const uint32_t* Fw = (const uint32_t*)g_F;
        for (int e0 = warp * 32; e0 < p.E; e0 += NT) {
            int e = e0 + lane;
            int s = 0, d = 0;
            uint32_t db = 0xffff, rxy = 0, rz = 0;
            bool act = false;
            if (e < p.E) {
                s = p.src[e]; d = p.dst[e];
                if (d >= node0 && d < node0 + nnodes) {
                    uint32_t sxy = posu[s * 3] | ((uint32_t)posu[s * 3 + 1] << 16), sz = posu[s * 3 + 2];
                    uint32_t dxy = posu[d * 3] | ((uint32_t)posu[d * 3 + 1] << 16), dz = posu[d * 3 + 2];
                    db  = edge_dist(sxy, sz, dxy, dz, rxy, rz);
                    act = db <= D_MAX_BITS;
                }
            }
            unsigned m = __ballot_sync(0xffffffffu, act);
            while (m) {
                int l = __ffs(m) - 1;
                m &= m - 1;
                int es = __shfl_sync(0xffffffffu, s, l), ed = __shfl_sync(0xffffffffu, d, l);
                uint32_t edb = __shfl_sync(0xffffffffu, db, l), exy = __shfl_sync(0xffffffffu, rxy, l), ez = __shfl_sync(0xffffffffu, rz, l);
                float inv = 1.0f / __uint_as_float(edb << 16);
                float rh[3] = {rbf(bf_lo(exy) * inv), rbf(bf_hi(exy) * inv), rbf(bf_lo(ez) * inv)};
                const uint32_t* fr = Fw + (size_t)es * 128 + lane;
                const uint32_t fh = __ldcg(fr);
                const uint32_t q[3] = {__ldcg(fr + 32), __ldcg(fr + 64), __ldcg(fr + 96)};
                float ps0 = 0.f, ps1 = 0.f, pr0 = 0.f, pr1 = 0.f;
                for (int j2 = 0; j2 < 32; j2++) {
                    uint32_t hj = __shfl_sync(0xffffffffu, fh, j2);
                    uint32_t a0 = *(const uint32_t*)(p.w2 + (2 * j2) * 192 + 2 * lane), a1 = *(const uint32_t*)(p.w2 + (2 * j2 + 1) * 192 + 2 * lane);
                    uint32_t b0 = *(const uint32_t*)(p.w2 + (2 * j2) * 192 + 128 + 2 * lane), b1 = *(const uint32_t*)(p.w2 + (2 * j2 + 1) * 192 + 128 + 2 * lane);
                    ps0 += bf_lo(hj) * bf_lo(a0) + bf_hi(hj) * bf_lo(a1);
                    ps1 += bf_lo(hj) * bf_hi(a0) + bf_hi(hj) * bf_hi(a1);
                    pr0 += bf_lo(hj) * bf_lo(b0) + bf_hi(hj) * bf_lo(b1);
                    pr1 += bf_lo(hj) * bf_hi(b0) + bf_hi(hj) * bf_hi(b1);
                }
                float ws0 = 0.f, ws1 = 0.f, wv0 = 0.f, wv1 = 0.f, wr0 = 0.f, wr1 = 0.f;
                for (int k2 = 0; k2 < 8; k2++) {
                    uint32_t rk2 = __ldcg(tabg + (edb - D_MIN_BITS) * 8 + k2);
#pragma unroll
                    for (int h = 0; h < 2; h++) {
                        float rv = h ? bf_hi(rk2) : bf_lo(rk2);
                        const __nv_bfloat16* wrow = p.wr + (2 * k2 + h) * 192 + 2 * lane;
                        uint32_t a = *(const uint32_t*)wrow, b = *(const uint32_t*)(wrow + 64), c = *(const uint32_t*)(wrow + 128);
                        ws0 += rv * bf_lo(a); ws1 += rv * bf_hi(a);
                        wv0 += rv * bf_lo(b); wv1 += rv * bf_hi(b);
                        wr0 += rv * bf_lo(c); wr1 += rv * bf_hi(c);
                    }
                }
                float* a = acc + (ed - node0) * 256 + 2 * lane;
                atomicAdd(a, ps0 * ws0); atomicAdd(a + 1, ps1 * ws1);
#pragma unroll
                for (int c = 0; c < 3; c++) {
                    atomicAdd(a + 64 * (c + 1), wv0 * bf_lo(q[c]) + pr0 * wr0 * rh[c]);
                    atomicAdd(a + 64 * (c + 1) + 1, wv1 * bf_hi(q[c]) + pr1 * wr1 * rh[c]);
                }
            }
        }
        __syncthreads();
        for (int i = tid; i < nnodes * 128; i += NT) {
            uint32_t r = *(const uint32_t*)(p.sv + (size_t)node0 * 256 + 2 * i);
            *(uint32_t*)(p.out + (size_t)node0 * 256 + 2 * i) = pack_bf(bf_lo(r) + acc[2 * i], bf_hi(r) + acc[2 * i + 1]);
        }
        return;
    }

    const int slots = __reduce_max_sync(0xffffffffu, ctrl[4]);
    const int split = __reduce_max_sync(0xffffffffu, ctrl[2]);
    const int nstage = slots <= SLOT_CAP4 ? 6 : 5;
    const uint32_t ring = sb + (nstage == 6 ? SM_RING4 : SM_RING3);
    const int mid = __reduce_max_sync(0xffffffffu, split < nnodes ? (int)(nInfo[split] & 0xffffu) : slots) >> 4;
    const int wgi = warp >> 2, w = warp & 3;
    uint32_t wp[3][4];
    if (wgi < 3) {
        const uint16_t* wr = (const uint16_t*)p.wr + 16 * w + g;
#pragma unroll
        for (int ty = 0; ty < 3; ty++) {
#pragma unroll
            for (int i = 0; i < 4; i++) {
                const uint16_t* q = wr + (8 * (i >> 1) + 2 * t) * 192 + ty * 64 + 8 * (i & 1);
                wp[ty][i] = (uint32_t)__ldg(q) | ((uint32_t)__ldg(q + 192) << 16);
            }
        }
    }
    constexpr uint32_t EMPTY_OFF = NCWG * MAX_STAGE * 8;
    if (wgi == 3) {
        const int sc = w >> 1, r = w & 1;
        const int g0 = (sc == 0 ? 0 : mid) + r, g1 = sc == 0 ? mid : slots >> 4;
        const uint32_t ring_wg = ring + sc * nstage * STAGE_B, full_wg = bar_full + sc * MAX_STAGE * 8;
        const int e = lane >> 1, half = lane & 1;
        const uint32_t coef_off = e * 128 + ((half ^ (e & 7)) << 4);
        const int vrot = (e & 3) ^ ((e >> 1) & 3);
        const uint8_t* tab = (const uint8_t*)g_table + half * 16;
        int stage = r;
        uint32_t phase = 1;
        uint32_t ma = sb + SM_META + (g0 * 16 + e) * 8, ida = sb + SM_SID + g0 * 32;
        uint2 m = make_uint2(0u, 0u);
        uint4 tv = make_uint4(0u, 0u, 0u, 0u), ia = tv, ib = tv;
        if (g0 < g1) {
            m  = lds64(ma);
            ia = lds128(ida);
            ib = lds128(ida + 16);
            tv = __ldg((const uint4*)(tab + (m.x & 0xffffu)));
        }
        for (int left = (g1 - g0 + 1) >> 1; left > 0; left--) {
            const uint32_t st = ring_wg + stage * STAGE_B, fb = full_wg + stage * 8;
            uint4 o[4];
            {
                const uint32_t mul[4] = {0x3f803f80u, __byte_perm(m.y, 0, 0x1010), __byte_perm(m.y, 0, 0x3232), __byte_perm(m.x, 0, 0x3232)};
#pragma unroll
                for (int j = 0; j < 4; j++) {
                    const int v = j ^ vrot;
                    const uint32_t lo = (v & 1) ? mul[1] : mul[0], hi = (v & 1) ? mul[3] : mul[2];
                    const uint32_t mm = (v & 2) ? hi : lo;
                    o[j] = make_uint4(hmul2(tv.x, mm), hmul2(tv.y, mm), hmul2(tv.z, mm), hmul2(tv.w, mm));
                }
            }
            ma += 256; ida += 64;
            if (left > 1) m = lds64(ma);
            mbar_wait(fb + EMPTY_OFF, phase);
            uint32_t leader;
            asm volatile("{\n.reg .pred p;\nelect.sync _|p, 0xffffffff;\nselp.u32 %0, 1, 0, p;\n}" : "=r"(leader));
            if (leader) {
                const uint32_t id2[8] = {ia.x, ia.y, ia.z, ia.w, ib.x, ib.y, ib.z, ib.w};
                const uint32_t rows = st + 2048;
                if ((ib.w >> 16) != 0xffffu) {
                    mbar_expect_tx(fb, 16 * 512);
#pragma unroll
                    for (int i = 0; i < 8; i++) {
                        tma_load(rows + (2 * i) * 640, &tmF, (int)(id2[i] & 0xffffu), fb);
                        tma_load(rows + (2 * i + 1) * 640, &tmF, (int)(id2[i] >> 16), fb);
                    }
                } else {
                    int nv = 0;
#pragma unroll
                    for (int i = 0; i < 8; i++) nv += ((id2[i] & 0xffffu) != 0xffffu) + ((id2[i] >> 16) != 0xffffu);
                    mbar_expect_tx(fb, (uint32_t)nv * 512u);
#pragma unroll
                    for (int q = 0; q < 4; q++) {
                        if (4 * q + 4 <= nv) {
                            tma_load(rows + (4 * q) * 640, &tmF, (int)(id2[2 * q] & 0xffffu), fb);
                            tma_load(rows + (4 * q + 1) * 640, &tmF, (int)(id2[2 * q] >> 16), fb);
                            tma_load(rows + (4 * q + 2) * 640, &tmF, (int)(id2[2 * q + 1] & 0xffffu), fb);
                            tma_load(rows + (4 * q + 3) * 640, &tmF, (int)(id2[2 * q + 1] >> 16), fb);
                        } else {
                            if (4 * q < nv)     tma_load(rows + (4 * q) * 640, &tmF, (int)(id2[2 * q] & 0xffffu), fb);
                            if (4 * q + 1 < nv) tma_load(rows + (4 * q + 1) * 640, &tmF, (int)(id2[2 * q] >> 16), fb);
                            if (4 * q + 2 < nv) tma_load(rows + (4 * q + 2) * 640, &tmF, (int)(id2[2 * q + 1] & 0xffffu), fb);
                        }
                    }
                }
            }
            __syncwarp();
            if (left > 1) {
                ia = lds128(ida);
                ib = lds128(ida + 16);
                tv = __ldg((const uint4*)(tab + (m.x & 0xffffu)));
            }
            const uint32_t a = st + coef_off;
#pragma unroll
            for (int j = 0; j < 4; j++) sts128(a ^ ((j ^ vrot) << 5), o[j]);
            fence_async_smem();
            __syncwarp();
            mbar_arrive_elected(fb);
            stage += 2;
            if (stage >= nstage) { stage -= nstage; phase ^= 1; }
        }
    } else if (wgi == 2) {
        mbar_arrive_elected(bar_hempty);
        mbar_arrive_elected(bar_hempty + 8);
        uint32_t wA[2][4][4];
        {
            const uint16_t* w2 = (const uint16_t*)p.w2 + 16 * w + g;
#pragma unroll
            for (int mk = 0; mk < 8; mk++) {
#pragma unroll
                for (int i = 0; i < 4; i++) {
                    const uint16_t* q = w2 + (16 * (mk & 3) + 2 * t + 8 * (i >> 1)) * 192 + (mk >> 2) * 128 + 8 * (i & 1);
                    wA[mk >> 2][mk & 3][i] = (uint32_t)__ldg(q) | ((uint32_t)__ldg(q + 192) << 16);
                }
            }
        }
        const uint32_t lane_off = (uint32_t)node0 * 512u + t * 128 + w * 32 + (g & 1) * 16 + (g >> 1) * 4;
        uint32_t hpar = 0;
        float zs[8], zv[24], pvv[6], pr[4][2];
        auto start = [&](int ent) {
            const int c = ent >> 7;
            mbar_wait(bar_hfull + c * 8, (hpar >> c) & 1);
            hpar ^= 1u << c;
            const uint32_t dht = desc_lo(sb + SM_HT + c * 8192);
            wg_fence();
            wgmma_n16_first(zs, wA[0][0], dht);
            wgmma_n48_first(zv, wA[1][0], dht + 2);
#pragma unroll
            for (int ks = 1; ks < 4; ks++) {
                wgmma_n16(zs, wA[0][ks], dht + ks * 128);
                wgmma_n48(zv, wA[1][ks], dht + ks * 128 + 2);
            }
            wg_commit();
        };
        auto side = [&](int ent) {
            const int c = ent >> 7;
            const uint32_t pa = sb + SM_PV + c * 3072 + (tid & 127) * 4;
            const uint32_t a0 = lds32(pa), a1 = lds32(pa + 512), a2 = lds32(pa + 1024);
            pvv[0] = bf_lo(a0); pvv[1] = bf_hi(a0); pvv[2] = bf_lo(a1); pvv[3] = bf_hi(a1); pvv[4] = bf_lo(a2); pvv[5] = bf_hi(a2);
            __syncwarp();
            mbar_arrive_elected(bar_hempty + c * 8);
        };
        auto weigh = [&]() {
#pragma unroll
            for (int i = 0; i < 12; i++) asm volatile("" : "+r"(wp[i >> 2][i & 3]));
            pr[0][0] = bf_lo(wp[0][0]) * zs[0] + bf_hi(wp[0][0]) * zs[1] + bf_lo(wp[0][2]) * zs[4] + bf_hi(wp[0][2]) * zs[5];
            pr[0][1] = bf_lo(wp[0][1]) * zs[2] + bf_hi(wp[0][1]) * zs[3] + bf_lo(wp[0][3]) * zs[6] + bf_hi(wp[0][3]) * zs[7];
#pragma unroll
            for (int a = 0; a < 3; a++) {
                const float* y = zv + 8 * a;
                pr[a + 1][0] = pvv[2 * a] + bf_lo(wp[2][0]) * y[0] + bf_hi(wp[2][0]) * y[1] + bf_lo(wp[2][2]) * y[4] + bf_hi(wp[2][2]) * y[5];
                pr[a + 1][1] = pvv[2 * a + 1] + bf_lo(wp[2][1]) * y[2] + bf_hi(wp[2][1]) * y[3] + bf_lo(wp[2][3]) * y[6] + bf_hi(wp[2][3]) * y[7];
            }
            asm volatile("" : "+f"(pr[0][0]), "+f"(pr[0][1]), "+f"(pr[1][0]), "+f"(pr[1][1]), "+f"(pr[2][0]), "+f"(pr[2][1]), "+f"(pr[3][0]), "+f"(pr[3][1]) :: "memory");
        };
        auto finish = [&](int ent, uint32_t resid) {
            const bool hi2 = t & 2, hi1 = t & 1, odd = g & 1;
            float ka0 = hi2 ? pr[2][0] : pr[0][0], ka1 = hi2 ? pr[2][1] : pr[0][1];
            float kb0 = hi2 ? pr[3][0] : pr[1][0], kb1 = hi2 ? pr[3][1] : pr[1][1];
            float sa0 = hi2 ? pr[0][0] : pr[2][0], sa1 = hi2 ? pr[0][1] : pr[2][1];
            float sb0 = hi2 ? pr[1][0] : pr[3][0], sb1 = hi2 ? pr[1][1] : pr[3][1];
            ka0 += __shfl_xor_sync(0xffffffffu, sa0, 2); ka1 += __shfl_xor_sync(0xffffffffu, sa1, 2);
            kb0 += __shfl_xor_sync(0xffffffffu, sb0, 2); kb1 += __shfl_xor_sync(0xffffffffu, sb1, 2);
            float k0 = hi1 ? kb0 : ka0, k1 = hi1 ? kb1 : ka1;
            float s0 = hi1 ? ka0 : kb0, s1 = hi1 ? ka1 : kb1;
            k0 += __shfl_xor_sync(0xffffffffu, s0, 1);
            k1 += __shfl_xor_sync(0xffffffffu, s1, 1);
            const float other = __shfl_xor_sync(0xffffffffu, odd ? k0 : k1, 4);
            const float lo = odd ? other : k0, hi = odd ? k1 : other;
            *(uint32_t*)((uint8_t*)p.out + (lane_off + (uint32_t)(ent & 127) * 512u)) = pack_bf(bf_lo(resid) + lo, bf_hi(resid) + hi);
        };
        auto entry = [&](int i) -> int { return __reduce_max_sync(0xffffffffu, (int)smem[SM_ORDER + i]); };
        auto load_resid = [&](int ent) -> uint32_t { return __ldg((const uint32_t*)((const uint8_t*)p.sv + (lane_off + (uint32_t)(ent & 127) * 512u))); };
        if (nnodes > 0) {
            int cur = entry(0), nxt = entry(1);
            uint32_t resid = load_resid(cur);
            start(cur);
#pragma unroll 1
            for (int i = 1; i < nnodes; i++) {
                wg_wait0();
                side(cur);
                weigh();
                start(nxt);
                finish(cur, resid);
                cur = nxt;
                resid = load_resid(cur);
                nxt = entry(i + 1);
            }
            wg_wait0();
            side(cur);
            weigh();
            finish(cur, resid);
        }
    } else {
        const int wg = wgi;
        uint32_t aoff[4];
        {
            const int e = (lane & 7) + 8 * (lane >> 4), ch = 2 * w + ((lane >> 3) & 1);
#pragma unroll
            for (int b = 0; b < 4; b++) aoff[b] = 2048 + e * 640 + b * 128 + ((ch ^ ((5 * e + b) & 7)) << 4);
        }
        const uint32_t stsm_a = sb + SM_HT + wg * 8192 + (16 * w + (lane & 15)) * 128 + (((lane >> 4) ^ (lane & 7)) << 4);
        const uint32_t pv_a = sb + SM_PV + wg * 3072 + (tid & 127) * 4;
        const uint32_t ring_wg = ring + wg * nstage * STAGE_B;
        const uint32_t full_wg = bar_full + wg * MAX_STAGE * 8;

        float ys[8], yv[24], dQ[3][8];
        uint32_t A0[4][4], A1[4][4];
#pragma unroll
        for (int i = 0; i < 24; i++) yv[i] = 0.f;
#pragma unroll
        for (int i = 0; i < 8; i++) { ys[i] = 0.f; dQ[0][i] = 0.f; dQ[1][i] = 0.f; dQ[2][i] = 0.f; }
        int left = wg == 0 ? mid : (slots >> 4) - mid;
        int fstage = 0;
        uint32_t fphase = 0, fst = ring_wg, fbar = full_wg, hphase = 0;
        uint32_t ninfo_a = sb + SM_NINFO + (wg == 0 ? 0 : split) * 4;
        int gi = 0, G = __reduce_max_sync(0xffffffffu, (int)(lds32(ninfo_a) >> 20));

        auto fetch = [&](uint32_t (&A)[4][4], uint32_t& bd, uint32_t& eb) {
            mbar_wait(fbar, fphase);
#pragma unroll
            for (int b = 0; b < 4; b++) ldsm4t(A[b], fst + aoff[b]);
            bd = desc_lo(fst);
            eb = fbar + EMPTY_OFF;
            fst += STAGE_B; fbar += 8;
            if (++fstage == nstage) { fstage = 0; fphase ^= 1; fst = ring_wg; fbar = full_wg; }
        };
        auto step = [&](uint32_t (&Ac)[4][4], uint32_t bdc, uint32_t ebc, uint32_t (&An)[4][4], uint32_t& bdn, uint32_t& ebn) {
            wg_fence();
            wgmma_n64_p(ys, yv, Ac[0], bdc, gi);
            wgmma_n16_p(dQ[0], Ac[1], bdc, gi);
            wgmma_n16_p(dQ[1], Ac[2], bdc, gi);
            wgmma_n16_p(dQ[2], Ac[3], bdc, gi);
            wg_commit();
            if (--left > 0) fetch(An, bdn, ebn);
            const bool last = ++gi == G;
            uint32_t info_next = 0;
            if (last) { ninfo_a += 4; info_next = lds32(ninfo_a); }
            wg_wait0();
            mbar_arrive_elected(ebc);
            if (last) {
                mbar_wait(bar_hempty + wg * 8, hphase);
                hphase ^= 1;
                stsm4(stsm_a, pack_bf(ys[0], ys[1]), pack_bf(ys[2], ys[3]), pack_bf(ys[4], ys[5]), pack_bf(ys[6], ys[7]));
#pragma unroll
                for (int i = 0; i < 6; i += 2) {
                    stsm4(stsm_a ^ ((i + 2) << 4),
                          pack_bf(yv[4 * i], yv[4 * i + 1]), pack_bf(yv[4 * i + 2], yv[4 * i + 3]),
                          pack_bf(yv[4 * i + 4], yv[4 * i + 5]), pack_bf(yv[4 * i + 6], yv[4 * i + 7]));
                }
#pragma unroll
                for (int i = 0; i < 4; i++) asm volatile("" : "+r"(wp[1][i]));
#pragma unroll
                for (int a = 0; a < 3; a++) {
                    const float* q = dQ[a];
                    const float p0 = bf_lo(wp[1][0]) * q[0] + bf_hi(wp[1][0]) * q[1] + bf_lo(wp[1][2]) * q[4] + bf_hi(wp[1][2]) * q[5];
                    const float p1 = bf_lo(wp[1][1]) * q[2] + bf_hi(wp[1][1]) * q[3] + bf_lo(wp[1][3]) * q[6] + bf_hi(wp[1][3]) * q[7];
                    sts32(pv_a + a * 512, pack_bf(p0, p1));
                }
                fence_async_smem();
                __syncwarp();
                mbar_arrive_elected(bar_hfull + wg * 8);
                G = __reduce_max_sync(0xffffffffu, (int)(info_next >> 20));
                gi = 0;
            }
        };
        if (left > 0) {
            uint32_t bd0, eb0, bd1 = 0, eb1 = 0;
            fetch(A0, bd0, eb0);
            while (true) {
                step(A0, bd0, eb0, A1, bd1, eb1);
                if (left <= 0) break;
                step(A1, bd1, eb1, A0, bd0, eb0);
                if (left <= 0) break;
            }
        }
    }
    STAMP(8);
}

typedef CUresult (*EncodeFn)(CUtensorMap*, CUtensorMapDataType, cuuint32_t, void*, const cuuint64_t*, const cuuint64_t*,
                             const cuuint32_t*, const cuuint32_t*, CUtensorMapInterleave, CUtensorMapSwizzle,
                             CUtensorMapL2promotion, CUtensorMapFloatOOBfill);

void make_map(EncodeFn enc, CUtensorMap* tm, const void* base, uint64_t lines, uint32_t box) {
    cuuint64_t gd[2] = {64, lines};
    cuuint64_t gs[1] = {128};
    cuuint32_t bd[2] = {64, box};
    cuuint32_t es[2] = {1, 1};
    enc(tm, CU_TENSOR_MAP_DATA_TYPE_BFLOAT16, 2, const_cast<void*>(base), gd, gs, bd, es, CU_TENSOR_MAP_INTERLEAVE_NONE,
        CU_TENSOR_MAP_SWIZZLE_128B, CU_TENSOR_MAP_L2_PROMOTION_L2_128B, CU_TENSOR_MAP_FLOAT_OOB_FILL_NONE);
}

void make_map3(EncodeFn enc, CUtensorMap* tm, const void* base, uint64_t nodes, uint32_t box) {
    cuuint64_t gd[3] = {64, 4, nodes};
    cuuint64_t gs[2] = {128, 512};
    cuuint32_t bd[3] = {64, 1, box};
    cuuint32_t es[3] = {1, 1, 1};
    enc(tm, CU_TENSOR_MAP_DATA_TYPE_BFLOAT16, 3, const_cast<void*>(base), gd, gs, bd, es, CU_TENSOR_MAP_INTERLEAVE_NONE,
        CU_TENSOR_MAP_SWIZZLE_128B, CU_TENSOR_MAP_L2_PROMOTION_L2_128B, CU_TENSOR_MAP_FLOAT_OOB_FILL_NONE);
}

}

extern "C" void kernel_launch(void* const* d_in, const int* in_sizes, int n_in, void* d_out, int out_size) {
    (void)n_in; (void)out_size;
    static int n_sm = 0;
    static EncodeFn enc = nullptr;
    static void* f_ptr = nullptr;
    if (n_sm == 0) {
        int dev = 0;
        cudaGetDevice(&dev);
        cudaDeviceGetAttribute(&n_sm, cudaDevAttrMultiProcessorCount, dev);
        cudaFuncSetAttribute(painn_kernel, cudaFuncAttributeMaxDynamicSharedMemorySize, SM_TOTAL);
        void* fn = nullptr;
        cudaDriverEntryPointQueryResult qr;
        cudaGetDriverEntryPoint("cuTensorMapEncodeTiled", &fn, cudaEnableDefault, &qr);
        enc = (EncodeFn)fn;
        cudaGetSymbolAddress(&f_ptr, g_F);
    }
    Params p;
    p.sv    = (const __nv_bfloat16*)d_in[0];
    p.pos   = (const __nv_bfloat16*)d_in[1];
    p.src   = (const int*)d_in[2];
    p.dst   = (const int*)d_in[3];
    p.freqs = (const __nv_bfloat16*)d_in[4];
    p.w1    = (const __nv_bfloat16*)d_in[5];
    p.w2    = (const __nv_bfloat16*)d_in[6];
    p.wr    = (const __nv_bfloat16*)d_in[7];
    p.out   = (__nv_bfloat16*)d_out;
    p.N = in_sizes[1] / 3;
    p.E = in_sizes[2];
    p.ncta = n_sm < MAX_CTA ? n_sm : MAX_CTA;
    p.npc = ((p.N + p.ncta - 1) / p.ncta + 3) & ~3;
    p.npc_magic = (uint32_t)(0x100000000ull / (uint32_t)p.npc) + 1u;
    p.quads_per_cta = ((p.E >> 2) + p.ncta - 1) / p.ncta;
    if (!enc || p.N > MAX_N || p.npc > MAX_NPC || (p.E & 3) || p.quads_per_cta > MAX_ROUNDS * 32) return;

    CUtensorMap tmF, tmFs;
    make_map(enc, &tmF, f_ptr, (uint64_t)p.N * 4, 4);
    make_map3(enc, &tmFs, f_ptr, (uint64_t)p.N, 4);

    cudaLaunchConfig_t cfg = {};
    cfg.gridDim = dim3(p.ncta);
    cfg.blockDim = dim3(NT);
    cfg.dynamicSmemBytes = SM_TOTAL;
    cfg.stream = cudaStreamPerThread;
    cudaLaunchAttribute attr[1];
    attr[0].id = cudaLaunchAttributeCooperative;
    attr[0].val.cooperative = 1;
    cfg.attrs = attr;
    cfg.numAttrs = 1;
    cudaLaunchKernelEx(&cfg, painn_kernel, p, tmF, tmFs);
}
```

```cpp
#include <cuda_runtime.h>
#include <cuda.h>
#include <cuda_bf16.h>
#include <stdint.h>

namespace {

constexpr int NT        = 512;
constexpr int NCWG      = 2;
constexpr int MAX_N     = 10240;
constexpr int MAX_CTA   = 136;
constexpr int MAX_NPC   = 80;
constexpr int MAX_ROUNDS = 38;
constexpr int REC_CAP   = MAX_ROUNDS * 128;
constexpr int SEG_CAP   = 64;
constexpr int SLOT_CAP  = 6144;
constexpr int MAX_STAGE = 5;
constexpr int STAGE_B   = 12288;

constexpr uint32_t D_MIN_BITS = 0x38D2;
constexpr uint32_t D_MAX_BITS = 0x409C;
constexpr int TAB_ROWS  = (int)(D_MAX_BITS - D_MIN_BITS) + 1;
constexpr int TAB_ZERO  = TAB_ROWS;
constexpr int TAB_BYTES = (TAB_ROWS + 1) * 32;

constexpr int SM_BINCNT = 0;
constexpr int SM_BINOFF = SM_BINCNT + MAX_CTA * 4;
constexpr int SM_NCNT   = SM_BINOFF + MAX_CTA * 4;
constexpr int SM_NINFO  = SM_NCNT + MAX_NPC * 4;
constexpr int SM_ORDER  = SM_NINFO + (MAX_NPC + 1) * 4;
constexpr int SM_CTRL   = SM_ORDER + MAX_NPC + 12;
constexpr int SM_BARS   = SM_CTRL + 64;
constexpr int SM_SID    = 2048 + 256;
constexpr int SM_META   = SM_SID + SLOT_CAP * 2;
constexpr int SM_TOTAL  = 232448;
constexpr int SM_HT     = (SM_TOTAL - 4 * 8192 - 4 * 1536) / 1024 * 1024;
constexpr int SM_PV     = SM_HT + 4 * 8192;
constexpr int SM_RING   = SM_HT - NCWG * MAX_STAGE * STAGE_B;
constexpr int P1_POS    = 3072;
constexpr int P1_SEGA   = P1_POS + 61440;
constexpr int P1_SEGB   = P1_SEGA + MAX_CTA * SEG_CAP * 8;
constexpr int P1_SV     = P1_SEGB + MAX_CTA * SEG_CAP * 4;
constexpr int P1_W1     = P1_SV + 4 * MAX_NPC * 128;
constexpr int P1_W2     = P1_W1 + 8192;
constexpr int P1_END    = P1_W2 + 8192;
constexpr int P1_REC    = P1_SEGA;
constexpr int STAGE_CAP = (P1_SV - P1_REC) / 16;
static_assert(SM_BARS + (12 + 2 * NCWG * MAX_STAGE) * 8 <= SM_SID, "misc block");
static_assert(SM_BARS + 256 <= P1_POS, "misc block");
static_assert(P1_END <= SM_TOTAL && P1_SV % 1024 == 0 && P1_REC % 16 == 0, "phase 1 overlay");
static_assert(SM_META + SLOT_CAP * 8 <= SM_RING && SM_PV + 4 * 1536 <= SM_TOTAL, "CSR");
static_assert(SM_RING % 1024 == 0 && SM_HT % 1024 == 0, "alignment");
static_assert(SM_BARS % 8 == 0 && SM_META % 8 == 0 && SM_CTRL % 4 == 0, "alignment");
static_assert(MAX_N * 6 <= 61440, "pos");
static_assert(SM_RING >= P1_SEGA && SM_HT <= P1_END, "every byte of the stages is written (finite) during phase 1");
static_assert(SM_SID + MAX_NPC * 1024 <= SM_TOTAL, "slow path accumulators");

__device__ __align__(1024) uint4 g_F[MAX_N * 32];
__device__ __align__(128) uint32_t g_seg[MAX_CTA * MAX_CTA * SEG_CAP * 3];
__device__ uint4    g_table[(TAB_BYTES + 15) / 16];
__device__ unsigned g_bar[2];
#define STAMP(k)
#define STAMPT(k, T)
#define ITS(k)

struct Params {
    const __nv_bfloat16* sv;
    const __nv_bfloat16* pos;
    const int*           src;
    const int*           dst;
    const __nv_bfloat16* freqs;
    const __nv_bfloat16* w1;
    const __nv_bfloat16* w2;
    const __nv_bfloat16* wr;
    __nv_bfloat16*       out;
    int N, E, ncta, npc;
    uint32_t npc_magic;
    int quads_per_cta;
};

__device__ __forceinline__ uint32_t smem_u32(const void* p) { return (uint32_t)__cvta_generic_to_shared(p); }
__device__ __forceinline__ float bf_lo(uint32_t v) { return __uint_as_float(v << 16); }
__device__ __forceinline__ float bf_hi(uint32_t v) { return __uint_as_float(v & 0xffff0000u); }
__device__ __forceinline__ float bf_u16(uint16_t v) { return __uint_as_float((uint32_t)v << 16); }
__device__ __forceinline__ uint32_t pack_bf(float lo, float hi) {
    uint32_t r;
    asm("cvt.rn.bf16x2.f32 %0, %1, %2;" : "=r"(r) : "f"(hi), "f"(lo));
    return r;
}
__device__ __forceinline__ float rbf(float x) { return bf_lo(pack_bf(x, 0.f)); }
__device__ __forceinline__ uint32_t hmul2(uint32_t a, uint32_t b) {
    uint32_t r;
    asm("mul.rn.bf16x2 %0, %1, %2;" : "=r"(r) : "r"(a), "r"(b));
    return r;
}
__device__ __forceinline__ uint32_t hsub2(uint32_t a, uint32_t b) {
    uint32_t r;
    asm("sub.rn.bf16x2 %0, %1, %2;" : "=r"(r) : "r"(a), "r"(b));
    return r;
}
__device__ __forceinline__ uint32_t lds32(uint32_t a) { uint32_t v; asm volatile("ld.shared.u32 %0, [%1];" : "=r"(v) : "r"(a)); return v; }
__device__ __forceinline__ uint32_t lds16(uint32_t a) { uint16_t v; asm volatile("ld.shared.u16 %0, [%1];" : "=h"(v) : "r"(a)); return v; }
__device__ __forceinline__ uint2 lds64(uint32_t a) { uint2 v; asm volatile("ld.shared.v2.u32 {%0,%1}, [%2];" : "=r"(v.x), "=r"(v.y) : "r"(a)); return v; }
__device__ __forceinline__ uint4 lds128(uint32_t a) { uint4 v; asm volatile("ld.shared.v4.u32 {%0,%1,%2,%3}, [%4];" : "=r"(v.x), "=r"(v.y), "=r"(v.z), "=r"(v.w) : "r"(a)); return v; }
__device__ __forceinline__ void sts32(uint32_t a, uint32_t v) { asm volatile("st.shared.u32 [%0], %1;" ::"r"(a), "r"(v) : "memory"); }
__device__ __forceinline__ void sts128(uint32_t a, uint4 v) { asm volatile("st.shared.v4.u32 [%0], {%1,%2,%3,%4};" ::"r"(a), "r"(v.x), "r"(v.y), "r"(v.z), "r"(v.w) : "memory"); }
__device__ __forceinline__ void mbar_init(uint32_t bar, int cnt) { asm volatile("mbarrier.init.shared::cta.b64 [%0], %1;" ::"r"(bar), "r"(cnt) : "memory"); }
__device__ __forceinline__ void mbar_expect_tx(uint32_t bar, uint32_t bytes) { asm volatile("mbarrier.arrive.expect_tx.shared::cta.b64 _, [%0], %1;" ::"r"(bar), "r"(bytes) : "memory"); }
__device__ __forceinline__ void mbar_arrive(uint32_t bar) { asm volatile("mbarrier.arrive.shared::cta.b64 _, [%0];" ::"r"(bar) : "memory"); }
#define WAIT_HINT ""
__device__ __forceinline__ void mbar_wait(uint32_t bar, uint32_t parity) {
    asm volatile("{\n.reg .pred p;\n.reg .u32 c;\n"
                 "mbarrier.try_wait.parity.shared::cta.b64 p, [%0], %1;\n"
                 "@p bra DONE_%=;\n"
                 "mov.u32 c, 0;\n"
                 "LOOP_%=:\n"
                 "mbarrier.try_wait.parity.shared::cta.b64 p, [%0], %1" WAIT_HINT ";\n"
                 "@p bra DONE_%=;\n"
                 "add.u32 c, c, 1;\n"
                 "setp.lt.u32 p, c, 4194304;\n"
                 "@p bra LOOP_%=;\n"
                 "DONE_%=:\n}"
                 ::"r"(bar), "r"(parity) : "memory");
}
__device__ __forceinline__ void mbar_arrive_elected(uint32_t bar) {
    asm volatile("{\n.reg .pred p;\nelect.sync _|p, 0xffffffff;\n@p mbarrier.arrive.shared::cta.b64 _, [%0];\n}" ::"r"(bar) : "memory");
}
__device__ __forceinline__ void bulk_g2s(uint32_t dst, const void* src, uint32_t bytes, uint32_t bar) {
    asm volatile("cp.async.bulk.shared::cluster.global.mbarrier::complete_tx::bytes [%0], [%1], %2, [%3];"
                 ::"r"(dst), "l"(src), "r"(bytes), "r"(bar) : "memory");
}
__device__ __forceinline__ void cp_async16(uint32_t dst, const void* src) {
    asm volatile("cp.async.cg.shared.global [%0], [%1], 16;" ::"r"(dst), "l"(src) : "memory");
}
__device__ __forceinline__ void tma_load(uint32_t dst, const CUtensorMap* tm, int line, uint32_t bar) {
    asm volatile("cp.async.bulk.tensor.2d.shared::cluster.global.mbarrier::complete_tx::bytes [%0], [%1, {%3, %4}], [%2];"
                 ::"r"(dst), "l"(tm), "r"(bar), "r"(0), "r"(line) : "memory");
}
__device__ __forceinline__ void tma_load3(uint32_t dst, const CUtensorMap* tm, int comp, int node, uint32_t bar) {
    asm volatile("cp.async.bulk.tensor.3d.shared::cluster.global.mbarrier::complete_tx::bytes [%0], [%1, {%3, %4, %5}], [%2];"
                 ::"r"(dst), "l"(tm), "r"(bar), "r"(0), "r"(comp), "r"(node) : "memory");
}
__device__ __forceinline__ void tma_store3(const CUtensorMap* tm, int comp, int node, uint32_t src) {
    asm volatile("cp.async.bulk.tensor.3d.global.shared::cta.bulk_group [%0, {%2, %3, %4}], [%1];"
                 ::"l"(tm), "r"(src), "r"(0), "r"(comp), "r"(node) : "memory");
}
__device__ __forceinline__ void fence_async_smem() { asm volatile("fence.proxy.async.shared::cta;" ::: "memory"); }
__device__ __forceinline__ void named_barrier(int id) { asm volatile("bar.sync %0, 128;" ::"r"(id) : "memory"); }
__device__ __forceinline__ void ldsm4(uint32_t (&r)[4], uint32_t a) {
    asm volatile("ldmatrix.sync.aligned.m8n8.x4.shared.b16 {%0,%1,%2,%3}, [%4];" : "=r"(r[0]), "=r"(r[1]), "=r"(r[2]), "=r"(r[3]) : "r"(a) : "memory");
}
__device__ __forceinline__ void ldsm4t(uint32_t (&r)[4], uint32_t a) {
    asm volatile("ldmatrix.sync.aligned.m8n8.x4.trans.shared.b16 {%0,%1,%2,%3}, [%4];" : "=r"(r[0]), "=r"(r[1]), "=r"(r[2]), "=r"(r[3]) : "r"(a) : "memory");
}
__device__ __forceinline__ void stsm4(uint32_t a, uint32_t r0, uint32_t r1, uint32_t r2, uint32_t r3) {
    asm volatile("stmatrix.sync.aligned.m8n8.x4.shared.b16 [%0], {%1,%2,%3,%4};" ::"r"(a), "r"(r0), "r"(r1), "r"(r2), "r"(r3) : "memory");
}
__device__ __forceinline__ void mma16816(float (&c)[4], const uint32_t (&a)[4], uint32_t b0, uint32_t b1) {
    asm volatile("mma.sync.aligned.m16n8k16.row.col.f32.bf16.bf16.f32 {%0,%1,%2,%3}, {%4,%5,%6,%7}, {%8,%9}, {%0,%1,%2,%3};"
                 : "+f"(c[0]), "+f"(c[1]), "+f"(c[2]), "+f"(c[3])
                 : "r"(a[0]), "r"(a[1]), "r"(a[2]), "r"(a[3]), "r"(b0), "r"(b1));
}

__device__ __forceinline__ uint32_t desc_lo(uint32_t saddr) { return ((saddr & 0x3FFFF) >> 4) | (1u << 16); }
#define DESC_HI "0x40000040"
__device__ __forceinline__ void wg_fence() { asm volatile("wgmma.fence.sync.aligned;" ::: "memory"); }
__device__ __forceinline__ void wg_commit() { asm volatile("wgmma.commit_group.sync.aligned;" ::: "memory"); }
__device__ __forceinline__ void wg_wait0() { asm volatile("wgmma.wait_group.sync.aligned 0;" ::: "memory"); }
__device__ __forceinline__ void wg_wait1() { asm volatile("wgmma.wait_group.sync.aligned 1;" ::: "memory"); }

__device__ __forceinline__ void wgmma_n64_first(float (&d)[8], float (&e)[24], const uint32_t (&a)[4], uint32_t bdesc) {
    asm volatile("{\n.reg .b64 b;\nmov.b64 b, {%36, " DESC_HI "};\n"
                 "wgmma.mma_async.sync.aligned.m64n64k16.f32.bf16.bf16 {%0,%1,%2,%3,%4,%5,%6,%7,%8,%9,%10,%11,%12,%13,%14,%15,%16,%17,%18,%19,%20,%21,%22,%23,%24,%25,%26,%27,%28,%29,%30,%31}, {%32,%33,%34,%35}, b, 0, 1, 1, 1;\n}"
                 : "=f"(d[0]), "=f"(d[1]), "=f"(d[2]), "=f"(d[3]), "=f"(d[4]), "=f"(d[5]), "=f"(d[6]), "=f"(d[7]),
                   "=f"(e[0]), "=f"(e[1]), "=f"(e[2]), "=f"(e[3]), "=f"(e[4]), "=f"(e[5]), "=f"(e[6]), "=f"(e[7]), "=f"(e[8]), "=f"(e[9]), "=f"(e[10]), "=f"(e[11]), "=f"(e[12]), "=f"(e[13]), "=f"(e[14]), "=f"(e[15]), "=f"(e[16]), "=f"(e[17]), "=f"(e[18]), "=f"(e[19]), "=f"(e[20]), "=f"(e[21]), "=f"(e[22]), "=f"(e[23])
                 : "r"(a[0]), "r"(a[1]), "r"(a[2]), "r"(a[3]), "r"(bdesc));
}
__device__ __forceinline__ void wgmma_n64(float (&d)[8], float (&e)[24], const uint32_t (&a)[4], uint32_t bdesc) {
    asm volatile("{\n.reg .b64 b;\nmov.b64 b, {%36, " DESC_HI "};\n"
                 "wgmma.mma_async.sync.aligned.m64n64k16.f32.bf16.bf16 {%0,%1,%2,%3,%4,%5,%6,%7,%8,%9,%10,%11,%12,%13,%14,%15,%16,%17,%18,%19,%20,%21,%22,%23,%24,%25,%26,%27,%28,%29,%30,%31}, {%32,%33,%34,%35}, b, 1, 1, 1, 1;\n}"
                 : "+f"(d[0]), "+f"(d[1]), "+f"(d[2]), "+f"(d[3]), "+f"(d[4]), "+f"(d[5]), "+f"(d[6]), "+f"(d[7]),
                   "+f"(e[0]), "+f"(e[1]), "+f"(e[2]), "+f"(e[3]), "+f"(e[4]), "+f"(e[5]), "+f"(e[6]), "+f"(e[7]), "+f"(e[8]), "+f"(e[9]), "+f"(e[10]), "+f"(e[11]), "+f"(e[12]), "+f"(e[13]), "+f"(e[14]), "+f"(e[15]), "+f"(e[16]), "+f"(e[17]), "+f"(e[18]), "+f"(e[19]), "+f"(e[20]), "+f"(e[21]), "+f"(e[22]), "+f"(e[23])
                 : "r"(a[0]), "r"(a[1]), "r"(a[2]), "r"(a[3]), "r"(bdesc));
}
__device__ __forceinline__ void wgmma_n48_first(float (&e)[24], const uint32_t (&a)[4], uint32_t bdesc) {
    asm volatile("{\n.reg .b64 b;\nmov.b64 b, {%28, " DESC_HI "};\n"
                 "wgmma.mma_async.sync.aligned.m64n48k16.f32.bf16.bf16 {%0,%1,%2,%3,%4,%5,%6,%7,%8,%9,%10,%11,%12,%13,%14,%15,%16,%17,%18,%19,%20,%21,%22,%23}, {%24,%25,%26,%27}, b, 0, 1, 1, 1;\n}"
                 : "=f"(e[0]), "=f"(e[1]), "=f"(e[2]), "=f"(e[3]), "=f"(e[4]), "=f"(e[5]), "=f"(e[6]), "=f"(e[7]), "=f"(e[8]), "=f"(e[9]), "=f"(e[10]), "=f"(e[11]), "=f"(e[12]), "=f"(e[13]), "=f"(e[14]), "=f"(e[15]), "=f"(e[16]), "=f"(e[17]), "=f"(e[18]), "=f"(e[19]), "=f"(e[20]), "=f"(e[21]), "=f"(e[22]), "=f"(e[23])
                 : "r"(a[0]), "r"(a[1]), "r"(a[2]), "r"(a[3]), "r"(bdesc));
}
__device__ __forceinline__ void wgmma_n48(float (&e)[24], const uint32_t (&a)[4], uint32_t bdesc) {
    asm volatile("{\n.reg .b64 b;\nmov.b64 b, {%28, " DESC_HI "};\n"
                 "wgmma.mma_async.sync.aligned.m64n48k16.f32.bf16.bf16 {%0,%1,%2,%3,%4,%5,%6,%7,%8,%9,%10,%11,%12,%13,%14,%15,%16,%17,%18,%19,%20,%21,%22,%23}, {%24,%25,%26,%27}, b, 1, 1, 1, 1;\n}"
                 : "+f"(e[0]), "+f"(e[1]), "+f"(e[2]), "+f"(e[3]), "+f"(e[4]), "+f"(e[5]), "+f"(e[6]), "+f"(e[7]), "+f"(e[8]), "+f"(e[9]), "+f"(e[10]), "+f"(e[11]), "+f"(e[12]), "+f"(e[13]), "+f"(e[14]), "+f"(e[15]), "+f"(e[16]), "+f"(e[17]), "+f"(e[18]), "+f"(e[19]), "+f"(e[20]), "+f"(e[21]), "+f"(e[22]), "+f"(e[23])
                 : "r"(a[0]), "r"(a[1]), "r"(a[2]), "r"(a[3]), "r"(bdesc));
}
__device__ __forceinline__ void wgmma_n16_first(float (&d)[8], const uint32_t (&a)[4], uint32_t bdesc) {
    asm volatile("{\n.reg .b64 b;\nmov.b64 b, {%12, " DESC_HI "};\n"
                 "wgmma.mma_async.sync.aligned.m64n16k16.f32.bf16.bf16 {%0,%1,%2,%3,%4,%5,%6,%7}, {%8,%9,%10,%11}, b, 0, 1, 1, 1;\n}"
                 : "=f"(d[0]), "=f"(d[1]), "=f"(d[2]), "=f"(d[3]), "=f"(d[4]), "=f"(d[5]), "=f"(d[6]), "=f"(d[7])
                 : "r"(a[0]), "r"(a[1]), "r"(a[2]), "r"(a[3]), "r"(bdesc));
}
__device__ __forceinline__ void wgmma_n16(float (&d)[8], const uint32_t (&a)[4], uint32_t bdesc) {
    asm volatile("{\n.reg .b64 b;\nmov.b64 b, {%12, " DESC_HI "};\n"
                 "wgmma.mma_async.sync.aligned.m64n16k16.f32.bf16.bf16 {%0,%1,%2,%3,%4,%5,%6,%7}, {%8,%9,%10,%11}, b, 1, 1, 1, 1;\n}"
                 : "+f"(d[0]), "+f"(d[1]), "+f"(d[2]), "+f"(d[3]), "+f"(d[4]), "+f"(d[5]), "+f"(d[6]), "+f"(d[7])
                 : "r"(a[0]), "r"(a[1]), "r"(a[2]), "r"(a[3]), "r"(bdesc));
}

__device__ __forceinline__ void wgmma_n64_p(float (&d)[8], float (&e)[24], const uint32_t (&a)[4], uint32_t bdesc, int acc) {
    asm volatile("{\n.reg .pred p;\n.reg .b64 b;\nsetp.ne.b32 p, %37, 0;\nmov.b64 b, {%36, " DESC_HI "};\n"
                 "wgmma.mma_async.sync.aligned.m64n64k16.f32.bf16.bf16 {%0,%1,%2,%3,%4,%5,%6,%7,%8,%9,%10,%11,%12,%13,%14,%15,%16,%17,%18,%19,%20,%21,%22,%23,%24,%25,%26,%27,%28,%29,%30,%31}, {%32,%33,%34,%35}, b, p, 1, 1, 1;\n}"
                 : "+f"(d[0]), "+f"(d[1]), "+f"(d[2]), "+f"(d[3]), "+f"(d[4]), "+f"(d[5]), "+f"(d[6]), "+f"(d[7]),
                   "+f"(e[0]), "+f"(e[1]), "+f"(e[2]), "+f"(e[3]), "+f"(e[4]), "+f"(e[5]), "+f"(e[6]), "+f"(e[7]), "+f"(e[8]), "+f"(e[9]), "+f"(e[10]), "+f"(e[11]), "+f"(e[12]), "+f"(e[13]), "+f"(e[14]), "+f"(e[15]), "+f"(e[16]), "+f"(e[17]), "+f"(e[18]), "+f"(e[19]), "+f"(e[20]), "+f"(e[21]), "+f"(e[22]), "+f"(e[23])
                 : "r"(a[0]), "r"(a[1]), "r"(a[2]), "r"(a[3]), "r"(bdesc), "r"(acc));
}
__device__ __forceinline__ void wgmma_n16_p(float (&d)[8], const uint32_t (&a)[4], uint32_t bdesc, int acc) {
    asm volatile("{\n.reg .pred p;\n.reg .b64 b;\nsetp.ne.b32 p, %13, 0;\nmov.b64 b, {%12, " DESC_HI "};\n"
                 "wgmma.mma_async.sync.aligned.m64n16k16.f32.bf16.bf16 {%0,%1,%2,%3,%4,%5,%6,%7}, {%8,%9,%10,%11}, b, p, 1, 1, 1;\n}"
                 : "+f"(d[0]), "+f"(d[1]), "+f"(d[2]), "+f"(d[3]), "+f"(d[4]), "+f"(d[5]), "+f"(d[6]), "+f"(d[7])
                 : "r"(a[0]), "r"(a[1]), "r"(a[2]), "r"(a[3]), "r"(bdesc), "r"(acc));
}

__device__ __forceinline__ uint32_t edge_dist(uint32_t sxy, uint32_t sz, uint32_t dxy, uint32_t dz, uint32_t& rxy, uint32_t& rz) {
    rxy = hsub2(sxy, dxy);
    rz  = hsub2(sz, dz);
    uint32_t qxy = hmul2(rxy, rxy), qz = hmul2(rz, rz);
    float ss = rbf((bf_lo(qxy) + bf_hi(qxy)) + bf_lo(qz));
    float s2 = rbf(ss + 1e-8f);
    float d;
    asm("sqrt.approx.ftz.f32 %0, %1;" : "=f"(d) : "f"(s2));
    return pack_bf(d, 0.f) & 0xffffu;
}

__device__ __forceinline__ void load_pos(uint32_t sm_pos, int i, uint32_t& xy, uint32_t& z) {
    uint32_t a  = (sm_pos + 6u * (uint32_t)i) & ~3u;
    uint32_t w0 = lds32(a), w1 = lds32(a + 4);
    uint32_t sh = (uint32_t)i << 4;
    xy = __funnelshift_r(w0, w1, sh);
    z  = __funnelshift_r(w1, w1, sh);
}

__device__ __noinline__ float radial_value(float d, float f) {
    float arg = rbf(d * f);
    float sn  = rbf(sinf(arg));
    float rb  = rbf(__fdiv_rn(sn, d));
    float c   = rbf(cosf(rbf(__fdiv_rn(rbf(d * 3.14159265358979323846f), 5.0f))));
    float fc  = rbf(0.5f * rbf(c + 1.0f));
    return rb * fc;
}

__global__ void __launch_bounds__(NT, 1)
painn_kernel(const Params p, const __grid_constant__ CUtensorMap tmF, const __grid_constant__ CUtensorMap tmFs) {
    extern __shared__ __align__(1024) uint8_t smem[];
    const uint32_t sb   = smem_u32(smem);
    const int tid  = threadIdx.x, lane = tid & 31, warp = __shfl_sync(0xffffffffu, tid >> 5, 0);
    const int cta  = blockIdx.x;
    const int g    = lane >> 2, t = lane & 3;
    int* binCnt = (int*)(smem + SM_BINCNT);
    int* binOff = (int*)(smem + SM_BINOFF);
    int* nCnt   = (int*)(smem + SM_NCNT);
    uint32_t* nInfo = (uint32_t*)(smem + SM_NINFO);
    volatile int* ctrl = (volatile int*)(smem + SM_CTRL);
    const uint32_t bar_pos = sb + SM_BARS, bar_mlp = bar_pos + 8, bar_rec = bar_pos + 16;
    const uint32_t bar_full = bar_pos + 32, bar_empty = bar_full + NCWG * MAX_STAGE * 8;
    const uint32_t bar_hfull = bar_empty + NCWG * MAX_STAGE * 8, bar_hempty = bar_hfull + 32;

    const int node0  = cta * p.npc;
    const int nnodes = max(0, min(p.npc, p.N - node0));

    STAMP(0);
    if (tid == 32) {
        mbar_init(bar_pos, 1);
        asm volatile("fence.mbarrier_init.release.cluster;" ::: "memory");
        uint32_t pos_bytes = (uint32_t)(p.N * 6 + 15) & ~15u;
        mbar_expect_tx(bar_pos, pos_bytes);
        bulk_g2s(sb + P1_POS, p.pos, pos_bytes, bar_pos);
    } else if (tid == 64) {
        mbar_init(bar_rec, 1);
        for (int i = 0; i < 4; i++) { mbar_init(bar_hfull + 8 * i, 4); mbar_init(bar_hempty + 8 * i, 4); }
        asm volatile("prefetch.tensormap [%0];" ::"l"(&tmF) : "memory");
        asm volatile("prefetch.tensormap [%0];" ::"l"(&tmFs) : "memory");
    } else if (tid >= 96 && tid < 96 + NCWG * MAX_STAGE) {
        mbar_init(bar_full + 8 * (tid - 96), 2);
        mbar_init(bar_empty + 8 * (tid - 96), 4);
    }
    unsigned bar_seen = 0;
    if (tid == 0 || tid == 32) asm volatile("ld.relaxed.gpu.global.u32 %0, [%1];" : "=r"(bar_seen) : "l"(&g_bar[tid >> 5]) : "memory");
    const bool mlp_warp = warp >= 6;
    int4 s4[3], d4[3];
    const int q0 = cta * p.quads_per_cta;
    const int qend = min(q0 + p.quads_per_cta, p.E >> 2);
#pragma unroll
    for (int k = 0; k < 3; k++) {
        const int q = q0 + (k < 2 ? warp + 16 * k : 32 + warp) * 32 + lane;
        const bool ok = q < qend && (k < 2 || !mlp_warp);
        s4[k] = ok ? __ldg((const int4*)p.src + q) : make_int4(-1, -1, -1, -1);
        d4[k] = ok ? __ldg((const int4*)p.dst + q) : make_int4(0, 0, 0, 0);
    }
    if (tid < MAX_CTA) binCnt[tid] = 0;
    if (tid < MAX_NPC) nCnt[tid] = 0;
    if (tid < 16) ctrl[tid] = 0;
    if (tid >= 256 && tid < 256 + 240) {
        const int i = tid - 256;
        asm volatile("prefetch.global.L2 [%0];" ::"l"(i < 48 ? (const uint8_t*)p.wr + i * 128 : (const uint8_t*)p.w2 + (i - 48) * 128));
    }
    for (int i = P1_SEGA / 16 + tid; i < P1_SV / 16; i += NT) sts128(sb + i * 16, make_uint4(0u, 0u, 0u, 0u));
    for (int i = tid; i < 4 * (MAX_NPC - nnodes) * 8; i += NT)
        sts128(sb + P1_SV + (i / ((MAX_NPC - nnodes) * 8)) * (MAX_NPC * 128) + nnodes * 128 + (i % ((MAX_NPC - nnodes) * 8)) * 16, make_uint4(0u, 0u, 0u, 0u));
    __syncthreads();

    mbar_wait(bar_pos, 0);
    if (s4[0].x == 0x7fffffff) ctrl[15] = 1;
    for (int i = tid; i < nnodes * 32; i += NT) {
        const int r = i >> 5, b = (i >> 3) & 3, c = i & 7;
        cp_async16(sb + P1_SV + b * (MAX_NPC * 128) + r * 128 + ((c ^ (r & 7)) << 4), (const uint8_t*)p.sv + (size_t)node0 * 512 + i * 16);
    }
    for (int i = tid; i < 1024; i += NT) {
        const int m = i >> 9, k = (i >> 3) & 63, c = i & 7;
        cp_async16(sb + P1_W1 + m * 8192 + k * 128 + ((c ^ (k & 7)) << 4),
                   m == 0 ? (const uint8_t*)p.w1 + k * 128 + c * 16 : (const uint8_t*)p.w2 + k * 384 + 128 + c * 16);
    }
    asm volatile("cp.async.commit_group;" ::: "memory");
    STAMP(1);
#pragma unroll
    for (int k = 0; k < 3; k++) {
        const int ss[4] = {s4[k].x, s4[k].y, s4[k].z, s4[k].w};
        const int dd[4] = {d4[k].x, d4[k].y, d4[k].z, d4[k].w};
        if (ss[0] >= 0) {
            uint32_t w0[4], w1[4], v0[4], v1[4], r0[4], r1[4], r2[4], bin[4], rank[4];
#pragma unroll
            for (int j = 0; j < 4; j++) {
                const uint32_t a = (sb + P1_POS + 6u * (uint32_t)ss[j]) & ~3u, c = (sb + P1_POS + 6u * (uint32_t)dd[j]) & ~3u;
                w0[j] = lds32(a); w1[j] = lds32(a + 4); v0[j] = lds32(c); v1[j] = lds32(c + 4);
            }
#pragma unroll
            for (int j = 0; j < 4; j++) {
                const uint32_t sh = (uint32_t)ss[j] << 4, dh = (uint32_t)dd[j] << 4;
                uint32_t rxy, rz;
                const uint32_t db = edge_dist(__funnelshift_r(w0[j], w1[j], sh), __funnelshift_r(w1[j], w1[j], sh),
                                              __funnelshift_r(v0[j], v1[j], dh), __funnelshift_r(v1[j], v1[j], dh), rxy, rz);
                float inv;
                asm("rcp.approx.ftz.f32 %0, %1;" : "=f"(inv) : "f"(__uint_as_float(db << 16)));
                bin[j] = __umulhi((uint32_t)dd[j], p.npc_magic);
                r0[j] = (uint32_t)ss[j] | ((db - D_MIN_BITS) << 16);
                r1[j] = pack_bf(bf_lo(rxy) * inv, bf_hi(rxy) * inv);
                r2[j] = __byte_perm(pack_bf(bf_lo(rz) * inv, 0.f), (uint32_t)dd[j] - bin[j] * (uint32_t)p.npc, 0x5410);
                rank[j] = db <= D_MAX_BITS ? (uint32_t)atomicAdd(&binCnt[bin[j]], 1) : 0xffffu;
            }
#pragma unroll
            for (int j = 0; j < 4; j++) {
                if (rank[j] < SEG_CAP) {
                    const uint32_t slot = bin[j] * SEG_CAP + rank[j];
                    asm volatile("st.shared.v2.u32 [%0], {%1, %2};" ::"r"(sb + P1_SEGA + slot * 8), "r"(r0[j]), "r"(r1[j]) : "memory");
                    sts32(sb + P1_SEGB + slot * 4, r2[j]);
                }
            }
        }
    }
    __syncthreads();
    STAMP(2);
    {
        constexpr int IT = (MAX_CTA + 31) / 32;
        uint2 ca[IT][2];
        uint32_t cb[IT][2];
        int cn[IT];
#pragma unroll
        for (int it = 0; it < IT; it++) {
            const int b = min(2 * warp + (lane >> 4) + 32 * it, MAX_CTA - 1);
            cn[it] = binCnt[b];
#pragma unroll
            for (int u = 0; u < 2; u++) {
                const int j = (lane & 15) + 16 * u;
                ca[it][u] = lds64(sb + P1_SEGA + (b * SEG_CAP + j) * 8);
                cb[it][u] = lds32(sb + P1_SEGB + (b * SEG_CAP + j) * 4);
            }
        }
#pragma unroll
        for (int it = 0; it < IT; it++) {
            const int b = 2 * warp + (lane >> 4) + 32 * it;
            if (b < p.ncta) {
                uint32_t* dstp = g_seg + ((size_t)cta * MAX_CTA + b) * (SEG_CAP * 3);
                const uint32_t tag = (uint32_t)min(cn[it], 511) << 23;
#pragma unroll
                for (int u = 0; u < 2; u++) {
                    const int j = (lane & 15) + 16 * u;
                    *(uint2*)(dstp + 2 * j) = ca[it][u];
                    dstp[2 * SEG_CAP + j] = cb[it][u] | tag;
                }
                for (int j = 32 + (lane & 15); j < ((min(cn[it], SEG_CAP) + 7) & ~7); j += 16) {
                    *(uint2*)(dstp + 2 * j) = lds64(sb + P1_SEGA + (b * SEG_CAP + j) * 8);
                    dstp[2 * SEG_CAP + j] = lds32(sb + P1_SEGB + (b * SEG_CAP + j) * 4);
                }
            }
        }
    }
    STAMP(7);
    asm volatile("cp.async.wait_group 0;" ::: "memory");
    __syncthreads();
    STAMP(3);
    if (tid == 64) asm volatile("red.add.release.gpu.global.u32 [%0], 1;" ::"l"(&g_bar[0]) : "memory");

    if (!mlp_warp) {
        const int rows_per = (TAB_ROWS + 1 + p.ncta - 1) / p.ncta;
        for (int i = tid; i < rows_per * 8; i += 6 * 32) {
            int row = cta * rows_per + (i >> 3), kp = i & 7;
            if (row <= TAB_ROWS) {
                uint32_t val = 0;
                if (row < TAB_ROWS) {
                    float d = __uint_as_float((D_MIN_BITS + row) << 16);
                    uint32_t f2 = __ldg((const uint32_t*)p.freqs + kp);
                    val = pack_bf(radial_value(d, bf_lo(f2)), radial_value(d, bf_hi(f2)));
                }
                ((uint32_t*)g_table)[row * 8 + kp] = val;
            }
        }
    } else {
        const int mt = (warp - 6) >> 1, hf = (warp - 6) & 1;
        if (mt * 16 < nnodes) {
            STAMPT(10, 6 * 32);
            const int lrow = lane & 15, lch = lane >> 4;
            const uint32_t rowb = sb + P1_SV + (mt * 16 + lrow) * 128;
            const uint32_t key0 = lrow & 7;
            float acc[4][4];
#pragma unroll
            for (int i = 0; i < 4; i++) { acc[i][0] = acc[i][1] = acc[i][2] = acc[i][3] = 0.f; }
#pragma unroll
            for (int ks = 0; ks < 4; ks++) {
                uint32_t a[4];
                ldsm4(a, rowb + (((2 * ks + lch) ^ key0) << 4));
                const int kk = 16 * ks + lrow;
#pragma unroll
                for (int nt = 0; nt < 4; nt += 2) {
                    uint32_t b[4];
                    ldsm4t(b, sb + P1_W1 + kk * 128 + (((4 * hf + nt + lch) ^ (kk & 7)) << 4));
                    mma16816(acc[nt], a, b[0], b[1]);
                    mma16816(acc[nt + 1], a, b[2], b[3]);
                }
            }
            uint32_t hp[4][2];
#pragma unroll
            for (int i = 0; i < 4; i++) {
                float h[4];
#pragma unroll
                for (int q = 0; q < 4; q++) {
                    float x = rbf(acc[i][q]);
                    h[q] = __fdividef(x, 1.0f + __expf(-x));
                    acc[i][q] = 0.f;
                }
                hp[i][0] = pack_bf(h[0], h[1]);
                hp[i][1] = pack_bf(h[2], h[3]);
            }
            asm volatile("bar.sync %0, 64;" ::"r"(4 + mt) : "memory");
#pragma unroll
            for (int i = 0; i < 4; i += 2)
                stsm4(rowb + (((4 * hf + i + lch) ^ key0) << 4), hp[i][0], hp[i][1], hp[i + 1][0], hp[i + 1][1]);
            asm volatile("bar.sync %0, 64;" ::"r"(4 + mt) : "memory");
#pragma unroll
            for (int ks = 0; ks < 4; ks++) {
                uint32_t a[4];
                ldsm4(a, rowb + (((2 * ks + lch) ^ key0) << 4));
                const int kk = 16 * ks + lrow;
#pragma unroll
                for (int nt = 0; nt < 4; nt += 2) {
                    uint32_t b[4];
                    ldsm4t(b, sb + P1_W2 + kk * 128 + (((4 * hf + nt + lch) ^ (kk & 7)) << 4));
                    mma16816(acc[nt], a, b[0], b[1]);
                    mma16816(acc[nt + 1], a, b[2], b[3]);
                }
            }
            uint32_t vq[2][3][4];
            const uint32_t vb = sb + P1_SV + (mt * 16 + g) * 128 + 4 * t;
#pragma unroll
            for (int rh = 0; rh < 2; rh++)
#pragma unroll
                for (int a = 0; a < 3; a++)
#pragma unroll
                    for (int i = 0; i < 4; i++) vq[rh][a][i] = lds32(vb + (a + 1) * (MAX_NPC * 128) + rh * 1024 + (((4 * hf + i) ^ g) << 4));
#pragma unroll
            for (int rh = 0; rh < 2; rh++)
#pragma unroll
                for (int a = 0; a < 3; a++)
#pragma unroll
                    for (int i = 0; i < 4; i++)
                        sts32(vb + (a + 1) * (MAX_NPC * 128) + rh * 1024 + (((4 * hf + i) ^ g) << 4),
                              hmul2(pack_bf(acc[i][2 * rh], acc[i][2 * rh + 1]), vq[rh][a][i]));
            fence_async_smem();
            asm volatile("bar.sync %0, 64;" ::"r"(4 + mt) : "memory");
            {
                const int r4 = mt * 16 + 8 * hf + 4 * (lane >> 2), comp = lane & 3;
                if (lane < 8 && r4 < nnodes) tma_store3(&tmFs, comp, node0 + r4, sb + P1_SV + comp * (MAX_NPC * 128) + r4 * 128);
            }
            asm volatile("cp.async.bulk.commit_group;" ::: "memory");
        }
        STAMPT(11, 6 * 32);
    }
    if (tid == 0) {
        const unsigned target = (bar_seen / (unsigned)p.ncta + 1u) * (unsigned)p.ncta;
        unsigned cur;
        int spins = 0;
        do {
            asm volatile("ld.acquire.gpu.global.u32 %0, [%1];" : "=r"(cur) : "l"(&g_bar[0]) : "memory");
        } while ((int)(cur - target) < 0 && ++spins < (1 << 24));
    }
    STAMP(4);
    __syncthreads();
    STAMP(5);

    constexpr int SEG_IT = (MAX_CTA + 31) / 32;
    uint2 ra[SEG_IT][2];
    uint32_t rb[SEG_IT][2], rr[SEG_IT][2];
#pragma unroll
    for (int it = 0; it < SEG_IT; it++) {
        const int b = 2 * warp + (lane >> 4) + 32 * it;
        const uint32_t* sp = g_seg + ((size_t)b * MAX_CTA + cta) * (SEG_CAP * 3);
#pragma unroll
        for (int u = 0; u < 2; u++) {
            const int j = (lane & 15) + 16 * u;
            ra[it][u] = b < p.ncta ? __ldcg((const uint2*)(sp + 2 * j)) : make_uint2(0u, 0u);
            rb[it][u] = b < p.ncta ? __ldcg(sp + 2 * SEG_CAP + j) : 0u;
        }
    }
    if (mlp_warp && lane < 8) {
        asm volatile("cp.async.bulk.wait_group 0;" ::: "memory");
        asm volatile("fence.proxy.async;" ::: "memory");
    }
    STAMP(9);
    uint2 xa[SEG_IT];
    uint32_t xb[SEG_IT];
#pragma unroll
    for (int it = 0; it < SEG_IT; it++) {
        const int cnt = rb[it][0] >> 23;
        const int b = 2 * warp + (lane >> 4) + 32 * it;
        const uint32_t* sp = g_seg + ((size_t)b * MAX_CTA + cta) * (SEG_CAP * 3);
        const bool has = 32 + (lane & 15) < cnt;
        xa[it] = has ? __ldcg((const uint2*)(sp + 2 * (32 + (lane & 15)))) : make_uint2(0u, 0u);
        xb[it] = has ? __ldcg(sp + 2 * SEG_CAP + 32 + (lane & 15)) : 0u;
    }
#pragma unroll
    for (int it = 0; it < SEG_IT; it++) {
        const int cnt = rb[it][0] >> 23;
        if (cnt > SEG_CAP) ctrl[1] = 1;
#pragma unroll
        for (int u = 0; u < 2; u++)
            rr[it][u] = (lane & 15) + 16 * u < cnt ? (uint32_t)atomicAdd(&nCnt[(rb[it][u] >> 16) & 0x7fu], 1) : 0xffffffffu;
    }
#pragma unroll
    for (int it = 0; it < SEG_IT; it++) {
        const int cnt = rb[it][0] >> 23;
        if (32 + (lane & 15) < cnt) {
            const int pos = atomicAdd((int*)&ctrl[8], 1);
            const uint32_t rank = (uint32_t)atomicAdd(&nCnt[(xb[it] >> 16) & 0x7fu], 1);
            if (pos < STAGE_CAP) sts128(sb + P1_REC + pos * 16, make_uint4(xa[it].x, xa[it].y, xb[it], rank));
        }
        if (cnt > 48) {
            const int b = 2 * warp + (lane >> 4) + 32 * it;
            const uint32_t* sp = g_seg + ((size_t)b * MAX_CTA + cta) * (SEG_CAP * 3);
            const int j = 48 + (lane & 15);
            if (j < min(cnt, SEG_CAP)) {
                const uint2 a = __ldcg((const uint2*)(sp + 2 * j));
                const uint32_t c = __ldcg(sp + 2 * SEG_CAP + j);
                const int pos = atomicAdd((int*)&ctrl[8], 1);
                const uint32_t rank = (uint32_t)atomicAdd(&nCnt[(c >> 16) & 0x7fu], 1);
                if (pos < STAGE_CAP) sts128(sb + P1_REC + pos * 16, make_uint4(a.x, a.y, c, rank));
            }
        }
    }
    STAMP(13);
    __syncthreads();
    if (tid == 64) asm volatile("red.add.release.gpu.global.u32 [%0], 1;" ::"l"(&g_bar[1]) : "memory");
    STAMP(14);
    const int total = ctrl[8];
    if (tid == 0 && total > STAGE_CAP) ctrl[1] = 1;
    if (warp == 0) {
        int c[3], s = 0;
#pragma unroll
        for (int i = 0; i < 3; i++) {
            int b = lane * 3 + i;
            c[i] = b < nnodes ? max(16, (nCnt[b] + 15) & ~15) : 0;
            s += c[i];
        }
        int x = s;
#pragma unroll
        for (int o = 1; o < 32; o <<= 1) { int y = __shfl_up_sync(0xffffffffu, x, o); if (lane >= o) x += y; }
        const int slots = __shfl_sync(0xffffffffu, x, 31);
        int off = x - s, below = 0;
#pragma unroll
        for (int i = 0; i < 3; i++) {
            int b = lane * 3 + i;
            if (b < nnodes) {
                nInfo[b] = (uint32_t)off | ((uint32_t)c[i] << 16);
                below += (2 * off + c[i] < slots);
            }
            off += c[i];
        }
        below = __reduce_add_sync(0xffffffffu, below);
        if (lane == 0) {
            ctrl[2] = below;
            ctrl[4] = slots;
            if (slots > SLOT_CAP) ctrl[1] = 1;
        }
    }
    __syncthreads();
    if (ctrl[1] == 0) {
        uint16_t* sid = (uint16_t*)(smem + SM_SID);
        uint2* meta = (uint2*)(smem + SM_META);
#pragma unroll
        for (int it = 0; it < SEG_IT; it++)
#pragma unroll
            for (int u = 0; u < 2; u++)
                if (rr[it][u] != 0xffffffffu) rr[it][u] += lds32(sb + SM_NINFO + ((rb[it][u] >> 16) & 0x7fu) * 4) & 0xffffu;
#pragma unroll
        for (int it = 0; it < SEG_IT; it++)
#pragma unroll
            for (int u = 0; u < 2; u++)
                if (rr[it][u] != 0xffffffffu) {
                    sid[rr[it][u]]  = (uint16_t)((ra[it][u].x & 0xffffu) << 2);
                    meta[rr[it][u]] = make_uint2(((ra[it][u].x >> 16) << 5) | (rb[it][u] << 16), ra[it][u].y);
                }
        for (int i = tid; i < total; i += NT) {
            const uint4 r = lds128(sb + P1_REC + i * 16);
            const int pos = (int)(lds32(sb + SM_NINFO + ((r.z >> 16) & 0x7fu) * 4) & 0xffffu) + (int)r.w;
            sid[pos]  = (uint16_t)((r.x & 0xffffu) << 2);
            meta[pos] = make_uint2(((r.x >> 16) << 5) | (r.z << 16), r.y);
        }
        if (tid >= NT - 128 && tid - (NT - 128) < nnodes) {
            const int b = tid - (NT - 128), split = ctrl[2];
            const int mid = split < nnodes ? (int)(nInfo[split] & 0xffffu) : ctrl[4];
            const int st = b >= split;
            const int mine = (int)(nInfo[b] & 0xffffu) + (int)(nInfo[b] >> 16) - (st ? mid : 0);
            int lo = st ? 0 : split, hi = st ? split : nnodes;
            const int first = lo;
            while (lo < hi) {
                const int o = (lo + hi) >> 1;
                const int other = (int)(nInfo[o] & 0xffffu) + (int)(nInfo[o] >> 16) - (st ? 0 : mid);
                if (st ? (other <= mine) : (other < mine)) lo = o + 1; else hi = o;
            }
            const int rank = (st ? b - split : b) + lo - first;
            smem[SM_ORDER + rank] = (uint8_t)(b | (st << 7));
        }
        for (int i = tid; i < nnodes * 16; i += NT) {
            int nl = i >> 4, c = nCnt[nl];
            int j = (c & ~15) + (i & 15);
            if (j >= c && (j < 16 || (c & 15))) {
                int pos = (int)(nInfo[nl] & 0xffffu) + j;
                sid[pos]  = 0xffffu;
                meta[pos] = make_uint2((uint32_t)TAB_ZERO << 5, 0u);
            }
        }
    }
    STAMP(15);
    if (tid == 32) {
        const unsigned target = (bar_seen / (unsigned)p.ncta + 1u) * (unsigned)p.ncta;
        unsigned cur;
        int spins = 0;
        do {
            asm volatile("ld.acquire.gpu.global.u32 %0, [%1];" : "=r"(cur) : "l"(&g_bar[1]) : "memory");
        } while ((int)(cur - target) < 0 && ++spins < (1 << 24));
    }
    fence_async_smem();
    __syncthreads();
    STAMP(6);

    if (__shfl_sync(0xffffffffu, ctrl[1], 0) != 0) {
        float* acc = (float*)(smem + P1_POS);
        for (int i = tid; i < nnodes * 256; i += NT) acc[i] = 0.f;
        __syncthreads();
        const uint16_t* posu = (const uint16_t*)p.pos;
        const uint32_t* tabg = (const uint32_t*)g_table;
        const uint32_t* Fw = (const uint32_t*)g_F;
        for (int e0 = warp * 32; e0 < p.E; e0 += NT) {
            int e = e0 + lane;
            int s = 0, d = 0;
            uint32_t db = 0xffff, rxy = 0, rz = 0;
            bool act = false;
            if (e < p.E) {
                s = p.src[e]; d = p.dst[e];
                if (d >= node0 && d < node0 + nnodes) {
                    uint32_t sxy = posu[s * 3] | ((uint32_t)posu[s * 3 + 1] << 16), sz = posu[s * 3 + 2];
                    uint32_t dxy = posu[d * 3] | ((uint32_t)posu[d * 3 + 1] << 16), dz = posu[d * 3 + 2];
                    db  = edge_dist(sxy, sz, dxy, dz, rxy, rz);
                    act = db <= D_MAX_BITS;
                }
            }
            unsigned m = __ballot_sync(0xffffffffu, act);
            while (m) {
                int l = __ffs(m) - 1;
                m &= m - 1;
                int es = __shfl_sync(0xffffffffu, s, l), ed = __shfl_sync(0xffffffffu, d, l);
                uint32_t edb = __shfl_sync(0xffffffffu, db, l), exy = __shfl_sync(0xffffffffu, rxy, l), ez = __shfl_sync(0xffffffffu, rz, l);
                float inv = 1.0f / __uint_as_float(edb << 16);
                float rh[3] = {rbf(bf_lo(exy) * inv), rbf(bf_hi(exy) * inv), rbf(bf_lo(ez) * inv)};
                const uint32_t* fr = Fw + (size_t)es * 128 + lane;
                const uint32_t fh = __ldcg(fr);
                const uint32_t q[3] = {__ldcg(fr + 32), __ldcg(fr + 64), __ldcg(fr + 96)};
                float ps0 = 0.f, ps1 = 0.f, pr0 = 0.f, pr1 = 0.f;
                for (int j2 = 0; j2 < 32; j2++) {
                    uint32_t hj = __shfl_sync(0xffffffffu, fh, j2);
                    uint32_t a0 = *(const uint32_t*)(p.w2 + (2 * j2) * 192 + 2 * lane), a1 = *(const uint32_t*)(p.w2 + (2 * j2 + 1) * 192 + 2 * lane);
                    uint32_t b0 = *(const uint32_t*)(p.w2 + (2 * j2) * 192 + 128 + 2 * lane), b1 = *(const uint32_t*)(p.w2 + (2 * j2 + 1) * 192 + 128 + 2 * lane);
                    ps0 += bf_lo(hj) * bf_lo(a0) + bf_hi(hj) * bf_lo(a1);
                    ps1 += bf_lo(hj) * bf_hi(a0) + bf_hi(hj) * bf_hi(a1);
                    pr0 += bf_lo(hj) * bf_lo(b0) + bf_hi(hj) * bf_lo(b1);
                    pr1 += bf_lo(hj) * bf_hi(b0) + bf_hi(hj) * bf_hi(b1);
                }
                float ws0 = 0.f, ws1 = 0.f, wv0 = 0.f, wv1 = 0.f, wr0 = 0.f, wr1 = 0.f;
                for (int k2 = 0; k2 < 8; k2++) {
                    uint32_t rk2 = __ldcg(tabg + (edb - D_MIN_BITS) * 8 + k2);
#pragma unroll
                    for (int h = 0; h < 2; h++) {
                        float rv = h ? bf_hi(rk2) : bf_lo(rk2);
                        const __nv_bfloat16* wrow = p.wr + (2 * k2 + h) * 192 + 2 * lane;
                        uint32_t a = *(const uint32_t*)wrow, b = *(const uint32_t*)(wrow + 64), c = *(const uint32_t*)(wrow + 128);
                        ws0 += rv * bf_lo(a); ws1 += rv * bf_hi(a);
                        wv0 += rv * bf_lo(b); wv1 += rv * bf_hi(b);
                        wr0 += rv * bf_lo(c); wr1 += rv * bf_hi(c);
                    }
                }
                float* a = acc + (ed - node0) * 256 + 2 * lane;
                atomicAdd(a, ps0 * ws0); atomicAdd(a + 1, ps1 * ws1);
#pragma unroll
                for (int c = 0; c < 3; c++) {
                    atomicAdd(a + 64 * (c + 1), wv0 * bf_lo(q[c]) + pr0 * wr0 * rh[c]);
                    atomicAdd(a + 64 * (c + 1) + 1, wv1 * bf_hi(q[c]) + pr1 * wr1 * rh[c]);
                }
            }
        }
        __syncthreads();
        for (int i = tid; i < nnodes * 128; i += NT) {
            uint32_t r = *(const uint32_t*)(p.sv + (size_t)node0 * 256 + 2 * i);
            *(uint32_t*)(p.out + (size_t)node0 * 256 + 2 * i) = pack_bf(bf_lo(r) + acc[2 * i], bf_hi(r) + acc[2 * i + 1]);
        }
        return;
    }

    const int slots = __reduce_max_sync(0xffffffffu, ctrl[4]);
    const int split = __reduce_max_sync(0xffffffffu, ctrl[2]);
    constexpr int nstage = MAX_STAGE;
    const uint32_t ring = sb + SM_RING;
    const int mid = __reduce_max_sync(0xffffffffu, split < nnodes ? (int)(nInfo[split] & 0xffffu) : slots) >> 4;
    const int wgi = warp >> 2, w = warp & 3;
    uint32_t wp[3][4];
    if (wgi < 3) {
        const uint16_t* wr = (const uint16_t*)p.wr + 16 * w + g;
#pragma unroll
        for (int ty = 0; ty < 3; ty++) {
#pragma unroll
            for (int i = 0; i < 4; i++) {
                const uint16_t* q = wr + (8 * (i >> 1) + 2 * t) * 192 + ty * 64 + 8 * (i & 1);
                wp[ty][i] = (uint32_t)__ldg(q) | ((uint32_t)__ldg(q + 192) << 16);
            }
        }
    }
    constexpr uint32_t EMPTY_OFF = NCWG * MAX_STAGE * 8;
    if (wgi == 3) {
        const int sc = w >> 1, r = w & 1;
        const int g0 = (sc == 0 ? 0 : mid) + r, g1 = sc == 0 ? mid : slots >> 4;
        const uint32_t ring_wg = ring + sc * nstage * STAGE_B, full_wg = bar_full + sc * MAX_STAGE * 8;
        const int e = lane >> 1, half = lane & 1;
        const uint32_t coef_off = e * 128 + ((half ^ (e & 7)) << 4);
        const int vrot = (e & 3) ^ ((e >> 1) & 3);
        const uint8_t* tab = (const uint8_t*)g_table + half * 16;
        int stage = r;
        uint32_t phase = 1;
        uint32_t ma = sb + SM_META + (g0 * 16 + e) * 8, ida = sb + SM_SID + g0 * 32;
        uint2 m = make_uint2(0u, 0u);
        uint4 tv = make_uint4(0u, 0u, 0u, 0u), ia = tv, ib = tv;
        if (g0 < g1) {
            m  = lds64(ma);
            ia = lds128(ida);
            ib = lds128(ida + 16);
            tv = __ldg((const uint4*)(tab + (m.x & 0xffffu)));
        }
        for (int left = (g1 - g0 + 1) >> 1; left > 0; left--) {
            const uint32_t st = ring_wg + stage * STAGE_B, fb = full_wg + stage * 8;
            ma += 256; ida += 64;
            uint2 mn = m;
            if (left > 1) mn = lds64(ma);
            mbar_wait(fb + EMPTY_OFF, phase);
            uint32_t leader;
            asm volatile("{\n.reg .pred p;\nelect.sync _|p, 0xffffffff;\nselp.u32 %0, 1, 0, p;\n}" : "=r"(leader));
            if (leader) {
                const uint32_t id2[8] = {ia.x, ia.y, ia.z, ia.w, ib.x, ib.y, ib.z, ib.w};
                const uint32_t rows = st + 2048;
                if ((ib.w >> 16) != 0xffffu) {
                    mbar_expect_tx(fb, 16 * 512);
#pragma unroll
                    for (int i = 0; i < 8; i++) {
                        tma_load(rows + (2 * i) * 640, &tmF, (int)(id2[i] & 0xffffu), fb);
                        tma_load(rows + (2 * i + 1) * 640, &tmF, (int)(id2[i] >> 16), fb);
                    }
                } else {
                    int nv = 0;
#pragma unroll
                    for (int i = 0; i < 8; i++) nv += ((id2[i] & 0xffffu) != 0xffffu) + ((id2[i] >> 16) != 0xffffu);
                    mbar_expect_tx(fb, (uint32_t)nv * 512u);
#pragma unroll
                    for (int q = 0; q < 4; q++) {
                        if (4 * q + 4 <= nv) {
                            tma_load(rows + (4 * q) * 640, &tmF, (int)(id2[2 * q] & 0xffffu), fb);
                            tma_load(rows + (4 * q + 1) * 640, &tmF, (int)(id2[2 * q] >> 16), fb);
                            tma_load(rows + (4 * q + 2) * 640, &tmF, (int)(id2[2 * q + 1] & 0xffffu), fb);
                            tma_load(rows + (4 * q + 3) * 640, &tmF, (int)(id2[2 * q + 1] >> 16), fb);
                        } else {
                            if (4 * q < nv)     tma_load(rows + (4 * q) * 640, &tmF, (int)(id2[2 * q] & 0xffffu), fb);
                            if (4 * q + 1 < nv) tma_load(rows + (4 * q + 1) * 640, &tmF, (int)(id2[2 * q] >> 16), fb);
                            if (4 * q + 2 < nv) tma_load(rows + (4 * q + 2) * 640, &tmF, (int)(id2[2 * q + 1] & 0xffffu), fb);
                        }
                    }
                }
            }
            __syncwarp();
            uint4 o[4];
            {
                const uint32_t mul[4] = {0x3f803f80u, __byte_perm(m.y, 0, 0x1010), __byte_perm(m.y, 0, 0x3232), __byte_perm(m.x, 0, 0x3232)};
#pragma unroll
                for (int j = 0; j < 4; j++) {
                    const int v = j ^ vrot;
                    const uint32_t lo = (v & 1) ? mul[1] : mul[0], hi = (v & 1) ? mul[3] : mul[2];
                    const uint32_t mm = (v & 2) ? hi : lo;
                    o[j] = make_uint4(hmul2(tv.x, mm), hmul2(tv.y, mm), hmul2(tv.z, mm), hmul2(tv.w, mm));
                }
            }
            m = mn;
            if (left > 1) {
                ia = lds128(ida);
                ib = lds128(ida + 16);
                tv = __ldg((const uint4*)(tab + (m.x & 0xffffu)));
            }
            const uint32_t a = st + coef_off;
#pragma unroll
            for (int j = 0; j < 4; j++) sts128(a ^ ((j ^ vrot) << 5), o[j]);
            fence_async_smem();
            __syncwarp();
            mbar_arrive_elected(fb);
            stage += 2;
            if (stage >= nstage) { stage -= nstage; phase ^= 1; }
        }
    } else if (wgi == 2) {
        uint32_t wA[2][4][4];
        {
            const uint16_t* w2 = (const uint16_t*)p.w2 + 16 * w + g;
#pragma unroll
            for (int mk = 0; mk < 8; mk++) {
#pragma unroll
                for (int i = 0; i < 4; i++) {
                    const uint16_t* q = w2 + (16 * (mk & 3) + 2 * t + 8 * (i >> 1)) * 192 + (mk >> 2) * 128 + 8 * (i & 1);
                    wA[mk >> 2][mk & 3][i] = (uint32_t)__ldg(q) | ((uint32_t)__ldg(q + 192) << 16);
                }
            }
        }
        const uint32_t lane_off = (uint32_t)node0 * 512u + t * 128 + w * 32 + (g & 1) * 16 + (g >> 1) * 4;
        uint32_t hcnt[2] = {0u, 0u};
        float zs[8], zv[24], pvv[6], pr[4][2];
        uint32_t hbuf = 0;
        auto start = [&](int ent) {
            const int c = ent >> 7;
            const uint32_t k = c ? hcnt[1] : hcnt[0];
            hbuf = 2 * c + (k & 1);
            mbar_wait(bar_hfull + hbuf * 8, (k >> 1) & 1);
            if (c) hcnt[1]++; else hcnt[0]++;
            const uint32_t dht = desc_lo(sb + SM_HT + hbuf * 8192);
            wg_fence();
            wgmma_n16_first(zs, wA[0][0], dht);
            wgmma_n48_first(zv, wA[1][0], dht + 2);
#pragma unroll
            for (int ks = 1; ks < 4; ks++) {
                wgmma_n16(zs, wA[0][ks], dht + ks * 128);
                wgmma_n48(zv, wA[1][ks], dht + ks * 128 + 2);
            }
            wg_commit();
        };
        auto side = [&](int ent) {
            const uint32_t pa = sb + SM_PV + hbuf * 1536 + (tid & 127) * 4;
            const uint32_t a0 = lds32(pa), a1 = lds32(pa + 512), a2 = lds32(pa + 1024);
            pvv[0] = bf_lo(a0); pvv[1] = bf_hi(a0); pvv[2] = bf_lo(a1); pvv[3] = bf_hi(a1); pvv[4] = bf_lo(a2); pvv[5] = bf_hi(a2);
            __syncwarp();
            mbar_arrive_elected(bar_hempty + hbuf * 8);
        };
        auto weigh = [&]() {
#pragma unroll
            for (int i = 0; i < 12; i++) asm volatile("" : "+r"(wp[i >> 2][i & 3]));
            pr[0][0] = bf_lo(wp[0][0]) * zs[0] + bf_hi(wp[0][0]) * zs[1] + bf_lo(wp[0][2]) * zs[4] + bf_hi(wp[0][2]) * zs[5];
            pr[0][1] = bf_lo(wp[0][1]) * zs[2] + bf_hi(wp[0][1]) * zs[3] + bf_lo(wp[0][3]) * zs[6] + bf_hi(wp[0][3]) * zs[7];
#pragma unroll
            for (int a = 0; a < 3; a++) {
                const float* y = zv + 8 * a;
                pr[a + 1][0] = pvv[2 * a] + bf_lo(wp[2][0]) * y[0] + bf_hi(wp[2][0]) * y[1] + bf_lo(wp[2][2]) * y[4] + bf_hi(wp[2][2]) * y[5];
                pr[a + 1][1] = pvv[2 * a + 1] + bf_lo(wp[2][1]) * y[2] + bf_hi(wp[2][1]) * y[3] + bf_lo(wp[2][3]) * y[6] + bf_hi(wp[2][3]) * y[7];
            }
            asm volatile("" : "+f"(pr[0][0]), "+f"(pr[0][1]), "+f"(pr[1][0]), "+f"(pr[1][1]), "+f"(pr[2][0]), "+f"(pr[2][1]), "+f"(pr[3][0]), "+f"(pr[3][1]) :: "memory");
        };
        auto finish = [&](int ent, uint32_t resid) {
            const bool hi2 = t & 2, hi1 = t & 1, odd = g & 1;
            float ka0 = hi2 ? pr[2][0] : pr[0][0], ka1 = hi2 ? pr[2][1] : pr[0][1];
            float kb0 = hi2 ? pr[3][0] : pr[1][0], kb1 = hi2 ? pr[3][1] : pr[1][1];
            float sa0 = hi2 ? pr[0][0] : pr[2][0], sa1 = hi2 ? pr[0][1] : pr[2][1];
            float sb0 = hi2 ? pr[1][0] : pr[3][0], sb1 = hi2 ? pr[1][1] : pr[3][1];
            ka0 += __shfl_xor_sync(0xffffffffu, sa0, 2); ka1 += __shfl_xor_sync(0xffffffffu, sa1, 2);
            kb0 += __shfl_xor_sync(0xffffffffu, sb0, 2); kb1 += __shfl_xor_sync(0xffffffffu, sb1, 2);
            float k0 = hi1 ? kb0 : ka0, k1 = hi1 ? kb1 : ka1;
            float s0 = hi1 ? ka0 : kb0, s1 = hi1 ? ka1 : kb1;
            k0 += __shfl_xor_sync(0xffffffffu, s0, 1);
            k1 += __shfl_xor_sync(0xffffffffu, s1, 1);
            const float other = __shfl_xor_sync(0xffffffffu, odd ? k0 : k1, 4);
            const float lo = odd ? other : k0, hi = odd ? k1 : other;
            *(uint32_t*)((uint8_t*)p.out + (lane_off + (uint32_t)(ent & 127) * 512u)) = pack_bf(bf_lo(resid) + lo, bf_hi(resid) + hi);
        };
        auto entry = [&](int i) -> int { return __reduce_max_sync(0xffffffffu, (int)smem[SM_ORDER + i]); };
        auto load_resid = [&](int ent) -> uint32_t { return __ldg((const uint32_t*)((const uint8_t*)p.sv + (lane_off + (uint32_t)(ent & 127) * 512u))); };
        if (nnodes > 0) {
            int cur = entry(0), nxt = entry(1);
            uint32_t resid = load_resid(cur);
            start(cur);
#pragma unroll 1
            for (int i = 1; i < nnodes; i++) {
                wg_wait0();
                side(cur);
                weigh();
                start(nxt);
                finish(cur, resid);
                cur = nxt;
                resid = load_resid(cur);
                nxt = entry(i + 1);
            }
            wg_wait0();
            side(cur);
            weigh();
            finish(cur, resid);
        }
    } else {
        const int wg = wgi;
        uint32_t aoff[4];
        {
            const int e = (lane & 7) + 8 * (lane >> 4), ch = 2 * w + ((lane >> 3) & 1);
#pragma unroll
            for (int b = 0; b < 4; b++) aoff[b] = 2048 + e * 640 + b * 128 + ((ch ^ ((5 * e + b) & 7)) << 4);
        }
        const uint32_t stsm_0 = sb + SM_HT + wg * 16384 + (16 * w + (lane & 15)) * 128 + (((lane >> 4) ^ (lane & 7)) << 4);
        const uint32_t pv_0 = sb + SM_PV + wg * 3072 + (tid & 127) * 4;
        uint32_t hk = 0;
        const uint32_t ring_wg = ring + wg * nstage * STAGE_B;
        const uint32_t full_wg = bar_full + wg * MAX_STAGE * 8;

        float ys[8], yv[24], dQ[3][8];
        uint32_t A0[4][4], A1[4][4];
#pragma unroll
        for (int i = 0; i < 24; i++) yv[i] = 0.f;
#pragma unroll
        for (int i = 0; i < 8; i++) { ys[i] = 0.f; dQ[0][i] = 0.f; dQ[1][i] = 0.f; dQ[2][i] = 0.f; }
        int left = wg == 0 ? mid : (slots >> 4) - mid;
        int fstage = 0;
        uint32_t fphase = 0, fst = ring_wg, fbar = full_wg;
        uint32_t ninfo_a = sb + SM_NINFO + (wg == 0 ? 0 : split) * 4;
        int gi = 0, G = __reduce_max_sync(0xffffffffu, (int)(lds32(ninfo_a) >> 20));

        auto fetch = [&](uint32_t (&A)[4][4], uint32_t& bd, uint32_t& eb) {
            mbar_wait(fbar, fphase);
#pragma unroll
            for (int b = 0; b < 4; b++) ldsm4t(A[b], fst + aoff[b]);
            bd = desc_lo(fst);
            eb = fbar + EMPTY_OFF;
            fst += STAGE_B; fbar += 8;
            if (++fstage == nstage) { fstage = 0; fphase ^= 1; fst = ring_wg; fbar = full_wg; }
        };
        auto step = [&](uint32_t (&Ac)[4][4], uint32_t bdc, uint32_t ebc, uint32_t (&An)[4][4], uint32_t& bdn, uint32_t& ebn) {
            wg_fence();
            wgmma_n64_p(ys, yv, Ac[0], bdc, gi);
            wgmma_n16_p(dQ[0], Ac[1], bdc, gi);
            wgmma_n16_p(dQ[1], Ac[2], bdc, gi);
            wgmma_n16_p(dQ[2], Ac[3], bdc, gi);
            wg_commit();
            if (--left > 0) fetch(An, bdn, ebn);
            const bool last = ++gi == G;
            uint32_t info_next = 0;
            if (last) { ninfo_a += 4; info_next = lds32(ninfo_a); }
            wg_wait0();
            mbar_arrive_elected(ebc);
            if (last) {
                const uint32_t hb = hk & 1;
                mbar_wait(bar_hempty + (2 * wg + hb) * 8, ((hk >> 1) & 1) ^ 1);
                hk++;
                const uint32_t stsm_a = stsm_0 + hb * 8192, pv_a = pv_0 + hb * 1536;
                stsm4(stsm_a, pack_bf(ys[0], ys[1]), pack_bf(ys[2], ys[3]), pack_bf(ys[4], ys[5]), pack_bf(ys[6], ys[7]));
#pragma unroll
                for (int i = 0; i < 6; i += 2) {
                    stsm4(stsm_a ^ ((i + 2) << 4),
                          pack_bf(yv[4 * i], yv[4 * i + 1]), pack_bf(yv[4 * i + 2], yv[4 * i + 3]),
                          pack_bf(yv[4 * i + 4], yv[4 * i + 5]), pack_bf(yv[4 * i + 6], yv[4 * i + 7]));
                }
#pragma unroll
                for (int i = 0; i < 4; i++) asm volatile("" : "+r"(wp[1][i]));
#pragma unroll
                for (int a = 0; a < 3; a++) {
                    const float* q = dQ[a];
                    const float p0 = bf_lo(wp[1][0]) * q[0] + bf_hi(wp[1][0]) * q[1] + bf_lo(wp[1][2]) * q[4] + bf_hi(wp[1][2]) * q[5];
                    const float p1 = bf_lo(wp[1][1]) * q[2] + bf_hi(wp[1][1]) * q[3] + bf_lo(wp[1][3]) * q[6] + bf_hi(wp[1][3]) * q[7];
                    sts32(pv_a + a * 512, pack_bf(p0, p1));
                }
                fence_async_smem();
                __syncwarp();
                mbar_arrive_elected(bar_hfull + (2 * wg + hb) * 8);
                G = __reduce_max_sync(0xffffffffu, (int)(info_next >> 20));
                gi = 0;
            }
        };
        if (left > 0) {
            uint32_t bd0, eb0, bd1 = 0, eb1 = 0;
            fetch(A0, bd0, eb0);
            while (true) {
                step(A0, bd0, eb0, A1, bd1, eb1);
                if (left <= 0) break;
                step(A1, bd1, eb1, A0, bd0, eb0);
                if (left <= 0) break;
            }
        }
    }
    STAMP(8);
}

typedef CUresult (*EncodeFn)(CUtensorMap*, CUtensorMapDataType, cuuint32_t, void*, const cuuint64_t*, const cuuint64_t*,
                             const cuuint32_t*, const cuuint32_t*, CUtensorMapInterleave, CUtensorMapSwizzle,
                             CUtensorMapL2promotion, CUtensorMapFloatOOBfill);

void make_map(EncodeFn enc, CUtensorMap* tm, const void* base, uint64_t lines, uint32_t box) {
    cuuint64_t gd[2] = {64, lines};
    cuuint64_t gs[1] = {128};
    cuuint32_t bd[2] = {64, box};
    cuuint32_t es[2] = {1, 1};
    enc(tm, CU_TENSOR_MAP_DATA_TYPE_BFLOAT16, 2, const_cast<void*>(base), gd, gs, bd, es, CU_TENSOR_MAP_INTERLEAVE_NONE,
        CU_TENSOR_MAP_SWIZZLE_128B, CU_TENSOR_MAP_L2_PROMOTION_L2_128B, CU_TENSOR_MAP_FLOAT_OOB_FILL_NONE);
}

void make_map3(EncodeFn enc, CUtensorMap* tm, const void* base, uint64_t nodes, uint32_t box) {
    cuuint64_t gd[3] = {64, 4, nodes};
    cuuint64_t gs[2] = {128, 512};
    cuuint32_t bd[3] = {64, 1, box};
    cuuint32_t es[3] = {1, 1, 1};
    enc(tm, CU_TENSOR_MAP_DATA_TYPE_BFLOAT16, 3, const_cast<void*>(base), gd, gs, bd, es, CU_TENSOR_MAP_INTERLEAVE_NONE,
        CU_TENSOR_MAP_SWIZZLE_128B, CU_TENSOR_MAP_L2_PROMOTION_L2_128B, CU_TENSOR_MAP_FLOAT_OOB_FILL_NONE);
}

}

extern "C" void kernel_launch(void* const* d_in, const int* in_sizes, int n_in, void* d_out, int out_size) {
    (void)n_in; (void)out_size;
    static int n_sm = 0;
    static EncodeFn enc = nullptr;
    static void* f_ptr = nullptr;
    if (n_sm == 0) {
        int dev = 0;
        cudaGetDevice(&dev);
        cudaDeviceGetAttribute(&n_sm, cudaDevAttrMultiProcessorCount, dev);
        cudaFuncSetAttribute(painn_kernel, cudaFuncAttributeMaxDynamicSharedMemorySize, SM_TOTAL);
        void* fn = nullptr;
        cudaDriverEntryPointQueryResult qr;
        cudaGetDriverEntryPoint("cuTensorMapEncodeTiled", &fn, cudaEnableDefault, &qr);
        enc = (EncodeFn)fn;
        cudaGetSymbolAddress(&f_ptr, g_F);
    }
    Params p;
    p.sv    = (const __nv_bfloat16*)d_in[0];
    p.pos   = (const __nv_bfloat16*)d_in[1];
    p.src   = (const int*)d_in[2];
    p.dst   = (const int*)d_in[3];
    p.freqs = (const __nv_bfloat16*)d_in[4];
    p.w1    = (const __nv_bfloat16*)d_in[5];
    p.w2    = (const __nv_bfloat16*)d_in[6];
    p.wr    = (const __nv_bfloat16*)d_in[7];
    p.out   = (__nv_bfloat16*)d_out;
    p.N = in_sizes[1] / 3;
    p.E = in_sizes[2];
    p.ncta = n_sm < MAX_CTA ? n_sm : MAX_CTA;
    p.npc = ((p.N + p.ncta - 1) / p.ncta + 3) & ~3;
    p.npc_magic = (uint32_t)(0x100000000ull / (uint32_t)p.npc) + 1u;
    p.quads_per_cta = ((p.E >> 2) + p.ncta - 1) / p.ncta;
    if (!enc || p.N > MAX_N || p.npc > MAX_NPC || (p.E & 3) || p.quads_per_cta > MAX_ROUNDS * 32) return;

    CUtensorMap tmF, tmFs;
    make_map(enc, &tmF, f_ptr, (uint64_t)p.N * 4, 4);
    make_map3(enc, &tmFs, f_ptr, (uint64_t)p.N, 4);

    cudaLaunchConfig_t cfg = {};
    cfg.gridDim = dim3(p.ncta);
    cfg.blockDim = dim3(NT);
    cfg.dynamicSmemBytes = SM_TOTAL;
    cfg.stream = cudaStreamPerThread;
    cudaLaunchAttribute attr[1];
    attr[0].id = cudaLaunchAttributeCooperative;
    attr[0].val.cooperative = 1;
    cfg.attrs = attr;
    cfg.numAttrs = 1;
    cudaLaunchKernelEx(&cfg, painn_kernel, p, tmF, tmFs);
}
```

```cpp
#include <cuda_runtime.h>
#include <cuda.h>
#include <cuda_bf16.h>
#include <stdint.h>

namespace {

constexpr int NT        = 512;
constexpr int NCWG      = 2;
constexpr int MAX_N     = 10240;
constexpr int MAX_CTA   = 136;
constexpr int MAX_NPC   = 80;
constexpr int MAX_ROUNDS = 38;
constexpr int SEG_CAP   = 64;
constexpr int SLOT_CAP  = 6144;
constexpr int MAX_STAGE = 5;
constexpr int STAGE_B   = 12288;

constexpr uint32_t D_MIN_BITS = 0x38D2;
constexpr uint32_t D_MAX_BITS = 0x409C;
constexpr int TAB_ROWS  = (int)(D_MAX_BITS - D_MIN_BITS) + 1;
constexpr int TAB_ZERO  = TAB_ROWS;
constexpr int TAB_BYTES = (TAB_ROWS + 1) * 32;

constexpr int SM_BINCNT = 0;
constexpr int SM_NCNT   = SM_BINCNT + MAX_CTA * 4;
constexpr int SM_NINFO  = SM_NCNT + MAX_NPC * 4;
constexpr int SM_ORDER  = SM_NINFO + (MAX_NPC + 1) * 4;
constexpr int SM_HALF   = SM_ORDER + MAX_NPC + 12;
constexpr int SM_CTRL   = SM_HALF + 56;
constexpr int SM_BARS   = SM_CTRL + 64;
constexpr int SM_SID    = 2048 + 256;
constexpr int SM_META   = SM_SID + SLOT_CAP * 2;
constexpr int SM_TOTAL  = 232448;
constexpr int SM_HT     = (SM_TOTAL - 4 * 8192 - 4 * 1536) / 1024 * 1024;
constexpr int SM_PV     = SM_HT + 4 * 8192;
constexpr int SM_RING   = SM_HT - NCWG * MAX_STAGE * STAGE_B;
constexpr int P1_POS    = 3072;
constexpr int P1_SEGA   = P1_POS + 61440;
constexpr int P1_SEGB   = P1_SEGA + MAX_CTA * SEG_CAP * 8;
constexpr int P1_SV     = P1_SEGB + MAX_CTA * SEG_CAP * 4;
constexpr int P1_W1     = P1_SV + 4 * MAX_NPC * 128;
constexpr int P1_W2     = P1_W1 + 8192;
constexpr int P1_END    = P1_W2 + 8192;
constexpr int P1_REC    = P1_SEGA;
constexpr int STAGE_CAP = (P1_SV - P1_REC) / 16;
static_assert(SM_BARS + (12 + 2 * NCWG * MAX_STAGE) * 8 <= SM_SID, "misc block");
static_assert(SM_BARS + 256 <= P1_POS, "misc block");
static_assert(P1_END <= SM_TOTAL && P1_SV % 1024 == 0 && P1_REC % 16 == 0, "phase 1 overlay");
static_assert(SM_META + SLOT_CAP * 8 <= SM_RING && SM_PV + 4 * 1536 <= SM_TOTAL, "CSR");
static_assert(SM_RING % 1024 == 0 && SM_HT % 1024 == 0, "alignment");
static_assert(SM_BARS % 8 == 0 && SM_META % 8 == 0 && SM_CTRL % 4 == 0, "alignment");
static_assert(MAX_N * 6 <= 61440, "pos");
static_assert(SM_RING >= P1_SEGA && SM_HT <= P1_END, "every byte of the stages is written (finite) during phase 1");
static_assert(SM_SID + MAX_NPC * 1024 <= SM_TOTAL, "slow path accumulators");

__device__ __align__(1024) uint4 g_F[MAX_N * 32];
__device__ __align__(128) uint32_t g_seg[MAX_CTA * MAX_CTA * SEG_CAP * 3];
__device__ uint4    g_table[(TAB_BYTES + 15) / 16];
__device__ unsigned g_bar[2];
#define STAMP(k)
#define STAMPT(k, T)

struct Params {
    const __nv_bfloat16* sv;
    const __nv_bfloat16* pos;
    const int*           src;
    const int*           dst;
    const __nv_bfloat16* freqs;
    const __nv_bfloat16* w1;
    const __nv_bfloat16* w2;
    const __nv_bfloat16* wr;
    __nv_bfloat16*       out;
    int N, E, ncta, npc;
    uint32_t npc_magic;
    int quads_per_cta;
};

__device__ __forceinline__ uint32_t smem_u32(const void* p) { return (uint32_t)__cvta_generic_to_shared(p); }
__device__ __forceinline__ float bf_lo(uint32_t v) { return __uint_as_float(v << 16); }
__device__ __forceinline__ float bf_hi(uint32_t v) { return __uint_as_float(v & 0xffff0000u); }
__device__ __forceinline__ uint32_t pack_bf(float lo, float hi) {
    uint32_t r;
    asm("cvt.rn.bf16x2.f32 %0, %1, %2;" : "=r"(r) : "f"(hi), "f"(lo));
    return r;
}
__device__ __forceinline__ float rbf(float x) { return bf_lo(pack_bf(x, 0.f)); }
__device__ __forceinline__ uint32_t hmul2(uint32_t a, uint32_t b) {
    uint32_t r;
    asm("mul.rn.bf16x2 %0, %1, %2;" : "=r"(r) : "r"(a), "r"(b));
    return r;
}
__device__ __forceinline__ uint32_t hsub2(uint32_t a, uint32_t b) {
    uint32_t r;
    asm("sub.rn.bf16x2 %0, %1, %2;" : "=r"(r) : "r"(a), "r"(b));
    return r;
}
__device__ __forceinline__ uint32_t lds32(uint32_t a) { uint32_t v; asm volatile("ld.shared.u32 %0, [%1];" : "=r"(v) : "r"(a)); return v; }
__device__ __forceinline__ uint2 lds64(uint32_t a) { uint2 v; asm volatile("ld.shared.v2.u32 {%0,%1}, [%2];" : "=r"(v.x), "=r"(v.y) : "r"(a)); return v; }
__device__ __forceinline__ uint4 lds128(uint32_t a) { uint4 v; asm volatile("ld.shared.v4.u32 {%0,%1,%2,%3}, [%4];" : "=r"(v.x), "=r"(v.y), "=r"(v.z), "=r"(v.w) : "r"(a)); return v; }
__device__ __forceinline__ void sts32(uint32_t a, uint32_t v) { asm volatile("st.shared.u32 [%0], %1;" ::"r"(a), "r"(v) : "memory"); }
__device__ __forceinline__ void sts128(uint32_t a, uint4 v) { asm volatile("st.shared.v4.u32 [%0], {%1,%2,%3,%4};" ::"r"(a), "r"(v.x), "r"(v.y), "r"(v.z), "r"(v.w) : "memory"); }
__device__ __forceinline__ void mbar_init(uint32_t bar, int cnt) { asm volatile("mbarrier.init.shared::cta.b64 [%0], %1;" ::"r"(bar), "r"(cnt) : "memory"); }
__device__ __forceinline__ void mbar_expect_tx(uint32_t bar, uint32_t bytes) { asm volatile("mbarrier.arrive.expect_tx.shared::cta.b64 _, [%0], %1;" ::"r"(bar), "r"(bytes) : "memory"); }
__device__ __forceinline__ void mbar_wait(uint32_t bar, uint32_t parity) {
    asm volatile("{\n.reg .pred p;\n.reg .u32 c;\n"
                 "mbarrier.try_wait.parity.shared::cta.b64 p, [%0], %1;\n"
                 "@p bra DONE_%=;\n"
                 "mov.u32 c, 0;\n"
                 "LOOP_%=:\n"
                 "mbarrier.try_wait.parity.shared::cta.b64 p, [%0], %1;\n"
                 "@p bra DONE_%=;\n"
                 "add.u32 c, c, 1;\n"
                 "setp.lt.u32 p, c, 4194304;\n"
                 "@p bra LOOP_%=;\n"
                 "DONE_%=:\n}"
                 ::"r"(bar), "r"(parity) : "memory");
}
__device__ __forceinline__ void mbar_arrive_elected(uint32_t bar) {
    asm volatile("{\n.reg .pred p;\nelect.sync _|p, 0xffffffff;\n@p mbarrier.arrive.shared::cta.b64 _, [%0];\n}" ::"r"(bar) : "memory");
}
__device__ __forceinline__ void bulk_g2s(uint32_t dst, const void* src, uint32_t bytes, uint32_t bar) {
    asm volatile("cp.async.bulk.shared::cluster.global.mbarrier::complete_tx::bytes [%0], [%1], %2, [%3];"
                 ::"r"(dst), "l"(src), "r"(bytes), "r"(bar) : "memory");
}
__device__ __forceinline__ void cp_async16(uint32_t dst, const void* src) {
    asm volatile("cp.async.cg.shared.global [%0], [%1], 16;" ::"r"(dst), "l"(src) : "memory");
}
__device__ __forceinline__ void tma_load(uint32_t dst, const CUtensorMap* tm, int line, uint32_t bar) {
    asm volatile("cp.async.bulk.tensor.2d.shared::cluster.global.mbarrier::complete_tx::bytes [%0], [%1, {%3, %4}], [%2];"
                 ::"r"(dst), "l"(tm), "r"(bar), "r"(0), "r"(line) : "memory");
}
__device__ __forceinline__ void tma_store3(const CUtensorMap* tm, int comp, int node, uint32_t src) {
    asm volatile("cp.async.bulk.tensor.3d.global.shared::cta.bulk_group [%0, {%2, %3, %4}], [%1];"
                 ::"l"(tm), "r"(src), "r"(0), "r"(comp), "r"(node) : "memory");
}
__device__ __forceinline__ void fence_async_smem() { asm volatile("fence.proxy.async.shared::cta;" ::: "memory"); }
__device__ __forceinline__ void ldsm4(uint32_t (&r)[4], uint32_t a) {
    asm volatile("ldmatrix.sync.aligned.m8n8.x4.shared.b16 {%0,%1,%2,%3}, [%4];" : "=r"(r[0]), "=r"(r[1]), "=r"(r[2]), "=r"(r[3]) : "r"(a) : "memory");
}
__device__ __forceinline__ void ldsm4t(uint32_t (&r)[4], uint32_t a) {
    asm volatile("ldmatrix.sync.aligned.m8n8.x4.trans.shared.b16 {%0,%1,%2,%3}, [%4];" : "=r"(r[0]), "=r"(r[1]), "=r"(r[2]), "=r"(r[3]) : "r"(a) : "memory");
}
__device__ __forceinline__ void ldsm2t(uint32_t& r0, uint32_t& r1, uint32_t a) {
    asm volatile("ldmatrix.sync.aligned.m8n8.x2.trans.shared.b16 {%0,%1}, [%2];" : "=r"(r0), "=r"(r1) : "r"(a) : "memory");
}
__device__ __forceinline__ void stsm4(uint32_t a, uint32_t r0, uint32_t r1, uint32_t r2, uint32_t r3) {
    asm volatile("stmatrix.sync.aligned.m8n8.x4.shared.b16 [%0], {%1,%2,%3,%4};" ::"r"(a), "r"(r0), "r"(r1), "r"(r2), "r"(r3) : "memory");
}
__device__ __forceinline__ void mma16816(float (&c)[4], const uint32_t (&a)[4], uint32_t b0, uint32_t b1) {
    asm volatile("mma.sync.aligned.m16n8k16.row.col.f32.bf16.bf16.f32 {%0,%1,%2,%3}, {%4,%5,%6,%7}, {%8,%9}, {%0,%1,%2,%3};"
                 : "+f"(c[0]), "+f"(c[1]), "+f"(c[2]), "+f"(c[3])
                 : "r"(a[0]), "r"(a[1]), "r"(a[2]), "r"(a[3]), "r"(b0), "r"(b1));
}

__device__ __forceinline__ uint32_t desc_lo(uint32_t saddr) { return ((saddr & 0x3FFFF) >> 4) | (1u << 16); }
#define DESC_HI "0x40000040"
__device__ __forceinline__ void wg_fence() { asm volatile("wgmma.fence.sync.aligned;" ::: "memory"); }
__device__ __forceinline__ void wg_commit() { asm volatile("wgmma.commit_group.sync.aligned;" ::: "memory"); }
__device__ __forceinline__ void wg_wait0() { asm volatile("wgmma.wait_group.sync.aligned 0;" ::: "memory"); }

__device__ __forceinline__ void wgmma_n48_first(float (&e)[24], const uint32_t (&a)[4], uint32_t bdesc) {
    asm volatile("{\n.reg .b64 b;\nmov.b64 b, {%28, " DESC_HI "};\n"
                 "wgmma.mma_async.sync.aligned.m64n48k16.f32.bf16.bf16 {%0,%1,%2,%3,%4,%5,%6,%7,%8,%9,%10,%11,%12,%13,%14,%15,%16,%17,%18,%19,%20,%21,%22,%23}, {%24,%25,%26,%27}, b, 0, 1, 1, 1;\n}"
                 : "=f"(e[0]), "=f"(e[1]), "=f"(e[2]), "=f"(e[3]), "=f"(e[4]), "=f"(e[5]), "=f"(e[6]), "=f"(e[7]), "=f"(e[8]), "=f"(e[9]), "=f"(e[10]), "=f"(e[11]), "=f"(e[12]), "=f"(e[13]), "=f"(e[14]), "=f"(e[15]), "=f"(e[16]), "=f"(e[17]), "=f"(e[18]), "=f"(e[19]), "=f"(e[20]), "=f"(e[21]), "=f"(e[22]), "=f"(e[23])
                 : "r"(a[0]), "r"(a[1]), "r"(a[2]), "r"(a[3]), "r"(bdesc));
}
__device__ __forceinline__ void wgmma_n48(float (&e)[24], const uint32_t (&a)[4], uint32_t bdesc) {
    asm volatile("{\n.reg .b64 b;\nmov.b64 b, {%28, " DESC_HI "};\n"
                 "wgmma.mma_async.sync.aligned.m64n48k16.f32.bf16.bf16 {%0,%1,%2,%3,%4,%5,%6,%7,%8,%9,%10,%11,%12,%13,%14,%15,%16,%17,%18,%19,%20,%21,%22,%23}, {%24,%25,%26,%27}, b, 1, 1, 1, 1;\n}"
                 : "+f"(e[0]), "+f"(e[1]), "+f"(e[2]), "+f"(e[3]), "+f"(e[4]), "+f"(e[5]), "+f"(e[6]), "+f"(e[7]), "+f"(e[8]), "+f"(e[9]), "+f"(e[10]), "+f"(e[11]), "+f"(e[12]), "+f"(e[13]), "+f"(e[14]), "+f"(e[15]), "+f"(e[16]), "+f"(e[17]), "+f"(e[18]), "+f"(e[19]), "+f"(e[20]), "+f"(e[21]), "+f"(e[22]), "+f"(e[23])
                 : "r"(a[0]), "r"(a[1]), "r"(a[2]), "r"(a[3]), "r"(bdesc));
}
__device__ __forceinline__ void wgmma_n16_first(float (&d)[8], const uint32_t (&a)[4], uint32_t bdesc) {
    asm volatile("{\n.reg .b64 b;\nmov.b64 b, {%12, " DESC_HI "};\n"
                 "wgmma.mma_async.sync.aligned.m64n16k16.f32.bf16.bf16 {%0,%1,%2,%3,%4,%5,%6,%7}, {%8,%9,%10,%11}, b, 0, 1, 1, 1;\n}"
                 : "=f"(d[0]), "=f"(d[1]), "=f"(d[2]), "=f"(d[3]), "=f"(d[4]), "=f"(d[5]), "=f"(d[6]), "=f"(d[7])
                 : "r"(a[0]), "r"(a[1]), "r"(a[2]), "r"(a[3]), "r"(bdesc));
}
__device__ __forceinline__ void wgmma_n16(float (&d)[8], const uint32_t (&a)[4], uint32_t bdesc) {
    asm volatile("{\n.reg .b64 b;\nmov.b64 b, {%12, " DESC_HI "};\n"
                 "wgmma.mma_async.sync.aligned.m64n16k16.f32.bf16.bf16 {%0,%1,%2,%3,%4,%5,%6,%7}, {%8,%9,%10,%11}, b, 1, 1, 1, 1;\n}"
                 : "+f"(d[0]), "+f"(d[1]), "+f"(d[2]), "+f"(d[3]), "+f"(d[4]), "+f"(d[5]), "+f"(d[6]), "+f"(d[7])
                 : "r"(a[0]), "r"(a[1]), "r"(a[2]), "r"(a[3]), "r"(bdesc));
}

__device__ __forceinline__ void wgmma_n64_p(float (&d)[8], float (&e)[24], const uint32_t (&a)[4], uint32_t bdesc, int acc) {
    asm volatile("{\n.reg .pred p;\n.reg .b64 b;\nsetp.ne.b32 p, %37, 0;\nmov.b64 b, {%36, " DESC_HI "};\n"
                 "wgmma.mma_async.sync.aligned.m64n64k16.f32.bf16.bf16 {%0,%1,%2,%3,%4,%5,%6,%7,%8,%9,%10,%11,%12,%13,%14,%15,%16,%17,%18,%19,%20,%21,%22,%23,%24,%25,%26,%27,%28,%29,%30,%31}, {%32,%33,%34,%35}, b, p, 1, 1, 1;\n}"
                 : "+f"(d[0]), "+f"(d[1]), "+f"(d[2]), "+f"(d[3]), "+f"(d[4]), "+f"(d[5]), "+f"(d[6]), "+f"(d[7]),
                   "+f"(e[0]), "+f"(e[1]), "+f"(e[2]), "+f"(e[3]), "+f"(e[4]), "+f"(e[5]), "+f"(e[6]), "+f"(e[7]), "+f"(e[8]), "+f"(e[9]), "+f"(e[10]), "+f"(e[11]), "+f"(e[12]), "+f"(e[13]), "+f"(e[14]), "+f"(e[15]), "+f"(e[16]), "+f"(e[17]), "+f"(e[18]), "+f"(e[19]), "+f"(e[20]), "+f"(e[21]), "+f"(e[22]), "+f"(e[23])
                 : "r"(a[0]), "r"(a[1]), "r"(a[2]), "r"(a[3]), "r"(bdesc), "r"(acc));
}
__device__ __forceinline__ void wgmma_n16_p(float (&d)[8], const uint32_t (&a)[4], uint32_t bdesc, int acc) {
    asm volatile("{\n.reg .pred p;\n.reg .b64 b;\nsetp.ne.b32 p, %13, 0;\nmov.b64 b, {%12, " DESC_HI "};\n"
                 "wgmma.mma_async.sync.aligned.m64n16k16.f32.bf16.bf16 {%0,%1,%2,%3,%4,%5,%6,%7}, {%8,%9,%10,%11}, b, p, 1, 1, 1;\n}"
                 : "+f"(d[0]), "+f"(d[1]), "+f"(d[2]), "+f"(d[3]), "+f"(d[4]), "+f"(d[5]), "+f"(d[6]), "+f"(d[7])
                 : "r"(a[0]), "r"(a[1]), "r"(a[2]), "r"(a[3]), "r"(bdesc), "r"(acc));
}

__device__ __forceinline__ uint32_t edge_dist(uint32_t sxy, uint32_t sz, uint32_t dxy, uint32_t dz, uint32_t& rxy, uint32_t& rz) {
    rxy = hsub2(sxy, dxy);
    rz  = hsub2(sz, dz);
    uint32_t qxy = hmul2(rxy, rxy), qz = hmul2(rz, rz);
    float ss = rbf((bf_lo(qxy) + bf_hi(qxy)) + bf_lo(qz));
    float s2 = rbf(ss + 1e-8f);
    float d;
    asm("sqrt.approx.ftz.f32 %0, %1;" : "=f"(d) : "f"(s2));
    return pack_bf(d, 0.f) & 0xffffu;
}

__device__ __noinline__ float radial_value(float d, float f) {
    float arg = rbf(d * f);
    float sn  = rbf(sinf(arg));
    float rb  = rbf(__fdiv_rn(sn, d));
    float c   = rbf(cosf(rbf(__fdiv_rn(rbf(d * 3.14159265358979323846f), 5.0f))));
    float fc  = rbf(0.5f * rbf(c + 1.0f));
    return rb * fc;
}

__global__ void __launch_bounds__(NT, 1)
painn_kernel(const Params p, const __grid_constant__ CUtensorMap tmF, const __grid_constant__ CUtensorMap tmFs) {
    extern __shared__ __align__(1024) uint8_t smem[];
    const uint32_t sb   = smem_u32(smem);
    const int tid  = threadIdx.x, lane = tid & 31, warp = __shfl_sync(0xffffffffu, tid >> 5, 0);
    const int cta  = blockIdx.x;
    const int g    = lane >> 2, t = lane & 3;
    int* binCnt = (int*)(smem + SM_BINCNT);
    int* nCnt   = (int*)(smem + SM_NCNT);
    uint32_t* nInfo = (uint32_t*)(smem + SM_NINFO);
    volatile int* ctrl = (volatile int*)(smem + SM_CTRL);
    const uint32_t bar_pos = sb + SM_BARS;
    const uint32_t bar_full = bar_pos + 32, bar_empty = bar_full + NCWG * MAX_STAGE * 8;
    const uint32_t bar_hfull = bar_empty + NCWG * MAX_STAGE * 8, bar_hempty = bar_hfull + 32;

    const int node0  = cta * p.npc;
    const int nnodes = max(0, min(p.npc, p.N - node0));

    STAMP(0);
    if (tid == 32) {
        mbar_init(bar_pos, 1);
        asm volatile("fence.mbarrier_init.release.cluster;" ::: "memory");
        uint32_t pos_bytes = (uint32_t)(p.N * 6 + 15) & ~15u;
        mbar_expect_tx(bar_pos, pos_bytes);
        bulk_g2s(sb + P1_POS, p.pos, pos_bytes, bar_pos);
    } else if (tid == 64) {
        for (int i = 0; i < 4; i++) { mbar_init(bar_hfull + 8 * i, 4); mbar_init(bar_hempty + 8 * i, 4); }
        asm volatile("prefetch.tensormap [%0];" ::"l"(&tmF) : "memory");
        asm volatile("prefetch.tensormap [%0];" ::"l"(&tmFs) : "memory");
    } else if (tid >= 96 && tid < 96 + NCWG * MAX_STAGE) {
        mbar_init(bar_full + 8 * (tid - 96), 2);
        mbar_init(bar_empty + 8 * (tid - 96), 4);
    }
    unsigned bar_seen = 0;
    if (tid == 0 || tid == 32) asm volatile("ld.relaxed.gpu.global.u32 %0, [%1];" : "=r"(bar_seen) : "l"(&g_bar[tid >> 5]) : "memory");
    const bool mlp_warp = warp >= 6;
    int4 s4[3], d4[3];
    const int q0 = cta * p.quads_per_cta;
    const int qend = min(q0 + p.quads_per_cta, p.E >> 2);
#pragma unroll
    for (int k = 0; k < 3; k++) {
        const int q = q0 + (k < 2 ? warp + 16 * k : 32 + warp) * 32 + lane;
        const bool ok = q < qend && (k < 2 || !mlp_warp);
        s4[k] = ok ? __ldg((const int4*)p.src + q) : make_int4(-1, -1, -1, -1);
        d4[k] = ok ? __ldg((const int4*)p.dst + q) : make_int4(0, 0, 0, 0);
    }
    if (tid < MAX_CTA) binCnt[tid] = 0;
    if (tid < MAX_NPC) nCnt[tid] = 0;
    if (tid < 16) ctrl[tid] = 0;
    if (tid >= 32 && tid < 32 + 14) sts32(sb + SM_HALF + (tid - 32) * 4, 0u);
    if (tid >= 256 && tid < 256 + 240) {
        const int i = tid - 256;
        asm volatile("prefetch.global.L2 [%0];" ::"l"(i < 48 ? (const uint8_t*)p.wr + i * 128 : (const uint8_t*)p.w2 + (i - 48) * 128));
    }
    for (int i = P1_SEGA / 16 + tid; i < P1_SV / 16; i += NT) sts128(sb + i * 16, make_uint4(0u, 0u, 0u, 0u));
    for (int i = tid; i < 4 * (MAX_NPC - nnodes) * 8; i += NT)
        sts128(sb + P1_SV + (i / ((MAX_NPC - nnodes) * 8)) * (MAX_NPC * 128) + nnodes * 128 + (i % ((MAX_NPC - nnodes) * 8)) * 16, make_uint4(0u, 0u, 0u, 0u));
    __syncthreads();

    mbar_wait(bar_pos, 0);
    if (s4[0].x == 0x7fffffff) ctrl[15] = 1;
    for (int i = tid; i < nnodes * 32; i += NT) {
        const int r = i >> 5, b = (i >> 3) & 3, c = i & 7;
        cp_async16(sb + P1_SV + b * (MAX_NPC * 128) + r * 128 + ((c ^ (r & 7)) << 4), (const uint8_t*)p.sv + (size_t)node0 * 512 + i * 16);
    }
    for (int i = tid; i < 1024; i += NT) {
        const int m = i >> 9, k = (i >> 3) & 63, c = i & 7;
        cp_async16(sb + P1_W1 + m * 8192 + k * 128 + ((c ^ (k & 7)) << 4),
                   m == 0 ? (const uint8_t*)p.w1 + k * 128 + c * 16 : (const uint8_t*)p.w2 + k * 384 + 128 + c * 16);
    }
    asm volatile("cp.async.commit_group;" ::: "memory");
    STAMP(1);
#pragma unroll
    for (int k = 0; k < 3; k++) {
        const int ss[4] = {s4[k].x, s4[k].y, s4[k].z, s4[k].w};
        const int dd[4] = {d4[k].x, d4[k].y, d4[k].z, d4[k].w};
        if (ss[0] >= 0) {
            uint32_t w0[4], w1[4], v0[4], v1[4], r0[4], r1[4], r2[4], bin[4], rank[4];
#pragma unroll
            for (int j = 0; j < 4; j++) {
                const uint32_t a = (sb + P1_POS + 6u * (uint32_t)ss[j]) & ~3u, c = (sb + P1_POS + 6u * (uint32_t)dd[j]) & ~3u;
                w0[j] = lds32(a); w1[j] = lds32(a + 4); v0[j] = lds32(c); v1[j] = lds32(c + 4);
            }
#pragma unroll
            for (int j = 0; j < 4; j++) {
                const uint32_t sh = (uint32_t)ss[j] << 4, dh = (uint32_t)dd[j] << 4;
                uint32_t rxy, rz;
                const uint32_t db = edge_dist(__funnelshift_r(w0[j], w1[j], sh), __funnelshift_r(w1[j], w1[j], sh),
                                              __funnelshift_r(v0[j], v1[j], dh), __funnelshift_r(v1[j], v1[j], dh), rxy, rz);
                float inv;
                asm("rcp.approx.ftz.f32 %0, %1;" : "=f"(inv) : "f"(__uint_as_float(db << 16)));
                bin[j] = __umulhi((uint32_t)dd[j], p.npc_magic);
                r0[j] = (uint32_t)ss[j] | ((db - D_MIN_BITS) << 16);
                r1[j] = pack_bf(bf_lo(rxy) * inv, bf_hi(rxy) * inv);
                r2[j] = __byte_perm(pack_bf(bf_lo(rz) * inv, 0.f), (uint32_t)dd[j] - bin[j] * (uint32_t)p.npc, 0x5410);
                rank[j] = db <= D_MAX_BITS ? (uint32_t)atomicAdd(&binCnt[bin[j]], 1) : 0xffffu;
            }
#pragma unroll
            for (int j = 0; j < 4; j++) {
                if (rank[j] < SEG_CAP) {
                    const uint32_t slot = bin[j] * SEG_CAP + rank[j];
                    asm volatile("st.shared.v2.u32 [%0], {%1, %2};" ::"r"(sb + P1_SEGA + slot * 8), "r"(r0[j]), "r"(r1[j]) : "memory");
                    sts32(sb + P1_SEGB + slot * 4, r2[j]);
                }
            }
        }
    }
    __syncthreads();
    STAMP(2);
    {
        constexpr int IT = (MAX_CTA + 31) / 32;
        uint2 ca[IT][2];
        uint32_t cb[IT][2];
        int cn[IT];
#pragma unroll
        for (int it = 0; it < IT; it++) {
            const int b = min(2 * warp + (lane >> 4) + 32 * it, MAX_CTA - 1);
            cn[it] = binCnt[b];
#pragma unroll
            for (int u = 0; u < 2; u++) {
                const int j = (lane & 15) + 16 * u;
                ca[it][u] = lds64(sb + P1_SEGA + (b * SEG_CAP + j) * 8);
                cb[it][u] = lds32(sb + P1_SEGB + (b * SEG_CAP + j) * 4);
            }
        }
#pragma unroll
        for (int it = 0; it < IT; it++) {
            const int b = 2 * warp + (lane >> 4) + 32 * it;
            if (b < p.ncta) {
                uint32_t* dstp = g_seg + ((size_t)cta * MAX_CTA + b) * (SEG_CAP * 3);
                const uint32_t tag = (uint32_t)min(cn[it], 511) << 23;
#pragma unroll
                for (int u = 0; u < 2; u++) {
                    const int j = (lane & 15) + 16 * u;
                    *(uint2*)(dstp + 2 * j) = ca[it][u];
                    dstp[2 * SEG_CAP + j] = cb[it][u] | tag;
                }
                for (int j = 32 + (lane & 15); j < ((min(cn[it], SEG_CAP) + 7) & ~7); j += 16) {
                    *(uint2*)(dstp + 2 * j) = lds64(sb + P1_SEGA + (b * SEG_CAP + j) * 8);
                    dstp[2 * SEG_CAP + j] = lds32(sb + P1_SEGB + (b * SEG_CAP + j) * 4);
                }
            }
        }
    }
    STAMP(7);
    asm volatile("cp.async.wait_group 0;" ::: "memory");
    __syncthreads();
    STAMP(3);
    if (tid == 64) asm volatile("red.add.release.gpu.global.u32 [%0], 1;" ::"l"(&g_bar[0]) : "memory");

    if (!mlp_warp) {
        const int rows_per = (TAB_ROWS + 1 + p.ncta - 1) / p.ncta;
        for (int i = tid; i < rows_per * 8; i += 6 * 32) {
            int row = cta * rows_per + (i >> 3), kp = i & 7;
            if (row <= TAB_ROWS) {
                uint32_t val = 0;
                if (row < TAB_ROWS) {
                    float d = __uint_as_float((D_MIN_BITS + row) << 16);
                    uint32_t f2 = __ldg((const uint32_t*)p.freqs + kp);
                    val = pack_bf(radial_value(d, bf_lo(f2)), radial_value(d, bf_hi(f2)));
                }
                ((uint32_t*)g_table)[row * 8 + kp] = val;
            }
        }
    } else {
        const int mt = (warp - 6) >> 1, hf = (warp - 6) & 1;
        if (mt * 16 < nnodes) {
            STAMPT(10, 6 * 32);
            const int lrow = lane & 15, lch = lane >> 4;
            const uint32_t rowb = sb + P1_SV + (mt * 16 + lrow) * 128;
            const uint32_t key0 = lrow & 7;
            float acc[4][4];
#pragma unroll
            for (int i = 0; i < 4; i++) { acc[i][0] = acc[i][1] = acc[i][2] = acc[i][3] = 0.f; }
#pragma unroll
            for (int ks = 0; ks < 4; ks++) {
                uint32_t a[4];
                ldsm4(a, rowb + (((2 * ks + lch) ^ key0) << 4));
                const int kk = 16 * ks + lrow;
#pragma unroll
                for (int nt = 0; nt < 4; nt += 2) {
                    uint32_t b[4];
                    ldsm4t(b, sb + P1_W1 + kk * 128 + (((4 * hf + nt + lch) ^ (kk & 7)) << 4));
                    mma16816(acc[nt], a, b[0], b[1]);
                    mma16816(acc[nt + 1], a, b[2], b[3]);
                }
            }
            uint32_t hp[4][2];
#pragma unroll
            for (int i = 0; i < 4; i++) {
                float h[4];
#pragma unroll
                for (int q = 0; q < 4; q++) {
                    float x = rbf(acc[i][q]);
                    h[q] = __fdividef(x, 1.0f + __expf(-x));
                    acc[i][q] = 0.f;
                }
                hp[i][0] = pack_bf(h[0], h[1]);
                hp[i][1] = pack_bf(h[2], h[3]);
            }
            asm volatile("bar.sync %0, 64;" ::"r"(4 + mt) : "memory");
#pragma unroll
            for (int i = 0; i < 4; i += 2)
                stsm4(rowb + (((4 * hf + i + lch) ^ key0) << 4), hp[i][0], hp[i][1], hp[i + 1][0], hp[i + 1][1]);
            asm volatile("bar.sync %0, 64;" ::"r"(4 + mt) : "memory");
#pragma unroll
            for (int ks = 0; ks < 4; ks++) {
                uint32_t a[4];
                ldsm4(a, rowb + (((2 * ks + lch) ^ key0) << 4));
                const int kk = 16 * ks + lrow;
#pragma unroll
                for (int nt = 0; nt < 4; nt += 2) {
                    uint32_t b[4];
                    ldsm4t(b, sb + P1_W2 + kk * 128 + (((4 * hf + nt + lch) ^ (kk & 7)) << 4));
                    mma16816(acc[nt], a, b[0], b[1]);
                    mma16816(acc[nt + 1], a, b[2], b[3]);
                }
            }
            uint32_t vq[2][3][4];
            const uint32_t vb = sb + P1_SV + (mt * 16 + g) * 128 + 4 * t;
#pragma unroll
            for (int rh = 0; rh < 2; rh++)
#pragma unroll
                for (int a = 0; a < 3; a++)
#pragma unroll
                    for (int i = 0; i < 4; i++) vq[rh][a][i] = lds32(vb + (a + 1) * (MAX_NPC * 128) + rh * 1024 + (((4 * hf + i) ^ g) << 4));
#pragma unroll
            for (int rh = 0; rh < 2; rh++)
#pragma unroll
                for (int a = 0; a < 3; a++)
#pragma unroll
                    for (int i = 0; i < 4; i++)
                        sts32(vb + (a + 1) * (MAX_NPC * 128) + rh * 1024 + (((4 * hf + i) ^ g) << 4),
                              hmul2(pack_bf(acc[i][2 * rh], acc[i][2 * rh + 1]), vq[rh][a][i]));
            fence_async_smem();
            asm volatile("bar.sync %0, 64;" ::"r"(4 + mt) : "memory");
            {
                const int r4 = mt * 16 + 8 * hf + 4 * (lane >> 2), comp = lane & 3;
                if (lane < 8 && r4 < nnodes) tma_store3(&tmFs, comp, node0 + r4, sb + P1_SV + comp * (MAX_NPC * 128) + r4 * 128);
            }
            asm volatile("cp.async.bulk.commit_group;" ::: "memory");
        }
        STAMPT(11, 6 * 32);
    }
    if (tid == 0) {
        const unsigned target = (bar_seen / (unsigned)p.ncta + 1u) * (unsigned)p.ncta;
        unsigned cur;
        int spins = 0;
        do {
            asm volatile("ld.acquire.gpu.global.u32 %0, [%1];" : "=r"(cur) : "l"(&g_bar[0]) : "memory");
        } while ((int)(cur - target) < 0 && ++spins < (1 << 24));
    }
    STAMP(4);
    __syncthreads();
    STAMP(5);

    constexpr int SEG_IT = (MAX_CTA + 31) / 32;
    uint2 ra[SEG_IT][2];
    uint32_t rb[SEG_IT][2], rr[SEG_IT][2];
#pragma unroll
    for (int it = 0; it < SEG_IT; it++) {
        const int b = 2 * warp + (lane >> 4) + 32 * it;
        const uint32_t* sp = g_seg + ((size_t)b * MAX_CTA + cta) * (SEG_CAP * 3);
#pragma unroll
        for (int u = 0; u < 2; u++) {
            const int j = (lane & 15) + 16 * u;
            ra[it][u] = b < p.ncta ? __ldcg((const uint2*)(sp + 2 * j)) : make_uint2(0u, 0u);
            rb[it][u] = b < p.ncta ? __ldcg(sp + 2 * SEG_CAP + j) : 0u;
        }
    }
    if (mlp_warp && lane < 8) {
        asm volatile("cp.async.bulk.wait_group 0;" ::: "memory");
        asm volatile("fence.proxy.async;" ::: "memory");
    }
    STAMP(9);
    uint2 xa[SEG_IT];
    uint32_t xb[SEG_IT];
#pragma unroll
    for (int it = 0; it < SEG_IT; it++) {
        const int cnt = rb[it][0] >> 23;
        const int b = 2 * warp + (lane >> 4) + 32 * it;
        const uint32_t* sp = g_seg + ((size_t)b * MAX_CTA + cta) * (SEG_CAP * 3);
        const bool has = 32 + (lane & 15) < cnt;
        xa[it] = has ? __ldcg((const uint2*)(sp + 2 * (32 + (lane & 15)))) : make_uint2(0u, 0u);
        xb[it] = has ? __ldcg(sp + 2 * SEG_CAP + 32 + (lane & 15)) : 0u;
    }
#pragma unroll
    for (int it = 0; it < SEG_IT; it++) {
        const int cnt = rb[it][0] >> 23;
        if (cnt > SEG_CAP) ctrl[1] = 1;
#pragma unroll
        for (int u = 0; u < 2; u++)
            rr[it][u] = (lane & 15) + 16 * u < cnt ? (uint32_t)atomicAdd(&nCnt[(rb[it][u] >> 16) & 0x7fu], 1) : 0xffffffffu;
    }
#pragma unroll
    for (int it = 0; it < SEG_IT; it++) {
        const int cnt = rb[it][0] >> 23;
        if (32 + (lane & 15) < cnt) {
            const int pos = atomicAdd((int*)&ctrl[8], 1);
            const uint32_t rank = (uint32_t)atomicAdd(&nCnt[(xb[it] >> 16) & 0x7fu], 1);
            if (pos < STAGE_CAP) sts128(sb + P1_REC + pos * 16, make_uint4(xa[it].x, xa[it].y, xb[it], rank));
        }
        if (cnt > 48) {
            const int b = 2 * warp + (lane >> 4) + 32 * it;
            const uint32_t* sp = g_seg + ((size_t)b * MAX_CTA + cta) * (SEG_CAP * 3);
            const int j = 48 + (lane & 15);
            if (j < min(cnt, SEG_CAP)) {
                const uint2 a = __ldcg((const uint2*)(sp + 2 * j));
                const uint32_t c = __ldcg(sp + 2 * SEG_CAP + j);
                const int pos = atomicAdd((int*)&ctrl[8], 1);
                const uint32_t rank = (uint32_t)atomicAdd(&nCnt[(c >> 16) & 0x7fu], 1);
                if (pos < STAGE_CAP) sts128(sb + P1_REC + pos * 16, make_uint4(a.x, a.y, c, rank));
            }
        }
    }
    STAMP(13);
    __syncthreads();
    if (tid == 64) asm volatile("red.add.release.gpu.global.u32 [%0], 1;" ::"l"(&g_bar[1]) : "memory");
    STAMP(14);
    const int total = ctrl[8];
    if (tid == 0 && total > STAGE_CAP) ctrl[1] = 1;
    if (warp == 0) {
        int c[3], s = 0;
#pragma unroll
        for (int i = 0; i < 3; i++) {
            int b = lane * 3 + i;
            c[i] = b < nnodes ? max(16, (nCnt[b] + 15) & ~15) : 0;
            s += c[i];
        }
        int x = s;
#pragma unroll
        for (int o = 1; o < 32; o <<= 1) { int y = __shfl_up_sync(0xffffffffu, x, o); if (lane >= o) x += y; }
        const int slots = __shfl_sync(0xffffffffu, x, 31);
        int off = x - s, below = 0;
#pragma unroll
        for (int i = 0; i < 3; i++) {
            int b = lane * 3 + i;
            if (b < nnodes) {
                nInfo[b] = (uint32_t)off | ((uint32_t)c[i] << 16);
                below += (2 * off + c[i] < slots);
            }
            off += c[i];
        }
        below = __reduce_add_sync(0xffffffffu, below);
        if (lane == 0) {
            ctrl[2] = below;
            ctrl[4] = slots;
            if (slots > SLOT_CAP) ctrl[1] = 1;
        }
    }
    __syncthreads();
    if (ctrl[1] == 0) {
        uint16_t* sid = (uint16_t*)(smem + SM_SID);
        uint2* meta = (uint2*)(smem + SM_META);
#pragma unroll
        for (int it = 0; it < SEG_IT; it++)
#pragma unroll
            for (int u = 0; u < 2; u++)
                if (rr[it][u] != 0xffffffffu) rr[it][u] += lds32(sb + SM_NINFO + ((rb[it][u] >> 16) & 0x7fu) * 4) & 0xffffu;
#pragma unroll
        for (int it = 0; it < SEG_IT; it++)
#pragma unroll
            for (int u = 0; u < 2; u++)
                if (rr[it][u] != 0xffffffffu) {
                    sid[rr[it][u]]  = (uint16_t)((ra[it][u].x & 0xffffu) << 2);
                    meta[rr[it][u]] = make_uint2(((ra[it][u].x >> 16) << 5) | (rb[it][u] << 16), ra[it][u].y);
                }
        for (int i = tid; i < total; i += NT) {
            const uint4 r = lds128(sb + P1_REC + i * 16);
            const int pos = (int)(lds32(sb + SM_NINFO + ((r.z >> 16) & 0x7fu) * 4) & 0xffffu) + (int)r.w;
            sid[pos]  = (uint16_t)((r.x & 0xffffu) << 2);
            meta[pos] = make_uint2(((r.x >> 16) << 5) | (r.z << 16), r.y);
        }
        if (tid >= NT - 128 && tid - (NT - 128) < nnodes) {
            const int b = tid - (NT - 128), split = ctrl[2];
            const int mid = split < nnodes ? (int)(nInfo[split] & 0xffffu) : ctrl[4];
            const int st = b >= split;
            const int mine = (int)(nInfo[b] & 0xffffu) + (int)(nInfo[b] >> 16) - (st ? mid : 0);
            int lo = st ? 0 : split, hi = st ? split : nnodes;
            const int first = lo;
            while (lo < hi) {
                const int o = (lo + hi) >> 1;
                const int other = (int)(nInfo[o] & 0xffffu) + (int)(nInfo[o] >> 16) - (st ? 0 : mid);
                if (st ? (other <= mine) : (other < mine)) lo = o + 1; else hi = o;
            }
            const int rank = (st ? b - split : b) + lo - first;
            smem[SM_ORDER + rank] = (uint8_t)(b | (st << 7));
            const int padded = (int)(nInfo[b] >> 16), lastg = ((int)(nInfo[b] & 0xffffu) + padded - 16) >> 4;
            if (nCnt[b] - (padded - 16) <= 8) atomicOr((unsigned*)(smem + SM_HALF) + (lastg >> 5), 1u << (lastg & 31));
        }
        for (int i = tid; i < nnodes * 16; i += NT) {
            int nl = i >> 4, c = nCnt[nl];
            int j = (c & ~15) + (i & 15);
            if (j >= c && (j < 16 || (c & 15))) {
                int pos = (int)(nInfo[nl] & 0xffffu) + j;
                sid[pos]  = 0xffffu;
                meta[pos] = make_uint2((uint32_t)TAB_ZERO << 5, 0u);
            }
        }
    }
    STAMP(15);
    if (tid == 32) {
        const unsigned target = (bar_seen / (unsigned)p.ncta + 1u) * (unsigned)p.ncta;
        unsigned cur;
        int spins = 0;
        do {
            asm volatile("ld.acquire.gpu.global.u32 %0, [%1];" : "=r"(cur) : "l"(&g_bar[1]) : "memory");
        } while ((int)(cur - target) < 0 && ++spins < (1 << 24));
    }
    fence_async_smem();
    __syncthreads();
    STAMP(6);

    if (__shfl_sync(0xffffffffu, ctrl[1], 0) != 0) {
        float* acc = (float*)(smem + P1_POS);
        for (int i = tid; i < nnodes * 256; i += NT) acc[i] = 0.f;
        __syncthreads();
        const uint16_t* posu = (const uint16_t*)p.pos;
        const uint32_t* tabg = (const uint32_t*)g_table;
        const uint32_t* Fw = (const uint32_t*)g_F;
        for (int e0 = warp * 32; e0 < p.E; e0 += NT) {
            int e = e0 + lane;
            int s = 0, d = 0;
            uint32_t db = 0xffff, rxy = 0, rz = 0;
            bool act = false;
            if (e < p.E) {
                s = p.src[e]; d = p.dst[e];
                if (d >= node0 && d < node0 + nnodes) {
                    uint32_t sxy = posu[s * 3] | ((uint32_t)posu[s * 3 + 1] << 16), sz = posu[s * 3 + 2];
                    uint32_t dxy = posu[d * 3] | ((uint32_t)posu[d * 3 + 1] << 16), dz = posu[d * 3 + 2];
                    db  = edge_dist(sxy, sz, dxy, dz, rxy, rz);
                    act = db <= D_MAX_BITS;
                }
            }
            unsigned m = __ballot_sync(0xffffffffu, act);
            while (m) {
                int l = __ffs(m) - 1;
                m &= m - 1;
                int es = __shfl_sync(0xffffffffu, s, l), ed = __shfl_sync(0xffffffffu, d, l);
                uint32_t edb = __shfl_sync(0xffffffffu, db, l), exy = __shfl_sync(0xffffffffu, rxy, l), ez = __shfl_sync(0xffffffffu, rz, l);
                float inv = 1.0f / __uint_as_float(edb << 16);
                float rh[3] = {rbf(bf_lo(exy) * inv), rbf(bf_hi(exy) * inv), rbf(bf_lo(ez) * inv)};
                const uint32_t* fr = Fw + (size_t)es * 128 + lane;
                const uint32_t fh = __ldcg(fr);
                const uint32_t q[3] = {__ldcg(fr + 32), __ldcg(fr + 64), __ldcg(fr + 96)};
                float ps0 = 0.f, ps1 = 0.f, pr0 = 0.f, pr1 = 0.f;
                for (int j2 = 0; j2 < 32; j2++) {
                    uint32_t hj = __shfl_sync(0xffffffffu, fh, j2);
                    uint32_t a0 = *(const uint32_t*)(p.w2 + (2 * j2) * 192 + 2 * lane), a1 = *(const uint32_t*)(p.w2 + (2 * j2 + 1) * 192 + 2 * lane);
                    uint32_t b0 = *(const uint32_t*)(p.w2 + (2 * j2) * 192 + 128 + 2 * lane), b1 = *(const uint32_t*)(p.w2 + (2 * j2 + 1) * 192 + 128 + 2 * lane);
                    ps0 += bf_lo(hj) * bf_lo(a0) + bf_hi(hj) * bf_lo(a1);
                    ps1 += bf_lo(hj) * bf_hi(a0) + bf_hi(hj) * bf_hi(a1);
                    pr0 += bf_lo(hj) * bf_lo(b0) + bf_hi(hj) * bf_lo(b1);
                    pr1 += bf_lo(hj) * bf_hi(b0) + bf_hi(hj) * bf_hi(b1);
                }
                float ws0 = 0.f, ws1 = 0.f, wv0 = 0.f, wv1 = 0.f, wr0 = 0.f, wr1 = 0.f;
                for (int k2 = 0; k2 < 8; k2++) {
                    uint32_t rk2 = __ldcg(tabg + (edb - D_MIN_BITS) * 8 + k2);
#pragma unroll
                    for (int h = 0; h < 2; h++) {
                        float rv = h ? bf_hi(rk2) : bf_lo(rk2);
                        const __nv_bfloat16* wrow = p.wr + (2 * k2 + h) * 192 + 2 * lane;
                        uint32_t a = *(const uint32_t*)wrow, b = *(const uint32_t*)(wrow + 64), c = *(const uint32_t*)(wrow + 128);
                        ws0 += rv * bf_lo(a); ws1 += rv * bf_hi(a);
                        wv0 += rv * bf_lo(b); wv1 += rv * bf_hi(b);
                        wr0 += rv * bf_lo(c); wr1 += rv * bf_hi(c);
                    }
                }
                float* a = acc + (ed - node0) * 256 + 2 * lane;
                atomicAdd(a, ps0 * ws0); atomicAdd(a + 1, ps1 * ws1);
#pragma unroll
                for (int c = 0; c < 3; c++) {
                    atomicAdd(a + 64 * (c + 1), wv0 * bf_lo(q[c]) + pr0 * wr0 * rh[c]);
                    atomicAdd(a + 64 * (c + 1) + 1, wv1 * bf_hi(q[c]) + pr1 * wr1 * rh[c]);
                }
            }
        }
        __syncthreads();
        for (int i = tid; i < nnodes * 128; i += NT) {
            uint32_t r = *(const uint32_t*)(p.sv + (size_t)node0 * 256 + 2 * i);
            *(uint32_t*)(p.out + (size_t)node0 * 256 + 2 * i) = pack_bf(bf_lo(r) + acc[2 * i], bf_hi(r) + acc[2 * i + 1]);
        }
        return;
    }

    const int slots = __reduce_max_sync(0xffffffffu, ctrl[4]);
    const int split = __reduce_max_sync(0xffffffffu, ctrl[2]);
    constexpr int nstage = MAX_STAGE;
    const uint32_t ring = sb + SM_RING;
    const int mid = __reduce_max_sync(0xffffffffu, split < nnodes ? (int)(nInfo[split] & 0xffffu) : slots) >> 4;
    const int wgi = warp >> 2, w = warp & 3;
    uint32_t wp[3][4];
    if (wgi < 3) {
        const uint16_t* wr = (const uint16_t*)p.wr + 16 * w + g;
#pragma unroll
        for (int ty = 0; ty < 3; ty++) {
#pragma unroll
            for (int i = 0; i < 4; i++) {
                const uint16_t* q = wr + (8 * (i >> 1) + 2 * t) * 192 + ty * 64 + 8 * (i & 1);
                wp[ty][i] = (uint32_t)__ldg(q) | ((uint32_t)__ldg(q + 192) << 16);
            }
        }
    }
    constexpr uint32_t EMPTY_OFF = NCWG * MAX_STAGE * 8;
    if (wgi == 3) {
        const int sc = w >> 1, r = w & 1;
        const int g0 = (sc == 0 ? 0 : mid) + r, g1 = sc == 0 ? mid : slots >> 4;
        const uint32_t ring_wg = ring + sc * nstage * STAGE_B, full_wg = bar_full + sc * MAX_STAGE * 8;
        const int e = lane >> 1, half = lane & 1;
        const uint32_t coef_off = e * 128 + ((half ^ (e & 7)) << 4);
        const int vrot = (e & 3) ^ ((e >> 1) & 3);
        const uint8_t* tab = (const uint8_t*)g_table + half * 16;
        int stage = r;
        uint32_t phase = 1;
        uint32_t ma = sb + SM_META + (g0 * 16 + e) * 8, ida = sb + SM_SID + g0 * 32;
        uint2 m = make_uint2(0u, 0u);
        uint4 tv = make_uint4(0u, 0u, 0u, 0u), ia = tv, ib = tv;
        if (g0 < g1) {
            m  = lds64(ma);
            ia = lds128(ida);
            ib = lds128(ida + 16);
            tv = __ldg((const uint4*)(tab + (m.x & 0xffffu)));
        }
        for (int left = (g1 - g0 + 1) >> 1; left > 0; left--) {
            const uint32_t st = ring_wg + stage * STAGE_B, fb = full_wg + stage * 8;
            ma += 256; ida += 64;
            uint2 mn = m;
            if (left > 1) mn = lds64(ma);
            mbar_wait(fb + EMPTY_OFF, phase);
            uint32_t leader;
            asm volatile("{\n.reg .pred p;\nelect.sync _|p, 0xffffffff;\nselp.u32 %0, 1, 0, p;\n}" : "=r"(leader));
            if (leader) {
                const uint32_t id2[8] = {ia.x, ia.y, ia.z, ia.w, ib.x, ib.y, ib.z, ib.w};
                const uint32_t rows = st + 2048;
                if ((ib.w >> 16) != 0xffffu) {
                    mbar_expect_tx(fb, 16 * 512);
#pragma unroll
                    for (int i = 0; i < 8; i++) {
                        tma_load(rows + (2 * i) * 640, &tmF, (int)(id2[i] & 0xffffu), fb);
                        tma_load(rows + (2 * i + 1) * 640, &tmF, (int)(id2[i] >> 16), fb);
                    }
                } else {
                    int nv = 0;
#pragma unroll
                    for (int i = 0; i < 8; i++) nv += ((id2[i] & 0xffffu) != 0xffffu) + ((id2[i] >> 16) != 0xffffu);
                    mbar_expect_tx(fb, (uint32_t)nv * 512u);
#pragma unroll
                    for (int q = 0; q < 4; q++) {
                        if (4 * q + 4 <= nv) {
                            tma_load(rows + (4 * q) * 640, &tmF, (int)(id2[2 * q] & 0xffffu), fb);
                            tma_load(rows + (4 * q + 1) * 640, &tmF, (int)(id2[2 * q] >> 16), fb);
                            tma_load(rows + (4 * q + 2) * 640, &tmF, (int)(id2[2 * q + 1] & 0xffffu), fb);
                            tma_load(rows + (4 * q + 3) * 640, &tmF, (int)(id2[2 * q + 1] >> 16), fb);
                        } else {
                            if (4 * q < nv)     tma_load(rows + (4 * q) * 640, &tmF, (int)(id2[2 * q] & 0xffffu), fb);
                            if (4 * q + 1 < nv) tma_load(rows + (4 * q + 1) * 640, &tmF, (int)(id2[2 * q] >> 16), fb);
                            if (4 * q + 2 < nv) tma_load(rows + (4 * q + 2) * 640, &tmF, (int)(id2[2 * q + 1] & 0xffffu), fb);
                        }
                    }
                }
            }
            __syncwarp();
            uint4 o[4];
            {
                const uint32_t mul[4] = {0x3f803f80u, __byte_perm(m.y, 0, 0x1010), __byte_perm(m.y, 0, 0x3232), __byte_perm(m.x, 0, 0x3232)};
#pragma unroll
                for (int j = 0; j < 4; j++) {
                    const int v = j ^ vrot;
                    const uint32_t lo = (v & 1) ? mul[1] : mul[0], hi = (v & 1) ? mul[3] : mul[2];
                    const uint32_t mm = (v & 2) ? hi : lo;
                    o[j] = make_uint4(hmul2(tv.x, mm), hmul2(tv.y, mm), hmul2(tv.z, mm), hmul2(tv.w, mm));
                }
            }
            const bool upper = __any_sync(0xffffffffu, lane >= 16 && (m.x & 0xffffu) != (uint32_t)(TAB_ZERO << 5));
            m = mn;
            if (left > 1) {
                ia = lds128(ida);
                ib = lds128(ida + 16);
                tv = __ldg((const uint4*)(tab + (m.x & 0xffffu)));
            }
            const uint32_t a = st + coef_off;
            if (upper || lane < 16) {
#pragma unroll
                for (int j = 0; j < 4; j++) sts128(a ^ ((j ^ vrot) << 5), o[j]);
            }
            fence_async_smem();
            __syncwarp();
            mbar_arrive_elected(fb);
            stage += 2;
            if (stage >= nstage) { stage -= nstage; phase ^= 1; }
        }
    } else if (wgi == 2) {
        uint32_t wA[2][4][4];
        {
            const uint16_t* w2 = (const uint16_t*)p.w2 + 16 * w + g;
#pragma unroll
            for (int mk = 0; mk < 8; mk++) {
#pragma unroll
                for (int i = 0; i < 4; i++) {
                    const uint16_t* q = w2 + (16 * (mk & 3) + 2 * t + 8 * (i >> 1)) * 192 + (mk >> 2) * 128 + 8 * (i & 1);
                    wA[mk >> 2][mk & 3][i] = (uint32_t)__ldg(q) | ((uint32_t)__ldg(q + 192) << 16);
                }
            }
        }
        const uint32_t lane_off = (uint32_t)node0 * 512u + t * 128 + w * 32 + (g & 1) * 16 + (g >> 1) * 4;
        uint32_t hcnt[2] = {0u, 0u};
        float zs[8], zv[24], pvv[6], pr[4][2];
        uint32_t hbuf = 0;
        auto start = [&](int ent) {
            const int c = ent >> 7;
            const uint32_t k = c ? hcnt[1] : hcnt[0];
            hbuf = 2 * c + (k & 1);
            mbar_wait(bar_hfull + hbuf * 8, (k >> 1) & 1);
            if (c) hcnt[1]++; else hcnt[0]++;
            const uint32_t dht = desc_lo(sb + SM_HT + hbuf * 8192);
            wg_fence();
            wgmma_n16_first(zs, wA[0][0], dht);
            wgmma_n48_first(zv, wA[1][0], dht + 2);
#pragma unroll
            for (int ks = 1; ks < 4; ks++) {
                wgmma_n16(zs, wA[0][ks], dht + ks * 128);
                wgmma_n48(zv, wA[1][ks], dht + ks * 128 + 2);
            }
            wg_commit();
        };
        auto side = [&](int ent) {
            const uint32_t pa = sb + SM_PV + hbuf * 1536 + (tid & 127) * 4;
            const uint32_t a0 = lds32(pa), a1 = lds32(pa + 512), a2 = lds32(pa + 1024);
            pvv[0] = bf_lo(a0); pvv[1] = bf_hi(a0); pvv[2] = bf_lo(a1); pvv[3] = bf_hi(a1); pvv[4] = bf_lo(a2); pvv[5] = bf_hi(a2);
            __syncwarp();
            mbar_arrive_elected(bar_hempty + hbuf * 8);
        };
        auto weigh = [&]() {
#pragma unroll
            for (int i = 0; i < 12; i++) asm volatile("" : "+r"(wp[i >> 2][i & 3]));
            pr[0][0] = bf_lo(wp[0][0]) * zs[0] + bf_hi(wp[0][0]) * zs[1] + bf_lo(wp[0][2]) * zs[4] + bf_hi(wp[0][2]) * zs[5];
            pr[0][1] = bf_lo(wp[0][1]) * zs[2] + bf_hi(wp[0][1]) * zs[3] + bf_lo(wp[0][3]) * zs[6] + bf_hi(wp[0][3]) * zs[7];
#pragma unroll
            for (int a = 0; a < 3; a++) {
                const float* y = zv + 8 * a;
                pr[a + 1][0] = pvv[2 * a] + bf_lo(wp[2][0]) * y[0] + bf_hi(wp[2][0]) * y[1] + bf_lo(wp[2][2]) * y[4] + bf_hi(wp[2][2]) * y[5];
                pr[a + 1][1] = pvv[2 * a + 1] + bf_lo(wp[2][1]) * y[2] + bf_hi(wp[2][1]) * y[3] + bf_lo(wp[2][3]) * y[6] + bf_hi(wp[2][3]) * y[7];
            }
            asm volatile("" : "+f"(pr[0][0]), "+f"(pr[0][1]), "+f"(pr[1][0]), "+f"(pr[1][1]), "+f"(pr[2][0]), "+f"(pr[2][1]), "+f"(pr[3][0]), "+f"(pr[3][1]) :: "memory");
        };
        auto finish = [&](int ent, uint32_t resid) {
            const bool hi2 = t & 2, hi1 = t & 1, odd = g & 1;
            float ka0 = hi2 ? pr[2][0] : pr[0][0], ka1 = hi2 ? pr[2][1] : pr[0][1];
            float kb0 = hi2 ? pr[3][0] : pr[1][0], kb1 = hi2 ? pr[3][1] : pr[1][1];
            float sa0 = hi2 ? pr[0][0] : pr[2][0], sa1 = hi2 ? pr[0][1] : pr[2][1];
            float sb0 = hi2 ? pr[1][0] : pr[3][0], sb1 = hi2 ? pr[1][1] : pr[3][1];
            ka0 += __shfl_xor_sync(0xffffffffu, sa0, 2); ka1 += __shfl_xor_sync(0xffffffffu, sa1, 2);
            kb0 += __shfl_xor_sync(0xffffffffu, sb0, 2); kb1 += __shfl_xor_sync(0xffffffffu, sb1, 2);
            float k0 = hi1 ? kb0 : ka0, k1 = hi1 ? kb1 : ka1;
            float s0 = hi1 ? ka0 : kb0, s1 = hi1 ? ka1 : kb1;
            k0 += __shfl_xor_sync(0xffffffffu, s0, 1);
            k1 += __shfl_xor_sync(0xffffffffu, s1, 1);
            const float other = __shfl_xor_sync(0xffffffffu, odd ? k0 : k1, 4);
            const float lo = odd ? other : k0, hi = odd ? k1 : other;
            *(uint32_t*)((uint8_t*)p.out + (lane_off + (uint32_t)(ent & 127) * 512u)) = pack_bf(bf_lo(resid) + lo, bf_hi(resid) + hi);
        };
        auto entry = [&](int i) -> int { return __reduce_max_sync(0xffffffffu, (int)smem[SM_ORDER + i]); };
        auto load_resid = [&](int ent) -> uint32_t { return __ldg((const uint32_t*)((const uint8_t*)p.sv + (lane_off + (uint32_t)(ent & 127) * 512u))); };
        if (nnodes > 0) {
            int cur = entry(0), nxt = entry(1);
            uint32_t resid = load_resid(cur);
            start(cur);
#pragma unroll 1
            for (int i = 1; i < nnodes; i++) {
                wg_wait0();
                side(cur);
                weigh();
                start(nxt);
                finish(cur, resid);
                cur = nxt;
                resid = load_resid(cur);
                nxt = entry(i + 1);
            }
            wg_wait0();
            side(cur);
            weigh();
            finish(cur, resid);
        }
    } else {
        const int wg = wgi;
        uint32_t aoff[4];
        {
            const int e = (lane & 7) + 8 * (lane >> 4), ch = 2 * w + ((lane >> 3) & 1);
#pragma unroll
            for (int b = 0; b < 4; b++) aoff[b] = 2048 + e * 640 + b * 128 + ((ch ^ ((5 * e + b) & 7)) << 4);
        }
        const uint32_t stsm_0 = sb + SM_HT + wg * 16384 + (16 * w + (lane & 15)) * 128 + (((lane >> 4) ^ (lane & 7)) << 4);
        const uint32_t pv_0 = sb + SM_PV + wg * 3072 + (tid & 127) * 4;
        uint32_t hk = 0;
        const uint32_t ring_wg = ring + wg * nstage * STAGE_B;
        const uint32_t full_wg = bar_full + wg * MAX_STAGE * 8;

        float ys[8], yv[24], dQ[3][8];
        uint32_t A0[4][4], A1[4][4];
#pragma unroll
        for (int i = 0; i < 24; i++) yv[i] = 0.f;
#pragma unroll
        for (int i = 0; i < 8; i++) { ys[i] = 0.f; dQ[0][i] = 0.f; dQ[1][i] = 0.f; dQ[2][i] = 0.f; }
        int left = wg == 0 ? mid : (slots >> 4) - mid;
        int fstage = 0;
        uint32_t fphase = 0, fst = ring_wg, fbar = full_wg;
        int fg = wg == 0 ? 0 : mid;
        uint32_t hmask = __reduce_or_sync(0xffffffffu, lds32(sb + SM_HALF + (fg >> 5) * 4));
        uint32_t ninfo_a = sb + SM_NINFO + (wg == 0 ? 0 : split) * 4;
        int gi = 0, G = __reduce_max_sync(0xffffffffu, (int)(lds32(ninfo_a) >> 20));

        auto fetch = [&](uint32_t (&A)[4][4], uint32_t& bd, uint32_t& eb) {
            if ((fg & 31) == 0) hmask = __reduce_or_sync(0xffffffffu, lds32(sb + SM_HALF + (fg >> 5) * 4));
            const bool lowhalf = (hmask >> (fg & 31)) & 1;
            fg++;
            mbar_wait(fbar, fphase);
            if (lowhalf) {
#pragma unroll
                for (int b = 0; b < 4; b++) { ldsm2t(A[b][0], A[b][1], fst + aoff[b]); A[b][2] = 0u; A[b][3] = 0u; }
            } else {
#pragma unroll
                for (int b = 0; b < 4; b++) ldsm4t(A[b], fst + aoff[b]);
            }
            bd = desc_lo(fst);
            eb = fbar + EMPTY_OFF;
            fst += STAGE_B; fbar += 8;
            if (++fstage == nstage) { fstage = 0; fphase ^= 1; fst = ring_wg; fbar = full_wg; }
        };
        auto step = [&](uint32_t (&Ac)[4][4], uint32_t bdc, uint32_t ebc, uint32_t (&An)[4][4], uint32_t& bdn, uint32_t& ebn) {
            wg_fence();
            wgmma_n64_p(ys, yv, Ac[0], bdc, gi);
            wgmma_n16_p(dQ[0], Ac[1], bdc, gi);
            wgmma_n16_p(dQ[1], Ac[2], bdc, gi);
            wgmma_n16_p(dQ[2], Ac[3], bdc, gi);
            wg_commit();
            if (--left > 0) fetch(An, bdn, ebn);
            const bool last = ++gi == G;
            uint32_t info_next = 0;
            if (last) { ninfo_a += 4; info_next = lds32(ninfo_a); }
            wg_wait0();
            mbar_arrive_elected(ebc);
            if (last) {
                const uint32_t hb = hk & 1;
                mbar_wait(bar_hempty + (2 * wg + hb) * 8, ((hk >> 1) & 1) ^ 1);
                hk++;
                const uint32_t stsm_a = stsm_0 + hb * 8192, pv_a = pv_0 + hb * 1536;
                stsm4(stsm_a, pack_bf(ys[0], ys[1]), pack_bf(ys[2], ys[3]), pack_bf(ys[4], ys[5]), pack_bf(ys[6], ys[7]));
#pragma unroll
                for (int i = 0; i < 6; i += 2) {
                    stsm4(stsm_a ^ ((i + 2) << 4),
                          pack_bf(yv[4 * i], yv[4 * i + 1]), pack_bf(yv[4 * i + 2], yv[4 * i + 3]),
                          pack_bf(yv[4 * i + 4], yv[4 * i + 5]), pack_bf(yv[4 * i + 6], yv[4 * i + 7]));
                }
#pragma unroll
                for (int i = 0; i < 4; i++) asm volatile("" : "+r"(wp[1][i]));
#pragma unroll
                for (int a = 0; a < 3; a++) {
                    const float* q = dQ[a];
                    const float p0 = bf_lo(wp[1][0]) * q[0] + bf_hi(wp[1][0]) * q[1] + bf_lo(wp[1][2]) * q[4] + bf_hi(wp[1][2]) * q[5];
                    const float p1 = bf_lo(wp[1][1]) * q[2] + bf_hi(wp[1][1]) * q[3] + bf_lo(wp[1][3]) * q[6] + bf_hi(wp[1][3]) * q[7];
                    sts32(pv_a + a * 512, pack_bf(p0, p1));
                }
                fence_async_smem();
                __syncwarp();
                mbar_arrive_elected(bar_hfull + (2 * wg + hb) * 8);
                G = __reduce_max_sync(0xffffffffu, (int)(info_next >> 20));
                gi = 0;
            }
        };
        if (left > 0) {
            uint32_t bd0, eb0, bd1 = 0, eb1 = 0;
            fetch(A0, bd0, eb0);
            while (true) {
                step(A0, bd0, eb0, A1, bd1, eb1);
                if (left <= 0) break;
                step(A1, bd1, eb1, A0, bd0, eb0);
                if (left <= 0) break;
            }
        }
    }
    STAMP(8);
}

typedef CUresult (*EncodeFn)(CUtensorMap*, CUtensorMapDataType, cuuint32_t, void*, const cuuint64_t*, const cuuint64_t*,
                             const cuuint32_t*, const cuuint32_t*, CUtensorMapInterleave, CUtensorMapSwizzle,
                             CUtensorMapL2promotion, CUtensorMapFloatOOBfill);

void make_map(EncodeFn enc, CUtensorMap* tm, const void* base, uint64_t lines, uint32_t box) {
    cuuint64_t gd[2] = {64, lines};
    cuuint64_t gs[1] = {128};
    cuuint32_t bd[2] = {64, box};
    cuuint32_t es[2] = {1, 1};
    enc(tm, CU_TENSOR_MAP_DATA_TYPE_BFLOAT16, 2, const_cast<void*>(base), gd, gs, bd, es, CU_TENSOR_MAP_INTERLEAVE_NONE,
        CU_TENSOR_MAP_SWIZZLE_128B, CU_TENSOR_MAP_L2_PROMOTION_L2_128B, CU_TENSOR_MAP_FLOAT_OOB_FILL_NONE);
}

void make_map3(EncodeFn enc, CUtensorMap* tm, const void* base, uint64_t nodes, uint32_t box) {
    cuuint64_t gd[3] = {64, 4, nodes};
    cuuint64_t gs[2] = {128, 512};
    cuuint32_t bd[3] = {64, 1, box};
    cuuint32_t es[3] = {1, 1, 1};
    enc(tm, CU_TENSOR_MAP_DATA_TYPE_BFLOAT16, 3, const_cast<void*>(base), gd, gs, bd, es, CU_TENSOR_MAP_INTERLEAVE_NONE,
        CU_TENSOR_MAP_SWIZZLE_128B, CU_TENSOR_MAP_L2_PROMOTION_L2_128B, CU_TENSOR_MAP_FLOAT_OOB_FILL_NONE);
}

}

extern "C" void kernel_launch(void* const* d_in, const int* in_sizes, int n_in, void* d_out, int out_size) {
    (void)n_in; (void)out_size;
    static int n_sm = 0;
    static EncodeFn enc = nullptr;
    static void* f_ptr = nullptr;
    if (n_sm == 0) {
        int dev = 0;
        cudaGetDevice(&dev);
        cudaDeviceGetAttribute(&n_sm, cudaDevAttrMultiProcessorCount, dev);
        cudaFuncSetAttribute(painn_kernel, cudaFuncAttributeMaxDynamicSharedMemorySize, SM_TOTAL);
        void* fn = nullptr;
        cudaDriverEntryPointQueryResult qr;
        cudaGetDriverEntryPoint("cuTensorMapEncodeTiled", &fn, cudaEnableDefault, &qr);
        enc = (EncodeFn)fn;
        cudaGetSymbolAddress(&f_ptr, g_F);
    }
    Params p;
    p.sv    = (const __nv_bfloat16*)d_in[0];
    p.pos   = (const __nv_bfloat16*)d_in[1];
    p.src   = (const int*)d_in[2];
    p.dst   = (const int*)d_in[3];
    p.freqs = (const __nv_bfloat16*)d_in[4];
    p.w1    = (const __nv_bfloat16*)d_in[5];
    p.w2    = (const __nv_bfloat16*)d_in[6];
    p.wr    = (const __nv_bfloat16*)d_in[7];
    p.out   = (__nv_bfloat16*)d_out;
    p.N = in_sizes[1] / 3;
    p.E = in_sizes[2];
    p.ncta = n_sm < MAX_CTA ? n_sm : MAX_CTA;
    p.npc = ((p.N + p.ncta - 1) / p.ncta + 3) & ~3;
    p.npc_magic = (uint32_t)(0x100000000ull / (uint32_t)p.npc) + 1u;
    p.quads_per_cta = ((p.E >> 2) + p.ncta - 1) / p.ncta;
    if (!enc || p.N > MAX_N || p.npc > MAX_NPC || (p.E & 3) || p.quads_per_cta > MAX_ROUNDS * 32) return;

    CUtensorMap tmF, tmFs;
    make_map(enc, &tmF, f_ptr, (uint64_t)p.N * 4, 4);
    make_map3(enc, &tmFs, f_ptr, (uint64_t)p.N, 4);

    cudaLaunchConfig_t cfg = {};
    cfg.gridDim = dim3(p.ncta);
    cfg.blockDim = dim3(NT);
    cfg.dynamicSmemBytes = SM_TOTAL;
    cfg.stream = cudaStreamPerThread;
    cudaLaunchAttribute attr[1];
    attr[0].id = cudaLaunchAttributeCooperative;
        attr[0].val.cooperative = 1;
    cfg.attrs = attr;
    cfg.numAttrs = 1;
    cudaLaunchKernelEx(&cfg, painn_kernel, p, tmF, tmFs);
}
```

```cpp
#include <cuda_runtime.h>
#include <cuda.h>
#include <cuda_bf16.h>
#include <stdint.h>

namespace {

constexpr int NT        = 512;
constexpr int NCWG      = 2;
constexpr int MAX_N     = 10240;
constexpr int MAX_CTA   = 136;
constexpr int MAX_NPC   = 80;
constexpr int MAX_ROUNDS = 38;
constexpr int SEG_CAP   = 64;
constexpr int SLOT_CAP  = 6144;
constexpr int MAX_STAGE = 5;
constexpr int STAGE_B   = 12288;

constexpr uint32_t D_MIN_BITS = 0x38D2;
constexpr uint32_t D_MAX_BITS = 0x409C;
constexpr int TAB_ROWS  = (int)(D_MAX_BITS - D_MIN_BITS) + 1;
constexpr int TAB_ZERO  = TAB_ROWS;
constexpr int TAB_BYTES = (TAB_ROWS + 1) * 32;

constexpr int SM_BINCNT = 0;
constexpr int SM_NCNT   = SM_BINCNT + MAX_CTA * 4;
constexpr int SM_NINFO  = SM_NCNT + MAX_NPC * 4;
constexpr int SM_ORDER  = SM_NINFO + (MAX_NPC + 1) * 4;
constexpr int SM_CTRL   = SM_ORDER + MAX_NPC + 12;
constexpr int SM_BARS   = SM_CTRL + 64;
constexpr int SM_SID    = 2048 + 256;
constexpr int SM_META   = SM_SID + SLOT_CAP * 2;
constexpr int SM_TOTAL  = 232448;
constexpr int SM_HT     = (SM_TOTAL - 4 * 8192 - 4 * 1536) / 1024 * 1024;
constexpr int SM_PV     = SM_HT + 4 * 8192;
constexpr int SM_RING   = SM_HT - NCWG * MAX_STAGE * STAGE_B;
constexpr int P1_POS    = 3072;
constexpr int P1_SEGA   = P1_POS + 61440;
constexpr int P1_SEGB   = P1_SEGA + MAX_CTA * SEG_CAP * 8;
constexpr int P1_SV     = P1_SEGB + MAX_CTA * SEG_CAP * 4;
constexpr int P1_W1     = P1_SV + 4 * MAX_NPC * 128;
constexpr int P1_W2     = P1_W1 + 8192;
constexpr int P1_END    = P1_W2 + 8192;
constexpr int P1_REC    = P1_SEGA;
constexpr int STAGE_CAP = (P1_SV - P1_REC) / 16;
static_assert(SM_BARS + (12 + 2 * NCWG * MAX_STAGE) * 8 <= SM_SID, "misc block");
static_assert(SM_BARS + 256 <= P1_POS, "misc block");
static_assert(P1_END <= SM_TOTAL && P1_SV % 1024 == 0 && P1_REC % 16 == 0, "phase 1 overlay");
static_assert(SM_META + SLOT_CAP * 8 <= SM_RING && SM_PV + 4 * 1536 <= SM_TOTAL, "CSR");
static_assert(SM_RING % 1024 == 0 && SM_HT % 1024 == 0, "alignment");
static_assert(SM_BARS % 8 == 0 && SM_META % 8 == 0 && SM_CTRL % 4 == 0, "alignment");
static_assert(MAX_N * 6 <= 61440, "pos");
static_assert(SM_RING >= P1_SEGA && SM_HT <= P1_END, "every byte of the stages is written (finite) during phase 1");
static_assert(SM_SID + MAX_NPC * 1024 <= SM_TOTAL, "slow path accumulators");

__device__ __align__(1024) uint4 g_F[MAX_N * 32];
__device__ __align__(128) uint32_t g_seg[MAX_CTA * MAX_CTA * SEG_CAP * 3];
__device__ uint4    g_table[(TAB_BYTES + 15) / 16];
__device__ unsigned g_bar[2];
#define STAMP(k)
#define STAMPT(k, T)

struct Params {
    const __nv_bfloat16* sv;
    const __nv_bfloat16* pos;
    const int*           src;
    const int*           dst;
    const __nv_bfloat16* freqs;
    const __nv_bfloat16* w1;
    const __nv_bfloat16* w2;
    const __nv_bfloat16* wr;
    __nv_bfloat16*       out;
    int N, E, ncta, npc;
    uint32_t npc_magic;
    int quads_per_cta;
};

__device__ __forceinline__ uint32_t smem_u32(const void* p) { return (uint32_t)__cvta_generic_to_shared(p); }
__device__ __forceinline__ float bf_lo(uint32_t v) { return __uint_as_float(v << 16); }
__device__ __forceinline__ float bf_hi(uint32_t v) { return __uint_as_float(v & 0xffff0000u); }
__device__ __forceinline__ uint32_t pack_bf(float lo, float hi) {
    uint32_t r;
    asm("cvt.rn.bf16x2.f32 %0, %1, %2;" : "=r"(r) : "f"(hi), "f"(lo));
    return r;
}
__device__ __forceinline__ float rbf(float x) { return bf_lo(pack_bf(x, 0.f)); }
__device__ __forceinline__ uint32_t hmul2(uint32_t a, uint32_t b) {
    uint32_t r;
    asm("mul.rn.bf16x2 %0, %1, %2;" : "=r"(r) : "r"(a), "r"(b));
    return r;
}
__device__ __forceinline__ uint32_t hsub2(uint32_t a, uint32_t b) {
    uint32_t r;
    asm("sub.rn.bf16x2 %0, %1, %2;" : "=r"(r) : "r"(a), "r"(b));
    return r;
}
__device__ __forceinline__ uint32_t lds32(uint32_t a) { uint32_t v; asm volatile("ld.shared.u32 %0, [%1];" : "=r"(v) : "r"(a)); return v; }
__device__ __forceinline__ uint2 lds64(uint32_t a) { uint2 v; asm volatile("ld.shared.v2.u32 {%0,%1}, [%2];" : "=r"(v.x), "=r"(v.y) : "r"(a)); return v; }
__device__ __forceinline__ uint4 lds128(uint32_t a) { uint4 v; asm volatile("ld.shared.v4.u32 {%0,%1,%2,%3}, [%4];" : "=r"(v.x), "=r"(v.y), "=r"(v.z), "=r"(v.w) : "r"(a)); return v; }
__device__ __forceinline__ void sts32(uint32_t a, uint32_t v) { asm volatile("st.shared.u32 [%0], %1;" ::"r"(a), "r"(v) : "memory"); }
__device__ __forceinline__ void sts128(uint32_t a, uint4 v) { asm volatile("st.shared.v4.u32 [%0], {%1,%2,%3,%4};" ::"r"(a), "r"(v.x), "r"(v.y), "r"(v.z), "r"(v.w) : "memory"); }
__device__ __forceinline__ void mbar_init(uint32_t bar, int cnt) { asm volatile("mbarrier.init.shared::cta.b64 [%0], %1;" ::"r"(bar), "r"(cnt) : "memory"); }
__device__ __forceinline__ void mbar_expect_tx(uint32_t bar, uint32_t bytes) { asm volatile("mbarrier.arrive.expect_tx.shared::cta.b64 _, [%0], %1;" ::"r"(bar), "r"(bytes) : "memory"); }
__device__ __forceinline__ void mbar_wait(uint32_t bar, uint32_t parity) {
    asm volatile("{\n.reg .pred p;\n.reg .u32 c;\n"
                 "mbarrier.try_wait.parity.shared::cta.b64 p, [%0], %1;\n"
                 "@p bra DONE_%=;\n"
                 "mov.u32 c, 0;\n"
                 "LOOP_%=:\n"
                 "mbarrier.try_wait.parity.shared::cta.b64 p, [%0], %1;\n"
                 "@p bra DONE_%=;\n"
                 "add.u32 c, c, 1;\n"
                 "setp.lt.u32 p, c, 4194304;\n"
                 "@p bra LOOP_%=;\n"
                 "DONE_%=:\n}"
                 ::"r"(bar), "r"(parity) : "memory");
}
__device__ __forceinline__ void mbar_arrive_elected(uint32_t bar) {
    asm volatile("{\n.reg .pred p;\nelect.sync _|p, 0xffffffff;\n@p mbarrier.arrive.shared::cta.b64 _, [%0];\n}" ::"r"(bar) : "memory");
}
__device__ __forceinline__ void bulk_g2s(uint32_t dst, const void* src, uint32_t bytes, uint32_t bar) {
    asm volatile("cp.async.bulk.shared::cluster.global.mbarrier::complete_tx::bytes [%0], [%1], %2, [%3];"
                 ::"r"(dst), "l"(src), "r"(bytes), "r"(bar) : "memory");
}
__device__ __forceinline__ void cp_async16(uint32_t dst, const void* src) {
    asm volatile("cp.async.cg.shared.global [%0], [%1], 16;" ::"r"(dst), "l"(src) : "memory");
}
__device__ __forceinline__ void tma_load(uint32_t dst, const CUtensorMap* tm, int line, uint32_t bar) {
    asm volatile("cp.async.bulk.tensor.2d.shared::cluster.global.mbarrier::complete_tx::bytes [%0], [%1, {%3, %4}], [%2];"
                 ::"r"(dst), "l"(tm), "r"(bar), "r"(0), "r"(line) : "memory");
}
__device__ __forceinline__ void tma_store3(const CUtensorMap* tm, int comp, int node, uint32_t src) {
    asm volatile("cp.async.bulk.tensor.3d.global.shared::cta.bulk_group [%0, {%2, %3, %4}], [%1];"
                 ::"l"(tm), "r"(src), "r"(0), "r"(comp), "r"(node) : "memory");
}
__device__ __forceinline__ void fence_async_smem() { asm volatile("fence.proxy.async.shared::cta;" ::: "memory"); }
__device__ __forceinline__ void ldsm4(uint32_t (&r)[4], uint32_t a) {
    asm volatile("ldmatrix.sync.aligned.m8n8.x4.shared.b16 {%0,%1,%2,%3}, [%4];" : "=r"(r[0]), "=r"(r[1]), "=r"(r[2]), "=r"(r[3]) : "r"(a) : "memory");
}
__device__ __forceinline__ void ldsm4t(uint32_t (&r)[4], uint32_t a) {
    asm volatile("ldmatrix.sync.aligned.m8n8.x4.trans.shared.b16 {%0,%1,%2,%3}, [%4];" : "=r"(r[0]), "=r"(r[1]), "=r"(r[2]), "=r"(r[3]) : "r"(a) : "memory");
}
__device__ __forceinline__ uint32_t ldsm4t_x4_probe(uint32_t (&A)[4][4], uint32_t a0, uint32_t a1, uint32_t a2, uint32_t a3,
                                                    uint32_t bar, uint32_t parity) {
    uint32_t ok;
    asm volatile("{\n.reg .pred p;\n"
                 "mbarrier.test_wait.parity.shared::cta.b64 p, [%21], %22;\n"
                 "ldmatrix.sync.aligned.m8n8.x4.trans.shared.b16 {%0,%1,%2,%3}, [%17];\n"
                 "ldmatrix.sync.aligned.m8n8.x4.trans.shared.b16 {%4,%5,%6,%7}, [%18];\n"
                 "ldmatrix.sync.aligned.m8n8.x4.trans.shared.b16 {%8,%9,%10,%11}, [%19];\n"
                 "ldmatrix.sync.aligned.m8n8.x4.trans.shared.b16 {%12,%13,%14,%15}, [%20];\n"
                 "selp.u32 %16, 1, 0, p;\n}"
                 : "=r"(A[0][0]), "=r"(A[0][1]), "=r"(A[0][2]), "=r"(A[0][3]), "=r"(A[1][0]), "=r"(A[1][1]), "=r"(A[1][2]), "=r"(A[1][3]),
                   "=r"(A[2][0]), "=r"(A[2][1]), "=r"(A[2][2]), "=r"(A[2][3]), "=r"(A[3][0]), "=r"(A[3][1]), "=r"(A[3][2]), "=r"(A[3][3]),
                   "=r"(ok)
                 : "r"(a0), "r"(a1), "r"(a2), "r"(a3), "r"(bar), "r"(parity) : "memory");
    return ok;
}
__device__ __forceinline__ void stsm4(uint32_t a, uint32_t r0, uint32_t r1, uint32_t r2, uint32_t r3) {
    asm volatile("stmatrix.sync.aligned.m8n8.x4.shared.b16 [%0], {%1,%2,%3,%4};" ::"r"(a), "r"(r0), "r"(r1), "r"(r2), "r"(r3) : "memory");
}
__device__ __forceinline__ void mma16816(float (&c)[4], const uint32_t (&a)[4], uint32_t b0, uint32_t b1) {
    asm volatile("mma.sync.aligned.m16n8k16.row.col.f32.bf16.bf16.f32 {%0,%1,%2,%3}, {%4,%5,%6,%7}, {%8,%9}, {%0,%1,%2,%3};"
                 : "+f"(c[0]), "+f"(c[1]), "+f"(c[2]), "+f"(c[3])
                 : "r"(a[0]), "r"(a[1]), "r"(a[2]), "r"(a[3]), "r"(b0), "r"(b1));
}

__device__ __forceinline__ uint32_t desc_lo(uint32_t saddr) { return ((saddr & 0x3FFFF) >> 4) | (1u << 16); }
#define DESC_HI "0x40000040"
__device__ __forceinline__ void wg_fence() { asm volatile("wgmma.fence.sync.aligned;" ::: "memory"); }
__device__ __forceinline__ void wg_commit() { asm volatile("wgmma.commit_group.sync.aligned;" ::: "memory"); }
__device__ __forceinline__ void wg_wait0() { asm volatile("wgmma.wait_group.sync.aligned 0;" ::: "memory"); }

__device__ __forceinline__ void wgmma_n48_first(float (&e)[24], const uint32_t (&a)[4], uint32_t bdesc) {
    asm volatile("{\n.reg .b64 b;\nmov.b64 b, {%28, " DESC_HI "};\n"
                 "wgmma.mma_async.sync.aligned.m64n48k16.f32.bf16.bf16 {%0,%1,%2,%3,%4,%5,%6,%7,%8,%9,%10,%11,%12,%13,%14,%15,%16,%17,%18,%19,%20,%21,%22,%23}, {%24,%25,%26,%27}, b, 0, 1, 1, 1;\n}"
                 : "=f"(e[0]), "=f"(e[1]), "=f"(e[2]), "=f"(e[3]), "=f"(e[4]), "=f"(e[5]), "=f"(e[6]), "=f"(e[7]), "=f"(e[8]), "=f"(e[9]), "=f"(e[10]), "=f"(e[11]), "=f"(e[12]), "=f"(e[13]), "=f"(e[14]), "=f"(e[15]), "=f"(e[16]), "=f"(e[17]), "=f"(e[18]), "=f"(e[19]), "=f"(e[20]), "=f"(e[21]), "=f"(e[22]), "=f"(e[23])
                 : "r"(a[0]), "r"(a[1]), "r"(a[2]), "r"(a[3]), "r"(bdesc));
}
__device__ __forceinline__ void wgmma_n48(float (&e)[24], const uint32_t (&a)[4], uint32_t bdesc) {
    asm volatile("{\n.reg .b64 b;\nmov.b64 b, {%28, " DESC_HI "};\n"
                 "wgmma.mma_async.sync.aligned.m64n48k16.f32.bf16.bf16 {%0,%1,%2,%3,%4,%5,%6,%7,%8,%9,%10,%11,%12,%13,%14,%15,%16,%17,%18,%19,%20,%21,%22,%23}, {%24,%25,%26,%27}, b, 1, 1, 1, 1;\n}"
                 : "+f"(e[0]), "+f"(e[1]), "+f"(e[2]), "+f"(e[3]), "+f"(e[4]), "+f"(e[5]), "+f"(e[6]), "+f"(e[7]), "+f"(e[8]), "+f"(e[9]), "+f"(e[10]), "+f"(e[11]), "+f"(e[12]), "+f"(e[13]), "+f"(e[14]), "+f"(e[15]), "+f"(e[16]), "+f"(e[17]), "+f"(e[18]), "+f"(e[19]), "+f"(e[20]), "+f"(e[21]), "+f"(e[22]), "+f"(e[23])
                 : "r"(a[0]), "r"(a[1]), "r"(a[2]), "r"(a[3]), "r"(bdesc));
}
__device__ __forceinline__ void wgmma_n16_first(float (&d)[8], const uint32_t (&a)[4], uint32_t bdesc) {
    asm volatile("{\n.reg .b64 b;\nmov.b64 b, {%12, " DESC_HI "};\n"
                 "wgmma.mma_async.sync.aligned.m64n16k16.f32.bf16.bf16 {%0,%1,%2,%3,%4,%5,%6,%7}, {%8,%9,%10,%11}, b, 0, 1, 1, 1;\n}"
                 : "=f"(d[0]), "=f"(d[1]), "=f"(d[2]), "=f"(d[3]), "=f"(d[4]), "=f"(d[5]), "=f"(d[6]), "=f"(d[7])
                 : "r"(a[0]), "r"(a[1]), "r"(a[2]), "r"(a[3]), "r"(bdesc));
}
__device__ __forceinline__ void wgmma_n16(float (&d)[8], const uint32_t (&a)[4], uint32_t bdesc) {
    asm volatile("{\n.reg .b64 b;\nmov.b64 b, {%12, " DESC_HI "};\n"
                 "wgmma.mma_async.sync.aligned.m64n16k16.f32.bf16.bf16 {%0,%1,%2,%3,%4,%5,%6,%7}, {%8,%9,%10,%11}, b, 1, 1, 1, 1;\n}"
                 : "+f"(d[0]), "+f"(d[1]), "+f"(d[2]), "+f"(d[3]), "+f"(d[4]), "+f"(d[5]), "+f"(d[6]), "+f"(d[7])
                 : "r"(a[0]), "r"(a[1]), "r"(a[2]), "r"(a[3]), "r"(bdesc));
}

__device__ __forceinline__ void wgmma_n64_p(float (&d)[8], float (&e)[24], const uint32_t (&a)[4], uint32_t bdesc, int acc) {
    asm volatile("{\n.reg .pred p;\n.reg .b64 b;\nsetp.ne.b32 p, %37, 0;\nmov.b64 b, {%36, " DESC_HI "};\n"
                 "wgmma.mma_async.sync.aligned.m64n64k16.f32.bf16.bf16 {%0,%1,%2,%3,%4,%5,%6,%7,%8,%9,%10,%11,%12,%13,%14,%15,%16,%17,%18,%19,%20,%21,%22,%23,%24,%25,%26,%27,%28,%29,%30,%31}, {%32,%33,%34,%35}, b, p, 1, 1, 1;\n}"
                 : "+f"(d[0]), "+f"(d[1]), "+f"(d[2]), "+f"(d[3]), "+f"(d[4]), "+f"(d[5]), "+f"(d[6]), "+f"(d[7]),
                   "+f"(e[0]), "+f"(e[1]), "+f"(e[2]), "+f"(e[3]), "+f"(e[4]), "+f"(e[5]), "+f"(e[6]), "+f"(e[7]), "+f"(e[8]), "+f"(e[9]), "+f"(e[10]), "+f"(e[11]), "+f"(e[12]), "+f"(e[13]), "+f"(e[14]), "+f"(e[15]), "+f"(e[16]), "+f"(e[17]), "+f"(e[18]), "+f"(e[19]), "+f"(e[20]), "+f"(e[21]), "+f"(e[22]), "+f"(e[23])
                 : "r"(a[0]), "r"(a[1]), "r"(a[2]), "r"(a[3]), "r"(bdesc), "r"(acc));
}
__device__ __forceinline__ void wgmma_n16_p(float (&d)[8], const uint32_t (&a)[4], uint32_t bdesc, int acc) {
    asm volatile("{\n.reg .pred p;\n.reg .b64 b;\nsetp.ne.b32 p, %13, 0;\nmov.b64 b, {%12, " DESC_HI "};\n"
                 "wgmma.mma_async.sync.aligned.m64n16k16.f32.bf16.bf16 {%0,%1,%2,%3,%4,%5,%6,%7}, {%8,%9,%10,%11}, b, p, 1, 1, 1;\n}"
                 : "+f"(d[0]), "+f"(d[1]), "+f"(d[2]), "+f"(d[3]), "+f"(d[4]), "+f"(d[5]), "+f"(d[6]), "+f"(d[7])
                 : "r"(a[0]), "r"(a[1]), "r"(a[2]), "r"(a[3]), "r"(bdesc), "r"(acc));
}

__device__ __forceinline__ uint32_t edge_dist(uint32_t sxy, uint32_t sz, uint32_t dxy, uint32_t dz, uint32_t& rxy, uint32_t& rz) {
    rxy = hsub2(sxy, dxy);
    rz  = hsub2(sz, dz);
    uint32_t qxy = hmul2(rxy, rxy), qz = hmul2(rz, rz);
    float ss = rbf((bf_lo(qxy) + bf_hi(qxy)) + bf_lo(qz));
    float s2 = rbf(ss + 1e-8f);
    float d;
    asm("sqrt.approx.ftz.f32 %0, %1;" : "=f"(d) : "f"(s2));
    return pack_bf(d, 0.f) & 0xffffu;
}

__device__ __noinline__ float radial_value(float d, float f) {
    float arg = rbf(d * f);
    float sn  = rbf(sinf(arg));
    float rb  = rbf(__fdiv_rn(sn, d));
    float c   = rbf(cosf(rbf(__fdiv_rn(rbf(d * 3.14159265358979323846f), 5.0f))));
    float fc  = rbf(0.5f * rbf(c + 1.0f));
    return rb * fc;
}

__global__ void __launch_bounds__(NT, 1)
painn_kernel(const Params p, const __grid_constant__ CUtensorMap tmF, const __grid_constant__ CUtensorMap tmFs) {
    extern __shared__ __align__(1024) uint8_t smem[];
    const uint32_t sb   = smem_u32(smem);
    const int tid  = threadIdx.x, lane = tid & 31, warp = __shfl_sync(0xffffffffu, tid >> 5, 0);
    const int cta  = blockIdx.x;
    const int g    = lane >> 2, t = lane & 3;
    int* binCnt = (int*)(smem + SM_BINCNT);
    int* nCnt   = (int*)(smem + SM_NCNT);
    uint32_t* nInfo = (uint32_t*)(smem + SM_NINFO);
    volatile int* ctrl = (volatile int*)(smem + SM_CTRL);
    const uint32_t bar_pos = sb + SM_BARS;
    const uint32_t bar_full = bar_pos + 32, bar_empty = bar_full + NCWG * MAX_STAGE * 8;
    const uint32_t bar_hfull = bar_empty + NCWG * MAX_STAGE * 8, bar_hempty = bar_hfull + 32;

    const int node0  = cta * p.npc;
    const int nnodes = max(0, min(p.npc, p.N - node0));

    STAMP(0);
    if (tid == 32) {
        mbar_init(bar_pos, 1);
        asm volatile("fence.mbarrier_init.release.cluster;" ::: "memory");
        uint32_t pos_bytes = (uint32_t)(p.N * 6 + 15) & ~15u;
        mbar_expect_tx(bar_pos, pos_bytes);
        bulk_g2s(sb + P1_POS, p.pos, pos_bytes, bar_pos);
    } else if (tid == 64) {
        for (int i = 0; i < 4; i++) { mbar_init(bar_hfull + 8 * i, 4); mbar_init(bar_hempty + 8 * i, 4); }
        asm volatile("prefetch.tensormap [%0];" ::"l"(&tmF) : "memory");
        asm volatile("prefetch.tensormap [%0];" ::"l"(&tmFs) : "memory");
    } else if (tid >= 96 && tid < 96 + NCWG * MAX_STAGE) {
        mbar_init(bar_full + 8 * (tid - 96), 2);
        mbar_init(bar_empty + 8 * (tid - 96), 4);
    }
    unsigned bar_seen = 0;
    if (tid == 0 || tid == 32) asm volatile("ld.relaxed.gpu.global.u32 %0, [%1];" : "=r"(bar_seen) : "l"(&g_bar[tid >> 5]) : "memory");
    const bool mlp_warp = warp >= 6;
    int4 s4[3], d4[3];
    const int q0 = cta * p.quads_per_cta;
    const int qend = min(q0 + p.quads_per_cta, p.E >> 2);
#pragma unroll
    for (int k = 0; k < 3; k++) {
        const int q = q0 + (k < 2 ? warp + 16 * k : 32 + warp) * 32 + lane;
        const bool ok = q < qend && (k < 2 || !mlp_warp);
        s4[k] = ok ? __ldg((const int4*)p.src + q) : make_int4(-1, -1, -1, -1);
        d4[k] = ok ? __ldg((const int4*)p.dst + q) : make_int4(0, 0, 0, 0);
    }
    if (tid < MAX_CTA) binCnt[tid] = 0;
    if (tid < MAX_NPC) nCnt[tid] = 0;
    if (tid < 16) ctrl[tid] = 0;
    if (tid >= 256 && tid < 256 + 240) {
        const int i = tid - 256;
        asm volatile("prefetch.global.L2 [%0];" ::"l"(i < 48 ? (const uint8_t*)p.wr + i * 128 : (const uint8_t*)p.w2 + (i - 48) * 128));
    }
    for (int i = P1_SEGA / 16 + tid; i < P1_SV / 16; i += NT) sts128(sb + i * 16, make_uint4(0u, 0u, 0u, 0u));
    for (int i = tid; i < 4 * (MAX_NPC - nnodes) * 8; i += NT)
        sts128(sb + P1_SV + (i / ((MAX_NPC - nnodes) * 8)) * (MAX_NPC * 128) + nnodes * 128 + (i % ((MAX_NPC - nnodes) * 8)) * 16, make_uint4(0u, 0u, 0u, 0u));
    __syncthreads();

    mbar_wait(bar_pos, 0);
    if (s4[0].x == 0x7fffffff) ctrl[15] = 1;
    for (int i = tid; i < nnodes * 32; i += NT) {
        const int r = i >> 5, b = (i >> 3) & 3, c = i & 7;
        cp_async16(sb + P1_SV + b * (MAX_NPC * 128) + r * 128 + ((c ^ (r & 7)) << 4), (const uint8_t*)p.sv + (size_t)node0 * 512 + i * 16);
    }
    for (int i = tid; i < 1024; i += NT) {
        const int m = i >> 9, k = (i >> 3) & 63, c = i & 7;
        cp_async16(sb + P1_W1 + m * 8192 + k * 128 + ((c ^ (k & 7)) << 4),
                   m == 0 ? (const uint8_t*)p.w1 + k * 128 + c * 16 : (const uint8_t*)p.w2 + k * 384 + 128 + c * 16);
    }
    asm volatile("cp.async.commit_group;" ::: "memory");
    STAMP(1);
#pragma unroll
    for (int k = 0; k < 3; k++) {
        const int ss[4] = {s4[k].x, s4[k].y, s4[k].z, s4[k].w};
        const int dd[4] = {d4[k].x, d4[k].y, d4[k].z, d4[k].w};
        if (ss[0] >= 0) {
            uint32_t w0[4], w1[4], v0[4], v1[4], r0[4], r1[4], r2[4], bin[4], rank[4];
#pragma unroll
            for (int j = 0; j < 4; j++) {
                const uint32_t a = (sb + P1_POS + 6u * (uint32_t)ss[j]) & ~3u, c = (sb + P1_POS + 6u * (uint32_t)dd[j]) & ~3u;
                w0[j] = lds32(a); w1[j] = lds32(a + 4); v0[j] = lds32(c); v1[j] = lds32(c + 4);
            }
#pragma unroll
            for (int j = 0; j < 4; j++) {
                const uint32_t sh = (uint32_t)ss[j] << 4, dh = (uint32_t)dd[j] << 4;
                uint32_t rxy, rz;
                const uint32_t db = edge_dist(__funnelshift_r(w0[j], w1[j], sh), __funnelshift_r(w1[j], w1[j], sh),
                                              __funnelshift_r(v0[j], v1[j], dh), __funnelshift_r(v1[j], v1[j], dh), rxy, rz);
                float inv;
                asm("rcp.approx.ftz.f32 %0, %1;" : "=f"(inv) : "f"(__uint_as_float(db << 16)));
                bin[j] = __umulhi((uint32_t)dd[j], p.npc_magic);
                r0[j] = (uint32_t)ss[j] | ((db - D_MIN_BITS) << 16);
                r1[j] = pack_bf(bf_lo(rxy) * inv, bf_hi(rxy) * inv);
                r2[j] = __byte_perm(pack_bf(bf_lo(rz) * inv, 0.f), (uint32_t)dd[j] - bin[j] * (uint32_t)p.npc, 0x5410);
                rank[j] = db <= D_MAX_BITS ? (uint32_t)atomicAdd(&binCnt[bin[j]], 1) : 0xffffu;
            }
#pragma unroll
            for (int j = 0; j < 4; j++) {
                if (rank[j] < SEG_CAP) {
                    const uint32_t slot = bin[j] * SEG_CAP + rank[j];
                    asm volatile("st.shared.v2.u32 [%0], {%1, %2};" ::"r"(sb + P1_SEGA + slot * 8), "r"(r0[j]), "r"(r1[j]) : "memory");
                    sts32(sb + P1_SEGB + slot * 4, r2[j]);
                }
            }
        }
    }
    __syncthreads();
    STAMP(2);
    {
        constexpr int IT = (MAX_CTA + 31) / 32;
        uint2 ca[IT][2];
        uint32_t cb[IT][2];
        int cn[IT];
#pragma unroll
        for (int it = 0; it < IT; it++) {
            const int b = min(2 * warp + (lane >> 4) + 32 * it, MAX_CTA - 1);
            cn[it] = binCnt[b];
#pragma unroll
            for (int u = 0; u < 2; u++) {
                const int j = (lane & 15) + 16 * u;
                ca[it][u] = lds64(sb + P1_SEGA + (b * SEG_CAP + j) * 8);
                cb[it][u] = lds32(sb + P1_SEGB + (b * SEG_CAP + j) * 4);
            }
        }
#pragma unroll
        for (int it = 0; it < IT; it++) {
            const int b = 2 * warp + (lane >> 4) + 32 * it;
            if (b < p.ncta) {
                uint32_t* dstp = g_seg + ((size_t)cta * MAX_CTA + b) * (SEG_CAP * 3);
                const uint32_t tag = (uint32_t)min(cn[it], 511) << 23;
#pragma unroll
                for (int u = 0; u < 2; u++) {
                    const int j = (lane & 15) + 16 * u;
                    *(uint2*)(dstp + 2 * j) = ca[it][u];
                    dstp[2 * SEG_CAP + j] = cb[it][u] | tag;
                }
                for (int j = 32 + (lane & 15); j < ((min(cn[it], SEG_CAP) + 7) & ~7); j += 16) {
                    *(uint2*)(dstp + 2 * j) = lds64(sb + P1_SEGA + (b * SEG_CAP + j) * 8);
                    dstp[2 * SEG_CAP + j] = lds32(sb + P1_SEGB + (b * SEG_CAP + j) * 4);
                }
            }
        }
    }
    STAMP(7);
    asm volatile("cp.async.wait_group 0;" ::: "memory");
    __syncthreads();
    STAMP(3);
    if (tid == 64) asm volatile("red.add.release.gpu.global.u32 [%0], 1;" ::"l"(&g_bar[0]) : "memory");

    if (!mlp_warp) {
        const int rows_per = (TAB_ROWS + 1 + p.ncta - 1) / p.ncta;
        for (int i = tid; i < rows_per * 8; i += 6 * 32) {
            int row = cta * rows_per + (i >> 3), kp = i & 7;
            if (row <= TAB_ROWS) {
                uint32_t val = 0;
                if (row < TAB_ROWS) {
                    float d = __uint_as_float((D_MIN_BITS + row) << 16);
                    uint32_t f2 = __ldg((const uint32_t*)p.freqs + kp);
                    val = pack_bf(radial_value(d, bf_lo(f2)), radial_value(d, bf_hi(f2)));
                }
                ((uint32_t*)g_table)[row * 8 + kp] = val;
            }
        }
    } else {
        const int mt = (warp - 6) >> 1, hf = (warp - 6) & 1;
        if (mt * 16 < nnodes) {
            STAMPT(10, 6 * 32);
            const int lrow = lane & 15, lch = lane >> 4;
            const uint32_t rowb = sb + P1_SV + (mt * 16 + lrow) * 128;
            const uint32_t key0 = lrow & 7;
            float acc[4][4];
#pragma unroll
            for (int i = 0; i < 4; i++) { acc[i][0] = acc[i][1] = acc[i][2] = acc[i][3] = 0.f; }
#pragma unroll
            for (int ks = 0; ks < 4; ks++) {
                uint32_t a[4];
                ldsm4(a, rowb + (((2 * ks + lch) ^ key0) << 4));
                const int kk = 16 * ks + lrow;
#pragma unroll
                for (int nt = 0; nt < 4; nt += 2) {
                    uint32_t b[4];
                    ldsm4t(b, sb + P1_W1 + kk * 128 + (((4 * hf + nt + lch) ^ (kk & 7)) << 4));
                    mma16816(acc[nt], a, b[0], b[1]);
                    mma16816(acc[nt + 1], a, b[2], b[3]);
                }
            }
            uint32_t hp[4][2];
#pragma unroll
            for (int i = 0; i < 4; i++) {
                float h[4];
#pragma unroll
                for (int q = 0; q < 4; q++) {
                    float x = rbf(acc[i][q]);
                    h[q] = __fdividef(x, 1.0f + __expf(-x));
                    acc[i][q] = 0.f;
                }
                hp[i][0] = pack_bf(h[0], h[1]);
                hp[i][1] = pack_bf(h[2], h[3]);
            }
            asm volatile("bar.sync %0, 64;" ::"r"(4 + mt) : "memory");
#pragma unroll
            for (int i = 0; i < 4; i += 2)
                stsm4(rowb + (((4 * hf + i + lch) ^ key0) << 4), hp[i][0], hp[i][1], hp[i + 1][0], hp[i + 1][1]);
            asm volatile("bar.sync %0, 64;" ::"r"(4 + mt) : "memory");
#pragma unroll
            for (int ks = 0; ks < 4; ks++) {
                uint32_t a[4];
                ldsm4(a, rowb + (((2 * ks + lch) ^ key0) << 4));
                const int kk = 16 * ks + lrow;
#pragma unroll
                for (int nt = 0; nt < 4; nt += 2) {
                    uint32_t b[4];
                    ldsm4t(b, sb + P1_W2 + kk * 128 + (((4 * hf + nt + lch) ^ (kk & 7)) << 4));
                    mma16816(acc[nt], a, b[0], b[1]);
                    mma16816(acc[nt + 1], a, b[2], b[3]);
                }
            }
            uint32_t vq[2][3][4];
            const uint32_t vb = sb + P1_SV + (mt * 16 + g) * 128 + 4 * t;
#pragma unroll
            for (int rh = 0; rh < 2; rh++)
#pragma unroll
                for (int a = 0; a < 3; a++)
#pragma unroll
                    for (int i = 0; i < 4; i++) vq[rh][a][i] = lds32(vb + (a + 1) * (MAX_NPC * 128) + rh * 1024 + (((4 * hf + i) ^ g) << 4));
#pragma unroll
            for (int rh = 0; rh < 2; rh++)
#pragma unroll
                for (int a = 0; a < 3; a++)
#pragma unroll
                    for (int i = 0; i < 4; i++)
                        sts32(vb + (a + 1) * (MAX_NPC * 128) + rh * 1024 + (((4 * hf + i) ^ g) << 4),
                              hmul2(pack_bf(acc[i][2 * rh], acc[i][2 * rh + 1]), vq[rh][a][i]));
            fence_async_smem();
            asm volatile("bar.sync %0, 64;" ::"r"(4 + mt) : "memory");
            {
                const int r4 = mt * 16 + 8 * hf + 4 * (lane >> 2), comp = lane & 3;
                if (lane < 8 && r4 < nnodes) tma_store3(&tmFs, comp, node0 + r4, sb + P1_SV + comp * (MAX_NPC * 128) + r4 * 128);
            }
            asm volatile("cp.async.bulk.commit_group;" ::: "memory");
        }
        STAMPT(11, 6 * 32);
    }
    if (tid == 0) {
        const unsigned target = (bar_seen / (unsigned)p.ncta + 1u) * (unsigned)p.ncta;
        unsigned cur;
        int spins = 0;
        do {
            asm volatile("ld.acquire.gpu.global.u32 %0, [%1];" : "=r"(cur) : "l"(&g_bar[0]) : "memory");
        } while ((int)(cur - target) < 0 && ++spins < (1 << 24));
    }
    STAMP(4);
    __syncthreads();
    STAMP(5);

    constexpr int SEG_IT = (MAX_CTA + 31) / 32;
    uint2 ra[SEG_IT][2];
    uint32_t rb[SEG_IT][2], rr[SEG_IT][2];
#pragma unroll
    for (int it = 0; it < SEG_IT; it++) {
        const int b = 2 * warp + (lane >> 4) + 32 * it;
        const uint32_t* sp = g_seg + ((size_t)b * MAX_CTA + cta) * (SEG_CAP * 3);
#pragma unroll
        for (int u = 0; u < 2; u++) {
            const int j = (lane & 15) + 16 * u;
            ra[it][u] = b < p.ncta ? __ldcg((const uint2*)(sp + 2 * j)) : make_uint2(0u, 0u);
            rb[it][u] = b < p.ncta ? __ldcg(sp + 2 * SEG_CAP + j) : 0u;
        }
    }
    if (mlp_warp && lane < 8) {
        asm volatile("cp.async.bulk.wait_group 0;" ::: "memory");
        asm volatile("fence.proxy.async;" ::: "memory");
    }
    STAMP(9);
    uint2 xa[SEG_IT];
    uint32_t xb[SEG_IT];
#pragma unroll
    for (int it = 0; it < SEG_IT; it++) {
        const int cnt = rb[it][0] >> 23;
        const int b = 2 * warp + (lane >> 4) + 32 * it;
        const uint32_t* sp = g_seg + ((size_t)b * MAX_CTA + cta) * (SEG_CAP * 3);
        const bool has = 32 + (lane & 15) < cnt;
        xa[it] = has ? __ldcg((const uint2*)(sp + 2 * (32 + (lane & 15)))) : make_uint2(0u, 0u);
        xb[it] = has ? __ldcg(sp + 2 * SEG_CAP + 32 + (lane & 15)) : 0u;
    }
#pragma unroll
    for (int it = 0; it < SEG_IT; it++) {
        const int cnt = rb[it][0] >> 23;
        if (cnt > SEG_CAP) ctrl[1] = 1;
#pragma unroll
        for (int u = 0; u < 2; u++)
            rr[it][u] = (lane & 15) + 16 * u < cnt ? (uint32_t)atomicAdd(&nCnt[(rb[it][u] >> 16) & 0x7fu], 1) : 0xffffffffu;
    }
#pragma unroll
    for (int it = 0; it < SEG_IT; it++) {
        const int cnt = rb[it][0] >> 23;
        if (32 + (lane & 15) < cnt) {
            const int pos = atomicAdd((int*)&ctrl[8], 1);
            const uint32_t rank = (uint32_t)atomicAdd(&nCnt[(xb[it] >> 16) & 0x7fu], 1);
            if (pos < STAGE_CAP) sts128(sb + P1_REC + pos * 16, make_uint4(xa[it].x, xa[it].y, xb[it], rank));
        }
        if (cnt > 48) {
            const int b = 2 * warp + (lane >> 4) + 32 * it;
            const uint32_t* sp = g_seg + ((size_t)b * MAX_CTA + cta) * (SEG_CAP * 3);
            const int j = 48 + (lane & 15);
            if (j < min(cnt, SEG_CAP)) {
                const uint2 a = __ldcg((const uint2*)(sp + 2 * j));
                const uint32_t c = __ldcg(sp + 2 * SEG_CAP + j);
                const int pos = atomicAdd((int*)&ctrl[8], 1);
                const uint32_t rank = (uint32_t)atomicAdd(&nCnt[(c >> 16) & 0x7fu], 1);
                if (pos < STAGE_CAP) sts128(sb + P1_REC + pos * 16, make_uint4(a.x, a.y, c, rank));
            }
        }
    }
    STAMP(13);
    __syncthreads();
    if (tid == 64) asm volatile("red.add.release.gpu.global.u32 [%0], 1;" ::"l"(&g_bar[1]) : "memory");
    STAMP(14);
    const int total = ctrl[8];
    if (tid == 0 && total > STAGE_CAP) ctrl[1] = 1;
    if (warp == 0) {
        int c[3], s = 0;
#pragma unroll
        for (int i = 0; i < 3; i++) {
            int b = lane * 3 + i;
            c[i] = b < nnodes ? max(16, (nCnt[b] + 15) & ~15) : 0;
            s += c[i];
        }
        int x = s;
#pragma unroll
        for (int o = 1; o < 32; o <<= 1) { int y = __shfl_up_sync(0xffffffffu, x, o); if (lane >= o) x += y; }
        const int slots = __shfl_sync(0xffffffffu, x, 31);
        int off = x - s, below = 0;
#pragma unroll
        for (int i = 0; i < 3; i++) {
            int b = lane * 3 + i;
            if (b < nnodes) {
                nInfo[b] = (uint32_t)off | ((uint32_t)c[i] << 16);
                below += (2 * off + c[i] < slots);
            }
            off += c[i];
        }
        below = __reduce_add_sync(0xffffffffu, below);
        if (lane == 0) {
            ctrl[2] = below;
            ctrl[4] = slots;
            if (slots > SLOT_CAP) ctrl[1] = 1;
        }
    }
    __syncthreads();
    if (ctrl[1] == 0) {
        uint16_t* sid = (uint16_t*)(smem + SM_SID);
        uint2* meta = (uint2*)(smem + SM_META);
#pragma unroll
        for (int it = 0; it < SEG_IT; it++)
#pragma unroll
            for (int u = 0; u < 2; u++)
                if (rr[it][u] != 0xffffffffu) rr[it][u] += lds32(sb + SM_NINFO + ((rb[it][u] >> 16) & 0x7fu) * 4) & 0xffffu;
#pragma unroll
        for (int it = 0; it < SEG_IT; it++)
#pragma unroll
            for (int u = 0; u < 2; u++)
                if (rr[it][u] != 0xffffffffu) {
                    sid[rr[it][u]]  = (uint16_t)((ra[it][u].x & 0xffffu) << 2);
                    meta[rr[it][u]] = make_uint2(((ra[it][u].x >> 16) << 5) | (rb[it][u] << 16), ra[it][u].y);
                }
        for (int i = tid; i < total; i += NT) {
            const uint4 r = lds128(sb + P1_REC + i * 16);
            const int pos = (int)(lds32(sb + SM_NINFO + ((r.z >> 16) & 0x7fu) * 4) & 0xffffu) + (int)r.w;
            sid[pos]  = (uint16_t)((r.x & 0xffffu) << 2);
            meta[pos] = make_uint2(((r.x >> 16) << 5) | (r.z << 16), r.y);
        }
        if (tid >= NT - 128 && tid - (NT - 128) < nnodes) {
            const int b = tid - (NT - 128), split = ctrl[2];
            const int mid = split < nnodes ? (int)(nInfo[split] & 0xffffu) : ctrl[4];
            const int st = b >= split;
            const int mine = (int)(nInfo[b] & 0xffffu) + (int)(nInfo[b] >> 16) - (st ? mid : 0);
            int lo = st ? 0 : split, hi = st ? split : nnodes;
            const int first = lo;
            while (lo < hi) {
                const int o = (lo + hi) >> 1;
                const int other = (int)(nInfo[o] & 0xffffu) + (int)(nInfo[o] >> 16) - (st ? 0 : mid);
                if (st ? (other <= mine) : (other < mine)) lo = o + 1; else hi = o;
            }
            const int rank = (st ? b - split : b) + lo - first;
            smem[SM_ORDER + rank] = (uint8_t)(b | (st << 7));
        }
        for (int i = tid; i < nnodes * 16; i += NT) {
            int nl = i >> 4, c = nCnt[nl];
            int j = (c & ~15) + (i & 15);
            if (j >= c && (j < 16 || (c & 15))) {
                int pos = (int)(nInfo[nl] & 0xffffu) + j;
                sid[pos]  = 0xffffu;
                meta[pos] = make_uint2((uint32_t)TAB_ZERO << 5, 0u);
            }
        }
    }
    STAMP(15);
    if (tid == 32) {
        const unsigned target = (bar_seen / (unsigned)p.ncta + 1u) * (unsigned)p.ncta;
        unsigned cur;
        int spins = 0;
        do {
            asm volatile("ld.acquire.gpu.global.u32 %0, [%1];" : "=r"(cur) : "l"(&g_bar[1]) : "memory");
        } while ((int)(cur - target) < 0 && ++spins < (1 << 24));
        asm volatile("fence.proxy.async.global;" ::: "memory");
    }
    fence_async_smem();
    __syncthreads();
    STAMP(6);

    if (__shfl_sync(0xffffffffu, ctrl[1], 0) != 0) {
        float* acc = (float*)(smem + P1_POS);
        for (int i = tid; i < nnodes * 256; i += NT) acc[i] = 0.f;
        __syncthreads();
        const uint16_t* posu = (const uint16_t*)p.pos;
        const uint32_t* tabg = (const uint32_t*)g_table;
        const uint32_t* Fw = (const uint32_t*)g_F;
        for (int e0 = warp * 32; e0 < p.E; e0 += NT) {
            int e = e0 + lane;
            int s = 0, d = 0;
            uint32_t db = 0xffff, rxy = 0, rz = 0;
            bool act = false;
            if (e < p.E) {
                s = p.src[e]; d = p.dst[e];
                if (d >= node0 && d < node0 + nnodes) {
                    uint32_t sxy = posu[s * 3] | ((uint32_t)posu[s * 3 + 1] << 16), sz = posu[s * 3 + 2];
                    uint32_t dxy = posu[d * 3] | ((uint32_t)posu[d * 3 + 1] << 16), dz = posu[d * 3 + 2];
                    db  = edge_dist(sxy, sz, dxy, dz, rxy, rz);
                    act = db <= D_MAX_BITS;
                }
            }
            unsigned m = __ballot_sync(0xffffffffu, act);
            while (m) {
                int l = __ffs(m) - 1;
                m &= m - 1;
                int es = __shfl_sync(0xffffffffu, s, l), ed = __shfl_sync(0xffffffffu, d, l);
                uint32_t edb = __shfl_sync(0xffffffffu, db, l), exy = __shfl_sync(0xffffffffu, rxy, l), ez = __shfl_sync(0xffffffffu, rz, l);
                float inv = 1.0f / __uint_as_float(edb << 16);
                float rh[3] = {rbf(bf_lo(exy) * inv), rbf(bf_hi(exy) * inv), rbf(bf_lo(ez) * inv)};
                const uint32_t* fr = Fw + (size_t)es * 128 + lane;
                const uint32_t fh = __ldcg(fr);
                const uint32_t q[3] = {__ldcg(fr + 32), __ldcg(fr + 64), __ldcg(fr + 96)};
                float ps0 = 0.f, ps1 = 0.f, pr0 = 0.f, pr1 = 0.f;
                for (int j2 = 0; j2 < 32; j2++) {
                    uint32_t hj = __shfl_sync(0xffffffffu, fh, j2);
                    uint32_t a0 = *(const uint32_t*)(p.w2 + (2 * j2) * 192 + 2 * lane), a1 = *(const uint32_t*)(p.w2 + (2 * j2 + 1) * 192 + 2 * lane);
                    uint32_t b0 = *(const uint32_t*)(p.w2 + (2 * j2) * 192 + 128 + 2 * lane), b1 = *(const uint32_t*)(p.w2 + (2 * j2 + 1) * 192 + 128 + 2 * lane);
                    ps0 += bf_lo(hj) * bf_lo(a0) + bf_hi(hj) * bf_lo(a1);
                    ps1 += bf_lo(hj) * bf_hi(a0) + bf_hi(hj) * bf_hi(a1);
                    pr0 += bf_lo(hj) * bf_lo(b0) + bf_hi(hj) * bf_lo(b1);
                    pr1 += bf_lo(hj) * bf_hi(b0) + bf_hi(hj) * bf_hi(b1);
                }
                float ws0 = 0.f, ws1 = 0.f, wv0 = 0.f, wv1 = 0.f, wr0 = 0.f, wr1 = 0.f;
                for (int k2 = 0; k2 < 8; k2++) {
                    uint32_t rk2 = __ldcg(tabg + (edb - D_MIN_BITS) * 8 + k2);
#pragma unroll
                    for (int h = 0; h < 2; h++) {
                        float rv = h ? bf_hi(rk2) : bf_lo(rk2);
                        const __nv_bfloat16* wrow = p.wr + (2 * k2 + h) * 192 + 2 * lane;
                        uint32_t a = *(const uint32_t*)wrow, b = *(const uint32_t*)(wrow + 64), c = *(const uint32_t*)(wrow + 128);
                        ws0 += rv * bf_lo(a); ws1 += rv * bf_hi(a);
                        wv0 += rv * bf_lo(b); wv1 += rv * bf_hi(b);
                        wr0 += rv * bf_lo(c); wr1 += rv * bf_hi(c);
                    }
                }
                float* a = acc + (ed - node0) * 256 + 2 * lane;
                atomicAdd(a, ps0 * ws0); atomicAdd(a + 1, ps1 * ws1);
#pragma unroll
                for (int c = 0; c < 3; c++) {
                    atomicAdd(a + 64 * (c + 1), wv0 * bf_lo(q[c]) + pr0 * wr0 * rh[c]);
                    atomicAdd(a + 64 * (c + 1) + 1, wv1 * bf_hi(q[c]) + pr1 * wr1 * rh[c]);
                }
            }
        }
        __syncthreads();
        for (int i = tid; i < nnodes * 128; i += NT) {
            uint32_t r = *(const uint32_t*)(p.sv + (size_t)node0 * 256 + 2 * i);
            *(uint32_t*)(p.out + (size_t)node0 * 256 + 2 * i) = pack_bf(bf_lo(r) + acc[2 * i], bf_hi(r) + acc[2 * i + 1]);
        }
        return;
    }

    const int slots = __reduce_max_sync(0xffffffffu, ctrl[4]);
    const int split = __reduce_max_sync(0xffffffffu, ctrl[2]);
    constexpr int nstage = MAX_STAGE;
    const uint32_t ring = sb + SM_RING;
    const int mid = __reduce_max_sync(0xffffffffu, split < nnodes ? (int)(nInfo[split] & 0xffffu) : slots) >> 4;
    const int wgi = warp >> 2, w = warp & 3;
    uint32_t wp[3][4];
    if (wgi < 3) {
        const uint16_t* wr = (const uint16_t*)p.wr + 16 * w + g;
#pragma unroll
        for (int ty = 0; ty < 3; ty++) {
#pragma unroll
            for (int i = 0; i < 4; i++) {
                const uint16_t* q = wr + (8 * (i >> 1) + 2 * t) * 192 + ty * 64 + 8 * (i & 1);
                wp[ty][i] = (uint32_t)__ldg(q) | ((uint32_t)__ldg(q + 192) << 16);
            }
        }
    }
    constexpr uint32_t EMPTY_OFF = NCWG * MAX_STAGE * 8;
    if (wgi == 3) {
        const int sc = w >> 1, r = w & 1;
        const int g0 = (sc == 0 ? 0 : mid) + r, g1 = sc == 0 ? mid : slots >> 4;
        const uint32_t ring_wg = ring + sc * nstage * STAGE_B, full_wg = bar_full + sc * MAX_STAGE * 8;
        const int e = lane >> 1, half = lane & 1;
        const uint32_t coef_off = e * 128 + ((half ^ (e & 7)) << 4);
        const int vrot = (e & 3) ^ ((e >> 1) & 3);
        const uint8_t* tab = (const uint8_t*)g_table + half * 16;
        int stage = r;
        uint32_t phase = 1;
        uint32_t ma = sb + SM_META + (g0 * 16 + e) * 8, ida = sb + SM_SID + g0 * 32;
        uint2 m = make_uint2(0u, 0u);
        uint4 tv = make_uint4(0u, 0u, 0u, 0u), ia = tv, ib = tv;
        if (g0 < g1) {
            m  = lds64(ma);
            ia = lds128(ida);
            ib = lds128(ida + 16);
            tv = __ldg((const uint4*)(tab + (m.x & 0xffffu)));
        }
        for (int left = (g1 - g0 + 1) >> 1; left > 0; left--) {
            const uint32_t st = ring_wg + stage * STAGE_B, fb = full_wg + stage * 8;
            ma += 256; ida += 64;
            uint2 mn = m;
            if (left > 1) mn = lds64(ma);
            mbar_wait(fb + EMPTY_OFF, phase);
            uint32_t leader;
            asm volatile("{\n.reg .pred p;\nelect.sync _|p, 0xffffffff;\nselp.u32 %0, 1, 0, p;\n}" : "=r"(leader));
            if (leader) {
                const uint32_t id2[8] = {ia.x, ia.y, ia.z, ia.w, ib.x, ib.y, ib.z, ib.w};
                const uint32_t rows = st + 2048;
                if ((ib.w >> 16) != 0xffffu) {
                    mbar_expect_tx(fb, 16 * 512);
#pragma unroll
                    for (int i = 0; i < 8; i++) {
                        tma_load(rows + (2 * i) * 640, &tmF, (int)(id2[i] & 0xffffu), fb);
                        tma_load(rows + (2 * i + 1) * 640, &tmF, (int)(id2[i] >> 16), fb);
                    }
                } else {
                    int nv = 0;
#pragma unroll
                    for (int i = 0; i < 8; i++) nv += ((id2[i] & 0xffffu) != 0xffffu) + ((id2[i] >> 16) != 0xffffu);
                    mbar_expect_tx(fb, (uint32_t)nv * 512u);
#pragma unroll
                    for (int q = 0; q < 4; q++) {
                        if (4 * q + 4 <= nv) {
                            tma_load(rows + (4 * q) * 640, &tmF, (int)(id2[2 * q] & 0xffffu), fb);
                            tma_load(rows + (4 * q + 1) * 640, &tmF, (int)(id2[2 * q] >> 16), fb);
                            tma_load(rows + (4 * q + 2) * 640, &tmF, (int)(id2[2 * q + 1] & 0xffffu), fb);
                            tma_load(rows + (4 * q + 3) * 640, &tmF, (int)(id2[2 * q + 1] >> 16), fb);
                        } else {
                            if (4 * q < nv)     tma_load(rows + (4 * q) * 640, &tmF, (int)(id2[2 * q] & 0xffffu), fb);
                            if (4 * q + 1 < nv) tma_load(rows + (4 * q + 1) * 640, &tmF, (int)(id2[2 * q] >> 16), fb);
                            if (4 * q + 2 < nv) tma_load(rows + (4 * q + 2) * 640, &tmF, (int)(id2[2 * q + 1] & 0xffffu), fb);
                        }
                    }
                }
            }
            __syncwarp();
            uint4 o[4];
            {
                const uint32_t mul[4] = {0x3f803f80u, __byte_perm(m.y, 0, 0x1010), __byte_perm(m.y, 0, 0x3232), __byte_perm(m.x, 0, 0x3232)};
#pragma unroll
                for (int j = 0; j < 4; j++) {
                    const int v = j ^ vrot;
                    const uint32_t lo = (v & 1) ? mul[1] : mul[0], hi = (v & 1) ? mul[3] : mul[2];
                    const uint32_t mm = (v & 2) ? hi : lo;
                    o[j] = make_uint4(hmul2(tv.x, mm), hmul2(tv.y, mm), hmul2(tv.z, mm), hmul2(tv.w, mm));
                }
            }
            m = mn;
            if (left > 1) {
                ia = lds128(ida);
                ib = lds128(ida + 16);
                tv = __ldg((const uint4*)(tab + (m.x & 0xffffu)));
            }
            const uint32_t a = st + coef_off;
#pragma unroll
            for (int j = 0; j < 4; j++) sts128(a ^ ((j ^ vrot) << 5), o[j]);
            fence_async_smem();
            __syncwarp();
            mbar_arrive_elected(fb);
            stage += 2;
            if (stage >= nstage) { stage -= nstage; phase ^= 1; }
        }
    } else if (wgi == 2) {
        uint32_t wA[2][4][4];
        {
            const uint16_t* w2 = (const uint16_t*)p.w2 + 16 * w + g;
#pragma unroll
            for (int mk = 0; mk < 8; mk++) {
#pragma unroll
                for (int i = 0; i < 4; i++) {
                    const uint16_t* q = w2 + (16 * (mk & 3) + 2 * t + 8 * (i >> 1)) * 192 + (mk >> 2) * 128 + 8 * (i & 1);
                    wA[mk >> 2][mk & 3][i] = (uint32_t)__ldg(q) | ((uint32_t)__ldg(q + 192) << 16);
                }
            }
        }
        const uint32_t lane_off = (uint32_t)node0 * 512u + t * 128 + w * 32 + (g & 1) * 16 + (g >> 1) * 4;
        uint32_t hcnt[2] = {0u, 0u};
        float zs[8], zv[24], pvv[6], pr[4][2];
        uint32_t hbuf = 0;
        auto start = [&](int ent) {
            const int c = ent >> 7;
            const uint32_t k = c ? hcnt[1] : hcnt[0];
            hbuf = 2 * c + (k & 1);
            mbar_wait(bar_hfull + hbuf * 8, (k >> 1) & 1);
            if (c) hcnt[1]++; else hcnt[0]++;
            const uint32_t dht = desc_lo(sb + SM_HT + hbuf * 8192);
            wg_fence();
            wgmma_n16_first(zs, wA[0][0], dht);
            wgmma_n48_first(zv, wA[1][0], dht + 2);
#pragma unroll
            for (int ks = 1; ks < 4; ks++) {
                wgmma_n16(zs, wA[0][ks], dht + ks * 128);
                wgmma_n48(zv, wA[1][ks], dht + ks * 128 + 2);
            }
            wg_commit();
        };
        auto side = [&](int ent) {
            const uint32_t pa = sb + SM_PV + hbuf * 1536 + (tid & 127) * 4;
            const uint32_t a0 = lds32(pa), a1 = lds32(pa + 512), a2 = lds32(pa + 1024);
            pvv[0] = bf_lo(a0); pvv[1] = bf_hi(a0); pvv[2] = bf_lo(a1); pvv[3] = bf_hi(a1); pvv[4] = bf_lo(a2); pvv[5] = bf_hi(a2);
            __syncwarp();
            mbar_arrive_elected(bar_hempty + hbuf * 8);
        };
        auto weigh = [&]() {
#pragma unroll
            for (int i = 0; i < 12; i++) asm volatile("" : "+r"(wp[i >> 2][i & 3]));
            pr[0][0] = bf_lo(wp[0][0]) * zs[0] + bf_hi(wp[0][0]) * zs[1] + bf_lo(wp[0][2]) * zs[4] + bf_hi(wp[0][2]) * zs[5];
            pr[0][1] = bf_lo(wp[0][1]) * zs[2] + bf_hi(wp[0][1]) * zs[3] + bf_lo(wp[0][3]) * zs[6] + bf_hi(wp[0][3]) * zs[7];
#pragma unroll
            for (int a = 0; a < 3; a++) {
                const float* y = zv + 8 * a;
                pr[a + 1][0] = pvv[2 * a] + bf_lo(wp[2][0]) * y[0] + bf_hi(wp[2][0]) * y[1] + bf_lo(wp[2][2]) * y[4] + bf_hi(wp[2][2]) * y[5];
                pr[a + 1][1] = pvv[2 * a + 1] + bf_lo(wp[2][1]) * y[2] + bf_hi(wp[2][1]) * y[3] + bf_lo(wp[2][3]) * y[6] + bf_hi(wp[2][3]) * y[7];
            }
            asm volatile("" : "+f"(pr[0][0]), "+f"(pr[0][1]), "+f"(pr[1][0]), "+f"(pr[1][1]), "+f"(pr[2][0]), "+f"(pr[2][1]), "+f"(pr[3][0]), "+f"(pr[3][1]) :: "memory");
        };
        auto finish = [&](int ent, uint32_t resid) {
            const bool hi2 = t & 2, hi1 = t & 1, odd = g & 1;
            float ka0 = hi2 ? pr[2][0] : pr[0][0], ka1 = hi2 ? pr[2][1] : pr[0][1];
            float kb0 = hi2 ? pr[3][0] : pr[1][0], kb1 = hi2 ? pr[3][1] : pr[1][1];
            float sa0 = hi2 ? pr[0][0] : pr[2][0], sa1 = hi2 ? pr[0][1] : pr[2][1];
            float sb0 = hi2 ? pr[1][0] : pr[3][0], sb1 = hi2 ? pr[1][1] : pr[3][1];
            ka0 += __shfl_xor_sync(0xffffffffu, sa0, 2); ka1 += __shfl_xor_sync(0xffffffffu, sa1, 2);
            kb0 += __shfl_xor_sync(0xffffffffu, sb0, 2); kb1 += __shfl_xor_sync(0xffffffffu, sb1, 2);
            float k0 = hi1 ? kb0 : ka0, k1 = hi1 ? kb1 : ka1;
            float s0 = hi1 ? ka0 : kb0, s1 = hi1 ? ka1 : kb1;
            k0 += __shfl_xor_sync(0xffffffffu, s0, 1);
            k1 += __shfl_xor_sync(0xffffffffu, s1, 1);
            const float other = __shfl_xor_sync(0xffffffffu, odd ? k0 : k1, 4);
            const float lo = odd ? other : k0, hi = odd ? k1 : other;
            *(uint32_t*)((uint8_t*)p.out + (lane_off + (uint32_t)(ent & 127) * 512u)) = pack_bf(bf_lo(resid) + lo, bf_hi(resid) + hi);
        };
        auto entry = [&](int i) -> int { return __reduce_max_sync(0xffffffffu, (int)smem[SM_ORDER + i]); };
        auto load_resid = [&](int ent) -> uint32_t { return __ldg((const uint32_t*)((const uint8_t*)p.sv + (lane_off + (uint32_t)(ent & 127) * 512u))); };
        if (nnodes > 0) {
            int cur = entry(0), nxt = entry(1);
            uint32_t resid = load_resid(cur);
            start(cur);
#pragma unroll 1
            for (int i = 1; i < nnodes; i++) {
                wg_wait0();
                side(cur);
                weigh();
                start(nxt);
                finish(cur, resid);
                cur = nxt;
                resid = load_resid(cur);
                nxt = entry(i + 1);
            }
            wg_wait0();
            side(cur);
            weigh();
            finish(cur, resid);
        }
    } else {
        const int wg = wgi;
        uint32_t aoff[4];
        {
            const int e = (lane & 7) + 8 * (lane >> 4), ch = 2 * w + ((lane >> 3) & 1);
#pragma unroll
            for (int b = 0; b < 4; b++) aoff[b] = 2048 + e * 640 + b * 128 + ((ch ^ ((5 * e + b) & 7)) << 4);
        }
        const uint32_t stsm_0 = sb + SM_HT + wg * 16384 + (16 * w + (lane & 15)) * 128 + (((lane >> 4) ^ (lane & 7)) << 4);
        const uint32_t pv_0 = sb + SM_PV + wg * 3072 + (tid & 127) * 4;
        uint32_t hk = 0;
        const uint32_t ring_wg = ring + wg * nstage * STAGE_B;
        const uint32_t full_wg = bar_full + wg * MAX_STAGE * 8;

        float ys[8], yv[24], dQ[3][8];
        uint32_t A0[4][4], A1[4][4];
#pragma unroll
        for (int i = 0; i < 24; i++) yv[i] = 0.f;
#pragma unroll
        for (int i = 0; i < 8; i++) { ys[i] = 0.f; dQ[0][i] = 0.f; dQ[1][i] = 0.f; dQ[2][i] = 0.f; }
        int left = wg == 0 ? mid : (slots >> 4) - mid;
        int fstage = 0;
        uint32_t fphase = 0, fst = ring_wg, fbar = full_wg;
        uint32_t ninfo_a = sb + SM_NINFO + (wg == 0 ? 0 : split) * 4;
        int gi = 0, G = __reduce_max_sync(0xffffffffu, (int)(lds32(ninfo_a) >> 20));

        uint32_t ready = 0;
        auto fetch = [&](uint32_t (&A)[4][4], uint32_t& bd, uint32_t& eb) {
            if (!ready) mbar_wait(fbar, fphase);
            const uint32_t st = fst;
            bd = desc_lo(st);
            eb = fbar + EMPTY_OFF;
            fst += STAGE_B; fbar += 8;
            if (++fstage == nstage) { fstage = 0; fphase ^= 1; fst = ring_wg; fbar = full_wg; }
            ready = __all_sync(0xffffffffu, ldsm4t_x4_probe(A, st + aoff[0], st + aoff[1], st + aoff[2], st + aoff[3], fbar, fphase));
        };
        uint32_t notify = 0;
        auto signal = [&]() {
            fence_async_smem();
            __syncwarp();
            mbar_arrive_elected(notify);
            notify = 0;
        };
        auto step = [&](uint32_t (&Ac)[4][4], uint32_t bdc, uint32_t ebc, uint32_t (&An)[4][4], uint32_t& bdn, uint32_t& ebn) {
            wg_fence();
            wgmma_n64_p(ys, yv, Ac[0], bdc, gi);
            wgmma_n16_p(dQ[0], Ac[1], bdc, gi);
            wgmma_n16_p(dQ[1], Ac[2], bdc, gi);
            wgmma_n16_p(dQ[2], Ac[3], bdc, gi);
            wg_commit();
            if (--left > 0) fetch(An, bdn, ebn);
            if (notify) signal();
            const bool last = ++gi == G;
            uint32_t info_next = 0;
            if (last) { ninfo_a += 4; info_next = lds32(ninfo_a); }
            wg_wait0();
            mbar_arrive_elected(ebc);
            if (last) {
                const uint32_t hb = hk & 1;
                mbar_wait(bar_hempty + (2 * wg + hb) * 8, ((hk >> 1) & 1) ^ 1);
                hk++;
                const uint32_t stsm_a = stsm_0 + hb * 8192, pv_a = pv_0 + hb * 1536;
                stsm4(stsm_a, pack_bf(ys[0], ys[1]), pack_bf(ys[2], ys[3]), pack_bf(ys[4], ys[5]), pack_bf(ys[6], ys[7]));
#pragma unroll
                for (int i = 0; i < 6; i += 2) {
                    stsm4(stsm_a ^ ((i + 2) << 4),
                          pack_bf(yv[4 * i], yv[4 * i + 1]), pack_bf(yv[4 * i + 2], yv[4 * i + 3]),
                          pack_bf(yv[4 * i + 4], yv[4 * i + 5]), pack_bf(yv[4 * i + 6], yv[4 * i + 7]));
                }
#pragma unroll
                for (int i = 0; i < 4; i++) asm volatile("" : "+r"(wp[1][i]));
#pragma unroll
                for (int a = 0; a < 3; a++) {
                    const float* q = dQ[a];
                    const float p0 = bf_lo(wp[1][0]) * q[0] + bf_hi(wp[1][0]) * q[1] + bf_lo(wp[1][2]) * q[4] + bf_hi(wp[1][2]) * q[5];
                    const float p1 = bf_lo(wp[1][1]) * q[2] + bf_hi(wp[1][1]) * q[3] + bf_lo(wp[1][3]) * q[6] + bf_hi(wp[1][3]) * q[7];
                    sts32(pv_a + a * 512, pack_bf(p0, p1));
                }
                notify = bar_hfull + (2 * wg + hb) * 8;
                G = __reduce_max_sync(0xffffffffu, (int)(info_next >> 20));
                gi = 0;
            }
        };
        if (left > 0) {
            uint32_t bd0, eb0, bd1 = 0, eb1 = 0;
            fetch(A0, bd0, eb0);
            while (true) {
                step(A0, bd0, eb0, A1, bd1, eb1);
                if (left <= 0) break;
                step(A1, bd1, eb1, A0, bd0, eb0);
                if (left <= 0) break;
            }
            if (notify) signal();
        }
    }
    STAMP(8);
}

typedef CUresult (*EncodeFn)(CUtensorMap*, CUtensorMapDataType, cuuint32_t, void*, const cuuint64_t*, const cuuint64_t*,
                             const cuuint32_t*, const cuuint32_t*, CUtensorMapInterleave, CUtensorMapSwizzle,
                             CUtensorMapL2promotion, CUtensorMapFloatOOBfill);

void make_map(EncodeFn enc, CUtensorMap* tm, const void* base, uint64_t lines, uint32_t box) {
    cuuint64_t gd[2] = {64, lines};
    cuuint64_t gs[1] = {128};
    cuuint32_t bd[2] = {64, box};
    cuuint32_t es[2] = {1, 1};
    enc(tm, CU_TENSOR_MAP_DATA_TYPE_BFLOAT16, 2, const_cast<void*>(base), gd, gs, bd, es, CU_TENSOR_MAP_INTERLEAVE_NONE,
        CU_TENSOR_MAP_SWIZZLE_128B, CU_TENSOR_MAP_L2_PROMOTION_L2_128B, CU_TENSOR_MAP_FLOAT_OOB_FILL_NONE);
}

void make_map3(EncodeFn enc, CUtensorMap* tm, const void* base, uint64_t nodes, uint32_t box) {
    cuuint64_t gd[3] = {64, 4, nodes};
    cuuint64_t gs[2] = {128, 512};
    cuuint32_t bd[3] = {64, 1, box};
    cuuint32_t es[3] = {1, 1, 1};
    enc(tm, CU_TENSOR_MAP_DATA_TYPE_BFLOAT16, 3, const_cast<void*>(base), gd, gs, bd, es, CU_TENSOR_MAP_INTERLEAVE_NONE,
        CU_TENSOR_MAP_SWIZZLE_128B, CU_TENSOR_MAP_L2_PROMOTION_L2_128B, CU_TENSOR_MAP_FLOAT_OOB_FILL_NONE);
}

}

extern "C" void kernel_launch(void* const* d_in, const int* in_sizes, int n_in, void* d_out, int out_size) {
    (void)n_in; (void)out_size;
    static int n_sm = 0;
    static EncodeFn enc = nullptr;
    static void* f_ptr = nullptr;
    if (n_sm == 0) {
        int dev = 0;
        cudaGetDevice(&dev);
        cudaDeviceGetAttribute(&n_sm, cudaDevAttrMultiProcessorCount, dev);
        cudaFuncSetAttribute(painn_kernel, cudaFuncAttributeMaxDynamicSharedMemorySize, SM_TOTAL);
        void* fn = nullptr;
        cudaDriverEntryPointQueryResult qr;
        cudaGetDriverEntryPoint("cuTensorMapEncodeTiled", &fn, cudaEnableDefault, &qr);
        enc = (EncodeFn)fn;
        cudaGetSymbolAddress(&f_ptr, g_F);
    }
    Params p;
    p.sv    = (const __nv_bfloat16*)d_in[0];
    p.pos   = (const __nv_bfloat16*)d_in[1];
    p.src   = (const int*)d_in[2];
    p.dst   = (const int*)d_in[3];
    p.freqs = (const __nv_bfloat16*)d_in[4];
    p.w1    = (const __nv_bfloat16*)d_in[5];
    p.w2    = (const __nv_bfloat16*)d_in[6];
    p.wr    = (const __nv_bfloat16*)d_in[7];
    p.out   = (__nv_bfloat16*)d_out;
    p.N = in_sizes[1] / 3;
    p.E = in_sizes[2];
    p.ncta = n_sm < MAX_CTA ? n_sm : MAX_CTA;
    p.npc = ((p.N + p.ncta - 1) / p.ncta + 3) & ~3;
    p.npc_magic = (uint32_t)(0x100000000ull / (uint32_t)p.npc) + 1u;
    p.quads_per_cta = ((p.E >> 2) + p.ncta - 1) / p.ncta;
    if (!enc || p.N > MAX_N || p.npc > MAX_NPC || (p.E & 3) || p.quads_per_cta > MAX_ROUNDS * 32) return;

    CUtensorMap tmF, tmFs;
    make_map(enc, &tmF, f_ptr, (uint64_t)p.N * 4, 4);
    make_map3(enc, &tmFs, f_ptr, (uint64_t)p.N, 4);

    cudaLaunchConfig_t cfg = {};
    cfg.gridDim = dim3(p.ncta);
    cfg.blockDim = dim3(NT);
    cfg.dynamicSmemBytes = SM_TOTAL;
    cfg.stream = cudaStreamPerThread;
    cudaLaunchAttribute attr[1];
    attr[0].id = cudaLaunchAttributeCooperative;
        attr[0].val.cooperative = 1;
    cfg.attrs = attr;
    cfg.numAttrs = 1;
    cudaLaunchKernelEx(&cfg, painn_kernel, p, tmF, tmFs);
}
```

```cpp
#include <cuda_runtime.h>
#include <cuda.h>
#include <cuda_bf16.h>
#include <stdint.h>

namespace {

constexpr int NT        = 512;
constexpr int NCWG      = 2;
constexpr int MAX_N     = 10240;
constexpr int MAX_CTA   = 136;
constexpr int MAX_NPC   = 80;
constexpr int MAX_ROUNDS = 38;
constexpr int SEG_CAP   = 64;
constexpr int SLOT_CAP  = 6144;
constexpr int MAX_STAGE = 5;
constexpr int STAGE_B   = 12288;

constexpr uint32_t D_MIN_BITS = 0x38D2;
constexpr uint32_t D_MAX_BITS = 0x409C;
constexpr int TAB_ROWS  = (int)(D_MAX_BITS - D_MIN_BITS) + 1;
constexpr int TAB_ZERO  = TAB_ROWS;
constexpr int TAB_BYTES = (TAB_ROWS + 1) * 32;

constexpr int SM_BINCNT = 0;
constexpr int SM_NCNT   = SM_BINCNT + MAX_CTA * 4;
constexpr int SM_NINFO  = SM_NCNT + MAX_NPC * 4;
constexpr int SM_ORDER  = SM_NINFO + (MAX_NPC + 1) * 4;
constexpr int SM_CTRL   = SM_ORDER + MAX_NPC + 12;
constexpr int SM_BARS   = SM_CTRL + 64;
constexpr int SM_SID    = 2048 + 256;
constexpr int SM_META   = SM_SID + SLOT_CAP * 2;
constexpr int SM_TOTAL  = 232448;
constexpr int SM_HT     = (SM_TOTAL - 4 * 8192 - 4 * 1536) / 1024 * 1024;
constexpr int SM_PV     = SM_HT + 4 * 8192;
constexpr int SM_RING   = SM_HT - NCWG * MAX_STAGE * STAGE_B;
constexpr int P1_POS    = 3072;
constexpr int P1_SEGA   = P1_POS + 61440;
constexpr int P1_SEGB   = P1_SEGA + MAX_CTA * SEG_CAP * 8;
constexpr int P1_SV     = P1_SEGB + MAX_CTA * SEG_CAP * 4;
constexpr int P1_W1     = P1_SV + 4 * MAX_NPC * 128;
constexpr int P1_W2     = P1_W1 + 8192;
constexpr int P1_END    = P1_W2 + 8192;
constexpr int P1_REC    = P1_SEGA;
constexpr int STAGE_CAP = (P1_SV - P1_REC) / 16;
static_assert(SM_BARS + (12 + 2 * NCWG * MAX_STAGE) * 8 <= SM_SID, "misc block");
static_assert(SM_BARS + 256 <= P1_POS, "misc block");
static_assert(P1_END <= SM_TOTAL && P1_SV % 1024 == 0 && P1_REC % 16 == 0, "phase 1 overlay");
static_assert(SM_META + SLOT_CAP * 8 <= SM_RING && SM_PV + 4 * 1536 <= SM_TOTAL, "CSR");
static_assert(SM_RING % 1024 == 0 && SM_HT % 1024 == 0, "alignment");
static_assert(SM_BARS % 8 == 0 && SM_META % 8 == 0 && SM_CTRL % 4 == 0, "alignment");
static_assert(MAX_N * 6 <= 61440, "pos");
static_assert(SM_RING >= P1_SEGA && SM_HT <= P1_END, "every byte of the stages is written (finite) during phase 1");
static_assert(SM_SID + MAX_NPC * 1024 <= SM_TOTAL, "slow path accumulators");

__device__ __align__(1024) uint4 g_F[MAX_N * 32];
__device__ __align__(128) uint32_t g_seg[MAX_CTA * MAX_CTA * SEG_CAP * 3];
__device__ uint4    g_table[(TAB_BYTES + 15) / 16];
__device__ unsigned g_bar[2];
#define STAMP(k)
#define STAMPT(k, T)

struct Params {
    const __nv_bfloat16* sv;
    const __nv_bfloat16* pos;
    const int*           src;
    const int*           dst;
    const __nv_bfloat16* freqs;
    const __nv_bfloat16* w1;
    const __nv_bfloat16* w2;
    const __nv_bfloat16* wr;
    __nv_bfloat16*       out;
    int N, E, ncta, npc;
    uint32_t npc_magic;
    int quads_per_cta;
};

__device__ __forceinline__ uint32_t smem_u32(const void* p) { return (uint32_t)__cvta_generic_to_shared(p); }
__device__ __forceinline__ float bf_lo(uint32_t v) { return __uint_as_float(v << 16); }
__device__ __forceinline__ float bf_hi(uint32_t v) { return __uint_as_float(v & 0xffff0000u); }
__device__ __forceinline__ uint32_t pack_bf(float lo, float hi) {
    uint32_t r;
    asm("cvt.rn.bf16x2.f32 %0, %1, %2;" : "=r"(r) : "f"(hi), "f"(lo));
    return r;
}
__device__ __forceinline__ float rbf(float x) { return bf_lo(pack_bf(x, 0.f)); }
__device__ __forceinline__ uint32_t hmul2(uint32_t a, uint32_t b) {
    uint32_t r;
    asm("mul.rn.bf16x2 %0, %1, %2;" : "=r"(r) : "r"(a), "r"(b));
    return r;
}
__device__ __forceinline__ uint32_t hsub2(uint32_t a, uint32_t b) {
    uint32_t r;
    asm("sub.rn.bf16x2 %0, %1, %2;" : "=r"(r) : "r"(a), "r"(b));
    return r;
}
__device__ __forceinline__ uint32_t lds32(uint32_t a) { uint32_t v; asm volatile("ld.shared.u32 %0, [%1];" : "=r"(v) : "r"(a)); return v; }
__device__ __forceinline__ uint2 lds64(uint32_t a) { uint2 v; asm volatile("ld.shared.v2.u32 {%0,%1}, [%2];" : "=r"(v.x), "=r"(v.y) : "r"(a)); return v; }
__device__ __forceinline__ uint4 lds128(uint32_t a) { uint4 v; asm volatile("ld.shared.v4.u32 {%0,%1,%2,%3}, [%4];" : "=r"(v.x), "=r"(v.y), "=r"(v.z), "=r"(v.w) : "r"(a)); return v; }
__device__ __forceinline__ void sts32(uint32_t a, uint32_t v) { asm volatile("st.shared.u32 [%0], %1;" ::"r"(a), "r"(v) : "memory"); }
__device__ __forceinline__ void sts128(uint32_t a, uint4 v) { asm volatile("st.shared.v4.u32 [%0], {%1,%2,%3,%4};" ::"r"(a), "r"(v.x), "r"(v.y), "r"(v.z), "r"(v.w) : "memory"); }
__device__ __forceinline__ void mbar_init(uint32_t bar, int cnt) { asm volatile("mbarrier.init.shared::cta.b64 [%0], %1;" ::"r"(bar), "r"(cnt) : "memory"); }
__device__ __forceinline__ void mbar_expect_tx(uint32_t bar, uint32_t bytes) { asm volatile("mbarrier.arrive.expect_tx.shared::cta.b64 _, [%0], %1;" ::"r"(bar), "r"(bytes) : "memory"); }
__device__ __forceinline__ void mbar_wait(uint32_t bar, uint32_t parity) {
    asm volatile("{\n.reg .pred p;\n.reg .u32 c;\n"
                 "mbarrier.try_wait.parity.shared::cta.b64 p, [%0], %1;\n"
                 "@p bra DONE_%=;\n"
                 "mov.u32 c, 0;\n"
                 "LOOP_%=:\n"
                 "mbarrier.try_wait.parity.shared::cta.b64 p, [%0], %1;\n"
                 "@p bra DONE_%=;\n"
                 "add.u32 c, c, 1;\n"
                 "setp.lt.u32 p, c, 4194304;\n"
                 "@p bra LOOP_%=;\n"
                 "DONE_%=:\n}"
                 ::"r"(bar), "r"(parity) : "memory");
}
__device__ __forceinline__ void mbar_arrive_elected(uint32_t bar) {
    asm volatile("{\n.reg .pred p;\nelect.sync _|p, 0xffffffff;\n@p mbarrier.arrive.shared::cta.b64 _, [%0];\n}" ::"r"(bar) : "memory");
}
__device__ __forceinline__ void bulk_g2s(uint32_t dst, const void* src, uint32_t bytes, uint32_t bar) {
    asm volatile("cp.async.bulk.shared::cluster.global.mbarrier::complete_tx::bytes [%0], [%1], %2, [%3];"
                 ::"r"(dst), "l"(src), "r"(bytes), "r"(bar) : "memory");
}
__device__ __forceinline__ void cp_async16(uint32_t dst, const void* src) {
    asm volatile("cp.async.cg.shared.global [%0], [%1], 16;" ::"r"(dst), "l"(src) : "memory");
}
__device__ __forceinline__ void tma_load(uint32_t dst, const CUtensorMap* tm, int line, uint32_t bar) {
    asm volatile("cp.async.bulk.tensor.2d.shared::cluster.global.mbarrier::complete_tx::bytes [%0], [%1, {%3, %4}], [%2];"
                 ::"r"(dst), "l"(tm), "r"(bar), "r"(0), "r"(line) : "memory");
}
__device__ __forceinline__ void tma_store3(const CUtensorMap* tm, int comp, int node, uint32_t src) {
    asm volatile("cp.async.bulk.tensor.3d.global.shared::cta.bulk_group [%0, {%2, %3, %4}], [%1];"
                 ::"l"(tm), "r"(src), "r"(0), "r"(comp), "r"(node) : "memory");
}
__device__ __forceinline__ void fence_async_smem() { asm volatile("fence.proxy.async.shared::cta;" ::: "memory"); }
__device__ __forceinline__ void ldsm4(uint32_t (&r)[4], uint32_t a) {
    asm volatile("ldmatrix.sync.aligned.m8n8.x4.shared.b16 {%0,%1,%2,%3}, [%4];" : "=r"(r[0]), "=r"(r[1]), "=r"(r[2]), "=r"(r[3]) : "r"(a) : "memory");
}
__device__ __forceinline__ void ldsm4t(uint32_t (&r)[4], uint32_t a) {
    asm volatile("ldmatrix.sync.aligned.m8n8.x4.trans.shared.b16 {%0,%1,%2,%3}, [%4];" : "=r"(r[0]), "=r"(r[1]), "=r"(r[2]), "=r"(r[3]) : "r"(a) : "memory");
}
__device__ __forceinline__ void stsm4(uint32_t a, uint32_t r0, uint32_t r1, uint32_t r2, uint32_t r3) {
    asm volatile("stmatrix.sync.aligned.m8n8.x4.shared.b16 [%0], {%1,%2,%3,%4};" ::"r"(a), "r"(r0), "r"(r1), "r"(r2), "r"(r3) : "memory");
}
__device__ __forceinline__ void mma16816(float (&c)[4], const uint32_t (&a)[4], uint32_t b0, uint32_t b1) {
    asm volatile("mma.sync.aligned.m16n8k16.row.col.f32.bf16.bf16.f32 {%0,%1,%2,%3}, {%4,%5,%6,%7}, {%8,%9}, {%0,%1,%2,%3};"
                 : "+f"(c[0]), "+f"(c[1]), "+f"(c[2]), "+f"(c[3])
                 : "r"(a[0]), "r"(a[1]), "r"(a[2]), "r"(a[3]), "r"(b0), "r"(b1));
}

__device__ __forceinline__ uint32_t desc_lo(uint32_t saddr) { return ((saddr & 0x3FFFF) >> 4) | (1u << 16); }
#define DESC_HI "0x40000040"
__device__ __forceinline__ void wg_fence() { asm volatile("wgmma.fence.sync.aligned;" ::: "memory"); }
__device__ __forceinline__ void wg_commit() { asm volatile("wgmma.commit_group.sync.aligned;" ::: "memory"); }
__device__ __forceinline__ void wg_wait0() { asm volatile("wgmma.wait_group.sync.aligned 0;" ::: "memory"); }

__device__ __forceinline__ void wgmma_n48_first(float (&e)[24], const uint32_t (&a)[4], uint32_t bdesc) {
    asm volatile("{\n.reg .b64 b;\nmov.b64 b, {%28, " DESC_HI "};\n"
                 "wgmma.mma_async.sync.aligned.m64n48k16.f32.bf16.bf16 {%0,%1,%2,%3,%4,%5,%6,%7,%8,%9,%10,%11,%12,%13,%14,%15,%16,%17,%18,%19,%20,%21,%22,%23}, {%24,%25,%26,%27}, b, 0, 1, 1, 1;\n}"
                 : "=f"(e[0]), "=f"(e[1]), "=f"(e[2]), "=f"(e[3]), "=f"(e[4]), "=f"(e[5]), "=f"(e[6]), "=f"(e[7]), "=f"(e[8]), "=f"(e[9]), "=f"(e[10]), "=f"(e[11]), "=f"(e[12]), "=f"(e[13]), "=f"(e[14]), "=f"(e[15]), "=f"(e[16]), "=f"(e[17]), "=f"(e[18]), "=f"(e[19]), "=f"(e[20]), "=f"(e[21]), "=f"(e[22]), "=f"(e[23])
                 : "r"(a[0]), "r"(a[1]), "r"(a[2]), "r"(a[3]), "r"(bdesc));
}
__device__ __forceinline__ void wgmma_n48(float (&e)[24], const uint32_t (&a)[4], uint32_t bdesc) {
    asm volatile("{\n.reg .b64 b;\nmov.b64 b, {%28, " DESC_HI "};\n"
                 "wgmma.mma_async.sync.aligned.m64n48k16.f32.bf16.bf16 {%0,%1,%2,%3,%4,%5,%6,%7,%8,%9,%10,%11,%12,%13,%14,%15,%16,%17,%18,%19,%20,%21,%22,%23}, {%24,%25,%26,%27}, b, 1, 1, 1, 1;\n}"
                 : "+f"(e[0]), "+f"(e[1]), "+f"(e[2]), "+f"(e[3]), "+f"(e[4]), "+f"(e[5]), "+f"(e[6]), "+f"(e[7]), "+f"(e[8]), "+f"(e[9]), "+f"(e[10]), "+f"(e[11]), "+f"(e[12]), "+f"(e[13]), "+f"(e[14]), "+f"(e[15]), "+f"(e[16]), "+f"(e[17]), "+f"(e[18]), "+f"(e[19]), "+f"(e[20]), "+f"(e[21]), "+f"(e[22]), "+f"(e[23])
                 : "r"(a[0]), "r"(a[1]), "r"(a[2]), "r"(a[3]), "r"(bdesc));
}
__device__ __forceinline__ void wgmma_n16_first(float (&d)[8], const uint32_t (&a)[4], uint32_t bdesc) {
    asm volatile("{\n.reg .b64 b;\nmov.b64 b, {%12, " DESC_HI "};\n"
                 "wgmma.mma_async.sync.aligned.m64n16k16.f32.bf16.bf16 {%0,%1,%2,%3,%4,%5,%6,%7}, {%8,%9,%10,%11}, b, 0, 1, 1, 1;\n}"
                 : "=f"(d[0]), "=f"(d[1]), "=f"(d[2]), "=f"(d[3]), "=f"(d[4]), "=f"(d[5]), "=f"(d[6]), "=f"(d[7])
                 : "r"(a[0]), "r"(a[1]), "r"(a[2]), "r"(a[3]), "r"(bdesc));
}
__device__ __forceinline__ void wgmma_n16(float (&d)[8], const uint32_t (&a)[4], uint32_t bdesc) {
    asm volatile("{\n.reg .b64 b;\nmov.b64 b, {%12, " DESC_HI "};\n"
                 "wgmma.mma_async.sync.aligned.m64n16k16.f32.bf16.bf16 {%0,%1,%2,%3,%4,%5,%6,%7}, {%8,%9,%10,%11}, b, 1, 1, 1, 1;\n}"
                 : "+f"(d[0]), "+f"(d[1]), "+f"(d[2]), "+f"(d[3]), "+f"(d[4]), "+f"(d[5]), "+f"(d[6]), "+f"(d[7])
                 : "r"(a[0]), "r"(a[1]), "r"(a[2]), "r"(a[3]), "r"(bdesc));
}

__device__ __forceinline__ void wgmma_n64_p(float (&d)[8], float (&e)[24], const uint32_t (&a)[4], uint32_t bdesc, int acc) {
    asm volatile("{\n.reg .pred p;\n.reg .b64 b;\nsetp.ne.b32 p, %37, 0;\nmov.b64 b, {%36, " DESC_HI "};\n"
                 "wgmma.mma_async.sync.aligned.m64n64k16.f32.bf16.bf16 {%0,%1,%2,%3,%4,%5,%6,%7,%8,%9,%10,%11,%12,%13,%14,%15,%16,%17,%18,%19,%20,%21,%22,%23,%24,%25,%26,%27,%28,%29,%30,%31}, {%32,%33,%34,%35}, b, p, 1, 1, 1;\n}"
                 : "+f"(d[0]), "+f"(d[1]), "+f"(d[2]), "+f"(d[3]), "+f"(d[4]), "+f"(d[5]), "+f"(d[6]), "+f"(d[7]),
                   "+f"(e[0]), "+f"(e[1]), "+f"(e[2]), "+f"(e[3]), "+f"(e[4]), "+f"(e[5]), "+f"(e[6]), "+f"(e[7]), "+f"(e[8]), "+f"(e[9]), "+f"(e[10]), "+f"(e[11]), "+f"(e[12]), "+f"(e[13]), "+f"(e[14]), "+f"(e[15]), "+f"(e[16]), "+f"(e[17]), "+f"(e[18]), "+f"(e[19]), "+f"(e[20]), "+f"(e[21]), "+f"(e[22]), "+f"(e[23])
                 : "r"(a[0]), "r"(a[1]), "r"(a[2]), "r"(a[3]), "r"(bdesc), "r"(acc));
}
__device__ __forceinline__ void wgmma_n16_p(float (&d)[8], const uint32_t (&a)[4], uint32_t bdesc, int acc) {
    asm volatile("{\n.reg .pred p;\n.reg .b64 b;\nsetp.ne.b32 p, %13, 0;\nmov.b64 b, {%12, " DESC_HI "};\n"
                 "wgmma.mma_async.sync.aligned.m64n16k16.f32.bf16.bf16 {%0,%1,%2,%3,%4,%5,%6,%7}, {%8,%9,%10,%11}, b, p, 1, 1, 1;\n}"
                 : "+f"(d[0]), "+f"(d[1]), "+f"(d[2]), "+f"(d[3]), "+f"(d[4]), "+f"(d[5]), "+f"(d[6]), "+f"(d[7])
                 : "r"(a[0]), "r"(a[1]), "r"(a[2]), "r"(a[3]), "r"(bdesc), "r"(acc));
}

__device__ __forceinline__ uint32_t edge_dist(uint32_t sxy, uint32_t sz, uint32_t dxy, uint32_t dz, uint32_t& rxy, uint32_t& rz) {
    rxy = hsub2(sxy, dxy);
    rz  = hsub2(sz, dz);
    uint32_t qxy = hmul2(rxy, rxy), qz = hmul2(rz, rz);
    float ss = rbf((bf_lo(qxy) + bf_hi(qxy)) + bf_lo(qz));
    float s2 = rbf(ss + 1e-8f);
    float d;
    asm("sqrt.approx.ftz.f32 %0, %1;" : "=f"(d) : "f"(s2));
    return pack_bf(d, 0.f) & 0xffffu;
}

__device__ __noinline__ float radial_value(float d, float f) {
    float arg = rbf(d * f);
    float sn  = rbf(sinf(arg));
    float rb  = rbf(__fdiv_rn(sn, d));
    float c   = rbf(cosf(rbf(__fdiv_rn(rbf(d * 3.14159265358979323846f), 5.0f))));
    float fc  = rbf(0.5f * rbf(c + 1.0f));
    return rb * fc;
}

__global__ void __launch_bounds__(NT, 1)
painn_kernel(const Params p, const __grid_constant__ CUtensorMap tmF, const __grid_constant__ CUtensorMap tmFs) {
    extern __shared__ __align__(1024) uint8_t smem[];
    const uint32_t sb   = smem_u32(smem);
    const int tid  = threadIdx.x, lane = tid & 31, warp = __shfl_sync(0xffffffffu, tid >> 5, 0);
    const int cta  = blockIdx.x;
    const int g    = lane >> 2, t = lane & 3;
    int* binCnt = (int*)(smem + SM_BINCNT);
    int* nCnt   = (int*)(smem + SM_NCNT);
    uint32_t* nInfo = (uint32_t*)(smem + SM_NINFO);
    volatile int* ctrl = (volatile int*)(smem + SM_CTRL);
    const uint32_t bar_pos = sb + SM_BARS;
    const uint32_t bar_full = bar_pos + 32, bar_empty = bar_full + NCWG * MAX_STAGE * 8;
    const uint32_t bar_hfull = bar_empty + NCWG * MAX_STAGE * 8, bar_hempty = bar_hfull + 32;

    const int node0  = cta * p.npc;
    const int nnodes = max(0, min(p.npc, p.N - node0));

    STAMP(0);
    if (tid == 32) {
        mbar_init(bar_pos, 1);
        asm volatile("fence.mbarrier_init.release.cluster;" ::: "memory");
        uint32_t pos_bytes = (uint32_t)(p.N * 6 + 15) & ~15u;
        mbar_expect_tx(bar_pos, pos_bytes);
        bulk_g2s(sb + P1_POS, p.pos, pos_bytes, bar_pos);
    } else if (tid == 64) {
        for (int i = 0; i < 4; i++) { mbar_init(bar_hfull + 8 * i, 4); mbar_init(bar_hempty + 8 * i, 4); }
        asm volatile("prefetch.tensormap [%0];" ::"l"(&tmF) : "memory");
        asm volatile("prefetch.tensormap [%0];" ::"l"(&tmFs) : "memory");
    } else if (tid >= 96 && tid < 96 + NCWG * MAX_STAGE) {
        mbar_init(bar_full + 8 * (tid - 96), 2);
        mbar_init(bar_empty + 8 * (tid - 96), 4);
    }
    unsigned bar_seen = 0;
    if (tid == 0 || tid == 32) asm volatile("ld.relaxed.gpu.global.u32 %0, [%1];" : "=r"(bar_seen) : "l"(&g_bar[tid >> 5]) : "memory");
    const bool mlp_warp = warp >= 6;
    int4 s4[3], d4[3];
    const int q0 = cta * p.quads_per_cta;
    const int qend = min(q0 + p.quads_per_cta, p.E >> 2);
#pragma unroll
    for (int k = 0; k < 3; k++) {
        const int q = q0 + (k < 2 ? warp + 16 * k : 32 + warp) * 32 + lane;
        const bool ok = q < qend && (k < 2 || !mlp_warp);
        s4[k] = ok ? __ldg((const int4*)p.src + q) : make_int4(-1, -1, -1, -1);
        d4[k] = ok ? __ldg((const int4*)p.dst + q) : make_int4(0, 0, 0, 0);
    }
    if (tid < MAX_CTA) binCnt[tid] = 0;
    if (tid < MAX_NPC) nCnt[tid] = 0;
    if (tid < 16) ctrl[tid] = 0;
    if (tid >= 256 && tid < 256 + 240) {
        const int i = tid - 256;
        asm volatile("prefetch.global.L2 [%0];" ::"l"(i < 48 ? (const uint8_t*)p.wr + i * 128 : (const uint8_t*)p.w2 + (i - 48) * 128));
    }
    for (int i = P1_SEGA / 16 + tid; i < P1_SV / 16; i += NT) sts128(sb + i * 16, make_uint4(0u, 0u, 0u, 0u));
    for (int i = tid; i < 4 * (MAX_NPC - nnodes) * 8; i += NT)
        sts128(sb + P1_SV + (i / ((MAX_NPC - nnodes) * 8)) * (MAX_NPC * 128) + nnodes * 128 + (i % ((MAX_NPC - nnodes) * 8)) * 16, make_uint4(0u, 0u, 0u, 0u));
    __syncthreads();

    mbar_wait(bar_pos, 0);
    if (s4[0].x == 0x7fffffff) ctrl[15] = 1;
    for (int i = tid; i < nnodes * 32; i += NT) {
        const int r = i >> 5, b = (i >> 3) & 3, c = i & 7;
        cp_async16(sb + P1_SV + b * (MAX_NPC * 128) + r * 128 + ((c ^ (r & 7)) << 4), (const uint8_t*)p.sv + (size_t)node0 * 512 + i * 16);
    }
    for (int i = tid; i < 1024; i += NT) {
        const int m = i >> 9, k = (i >> 3) & 63, c = i & 7;
        cp_async16(sb + P1_W1 + m * 8192 + k * 128 + ((c ^ (k & 7)) << 4),
                   m == 0 ? (const uint8_t*)p.w1 + k * 128 + c * 16 : (const uint8_t*)p.w2 + k * 384 + 128 + c * 16);
    }
    asm volatile("cp.async.commit_group;" ::: "memory");
    STAMP(1);
#pragma unroll
    for (int k = 0; k < 3; k++) {
        const int ss[4] = {s4[k].x, s4[k].y, s4[k].z, s4[k].w};
        const int dd[4] = {d4[k].x, d4[k].y, d4[k].z, d4[k].w};
        if (ss[0] >= 0) {
            uint32_t w0[4], w1[4], v0[4], v1[4], r0[4], r1[4], r2[4], bin[4], rank[4];
#pragma unroll
            for (int j = 0; j < 4; j++) {
                const uint32_t a = (sb + P1_POS + 6u * (uint32_t)ss[j]) & ~3u, c = (sb + P1_POS + 6u * (uint32_t)dd[j]) & ~3u;
                w0[j] = lds32(a); w1[j] = lds32(a + 4); v0[j] = lds32(c); v1[j] = lds32(c + 4);
            }
#pragma unroll
            for (int j = 0; j < 4; j++) {
                const uint32_t sh = (uint32_t)ss[j] << 4, dh = (uint32_t)dd[j] << 4;
                uint32_t rxy, rz;
                const uint32_t db = edge_dist(__funnelshift_r(w0[j], w1[j], sh), __funnelshift_r(w1[j], w1[j], sh),
                                              __funnelshift_r(v0[j], v1[j], dh), __funnelshift_r(v1[j], v1[j], dh), rxy, rz);
                float inv;
                asm("rcp.approx.ftz.f32 %0, %1;" : "=f"(inv) : "f"(__uint_as_float(db << 16)));
                bin[j] = __umulhi((uint32_t)dd[j], p.npc_magic);
                r0[j] = (uint32_t)ss[j] | ((db - D_MIN_BITS) << 16);
                r1[j] = pack_bf(bf_lo(rxy) * inv, bf_hi(rxy) * inv);
                r2[j] = __byte_perm(pack_bf(bf_lo(rz) * inv, 0.f), (uint32_t)dd[j] - bin[j] * (uint32_t)p.npc, 0x5410);
                rank[j] = db <= D_MAX_BITS ? (uint32_t)atomicAdd(&binCnt[bin[j]], 1) : 0xffffu;
            }
#pragma unroll
            for (int j = 0; j < 4; j++) {
                if (rank[j] < SEG_CAP) {
                    const uint32_t slot = bin[j] * SEG_CAP + rank[j];
                    asm volatile("st.shared.v2.u32 [%0], {%1, %2};" ::"r"(sb + P1_SEGA + slot * 8), "r"(r0[j]), "r"(r1[j]) : "memory");
                    sts32(sb + P1_SEGB + slot * 4, r2[j]);
                }
            }
        }
    }
    __syncthreads();
    STAMP(2);
    {
        constexpr int IT = (MAX_CTA + 31) / 32;
        uint2 ca[IT][2];
        uint32_t cb[IT][2];
        int cn[IT];
#pragma unroll
        for (int it = 0; it < IT; it++) {
            const int b = min(2 * warp + (lane >> 4) + 32 * it, MAX_CTA - 1);
            cn[it] = binCnt[b];
#pragma unroll
            for (int u = 0; u < 2; u++) {
                const int j = (lane & 15) + 16 * u;
                ca[it][u] = lds64(sb + P1_SEGA + (b * SEG_CAP + j) * 8);
                cb[it][u] = lds32(sb + P1_SEGB + (b * SEG_CAP + j) * 4);
            }
        }
#pragma unroll
        for (int it = 0; it < IT; it++) {
            const int b = 2 * warp + (lane >> 4) + 32 * it;
            if (b < p.ncta) {
                uint32_t* dstp = g_seg + ((size_t)cta * MAX_CTA + b) * (SEG_CAP * 3);
                const uint32_t tag = (uint32_t)min(cn[it], 511) << 23;
#pragma unroll
                for (int u = 0; u < 2; u++) {
                    const int j = (lane & 15) + 16 * u;
                    *(uint2*)(dstp + 2 * j) = ca[it][u];
                    dstp[2 * SEG_CAP + j] = cb[it][u] | tag;
                }
                for (int j = 32 + (lane & 15); j < ((min(cn[it], SEG_CAP) + 7) & ~7); j += 16) {
                    *(uint2*)(dstp + 2 * j) = lds64(sb + P1_SEGA + (b * SEG_CAP + j) * 8);
                    dstp[2 * SEG_CAP + j] = lds32(sb + P1_SEGB + (b * SEG_CAP + j) * 4);
                }
            }
        }
    }
    STAMP(7);
    asm volatile("cp.async.wait_group 0;" ::: "memory");
    __syncthreads();
    STAMP(3);
    if (tid == 64) asm volatile("red.add.release.gpu.global.u32 [%0], 1;" ::"l"(&g_bar[0]) : "memory");

    if (!mlp_warp) {
        const int rows_per = (TAB_ROWS + 1 + p.ncta - 1) / p.ncta;
        for (int i = tid; i < rows_per * 8; i += 6 * 32) {
            int row = cta * rows_per + (i >> 3), kp = i & 7;
            if (row <= TAB_ROWS) {
                uint32_t val = 0;
                if (row < TAB_ROWS) {
                    float d = __uint_as_float((D_MIN_BITS + row) << 16);
                    uint32_t f2 = __ldg((const uint32_t*)p.freqs + kp);
                    val = pack_bf(radial_value(d, bf_lo(f2)), radial_value(d, bf_hi(f2)));
                }
                ((uint32_t*)g_table)[row * 8 + kp] = val;
            }
        }
    } else {
        const int mt = (warp - 6) >> 1, hf = (warp - 6) & 1;
        if (mt * 16 < nnodes) {
            STAMPT(10, 6 * 32);
            const int lrow = lane & 15, lch = lane >> 4;
            const uint32_t rowb = sb + P1_SV + (mt * 16 + lrow) * 128;
            const uint32_t key0 = lrow & 7;
            float acc[4][4];
#pragma unroll
            for (int i = 0; i < 4; i++) { acc[i][0] = acc[i][1] = acc[i][2] = acc[i][3] = 0.f; }
#pragma unroll
            for (int ks = 0; ks < 4; ks++) {
                uint32_t a[4];
                ldsm4(a, rowb + (((2 * ks + lch) ^ key0) << 4));
                const int kk = 16 * ks + lrow;
#pragma unroll
                for (int nt = 0; nt < 4; nt += 2) {
                    uint32_t b[4];
                    ldsm4t(b, sb + P1_W1 + kk * 128 + (((4 * hf + nt + lch) ^ (kk & 7)) << 4));
                    mma16816(acc[nt], a, b[0], b[1]);
                    mma16816(acc[nt + 1], a, b[2], b[3]);
                }
            }
            uint32_t hp[4][2];
#pragma unroll
            for (int i = 0; i < 4; i++) {
                float h[4];
#pragma unroll
                for (int q = 0; q < 4; q++) {
                    float x = rbf(acc[i][q]);
                    h[q] = __fdividef(x, 1.0f + __expf(-x));
                    acc[i][q] = 0.f;
                }
                hp[i][0] = pack_bf(h[0], h[1]);
                hp[i][1] = pack_bf(h[2], h[3]);
            }
            asm volatile("bar.sync %0, 64;" ::"r"(4 + mt) : "memory");
#pragma unroll
            for (int i = 0; i < 4; i += 2)
                stsm4(rowb + (((4 * hf + i + lch) ^ key0) << 4), hp[i][0], hp[i][1], hp[i + 1][0], hp[i + 1][1]);
            asm volatile("bar.sync %0, 64;" ::"r"(4 + mt) : "memory");
#pragma unroll
            for (int ks = 0; ks < 4; ks++) {
                uint32_t a[4];
                ldsm4(a, rowb + (((2 * ks + lch) ^ key0) << 4));
                const int kk = 16 * ks + lrow;
#pragma unroll
                for (int nt = 0; nt < 4; nt += 2) {
                    uint32_t b[4];
                    ldsm4t(b, sb + P1_W2 + kk * 128 + (((4 * hf + nt + lch) ^ (kk & 7)) << 4));
                    mma16816(acc[nt], a, b[0], b[1]);
                    mma16816(acc[nt + 1], a, b[2], b[3]);
                }
            }
            uint32_t vq[2][3][4];
            const uint32_t vb = sb + P1_SV + (mt * 16 + g) * 128 + 4 * t;
#pragma unroll
            for (int rh = 0; rh < 2; rh++)
#pragma unroll
                for (int a = 0; a < 3; a++)
#pragma unroll
                    for (int i = 0; i < 4; i++) vq[rh][a][i] = lds32(vb + (a + 1) * (MAX_NPC * 128) + rh * 1024 + (((4 * hf + i) ^ g) << 4));
#pragma unroll
            for (int rh = 0; rh < 2; rh++)
#pragma unroll
                for (int a = 0; a < 3; a++)
#pragma unroll
                    for (int i = 0; i < 4; i++)
                        sts32(vb + (a + 1) * (MAX_NPC * 128) + rh * 1024 + (((4 * hf + i) ^ g) << 4),
                              hmul2(pack_bf(acc[i][2 * rh], acc[i][2 * rh + 1]), vq[rh][a][i]));
            fence_async_smem();
            asm volatile("bar.sync %0, 64;" ::"r"(4 + mt) : "memory");
            {
                const int r4 = mt * 16 + 8 * hf + 4 * (lane >> 2), comp = lane & 3;
                if (lane < 8 && r4 < nnodes) tma_store3(&tmFs, comp, node0 + r4, sb + P1_SV + comp * (MAX_NPC * 128) + r4 * 128);
            }
            asm volatile("cp.async.bulk.commit_group;" ::: "memory");
        }
        STAMPT(11, 6 * 32);
    }
    if (tid == 0) {
        const unsigned target = (bar_seen / (unsigned)p.ncta + 1u) * (unsigned)p.ncta;
        unsigned cur;
        int spins = 0;
        do {
            asm volatile("ld.acquire.gpu.global.u32 %0, [%1];" : "=r"(cur) : "l"(&g_bar[0]) : "memory");
        } while ((int)(cur - target) < 0 && ++spins < (1 << 24));
    }
    STAMP(4);
    __syncthreads();
    STAMP(5);

    constexpr int SEG_IT = (MAX_CTA + 31) / 32;
    uint2 ra[SEG_IT][2];
    uint32_t rb[SEG_IT][2], rr[SEG_IT][2];
#pragma unroll
    for (int it = 0; it < SEG_IT; it++) {
        const int b = 2 * warp + (lane >> 4) + 32 * it;
        const uint32_t* sp = g_seg + ((size_t)b * MAX_CTA + cta) * (SEG_CAP * 3);
#pragma unroll
        for (int u = 0; u < 2; u++) {
            const int j = (lane & 15) + 16 * u;
            ra[it][u] = b < p.ncta ? __ldcg((const uint2*)(sp + 2 * j)) : make_uint2(0u, 0u);
            rb[it][u] = b < p.ncta ? __ldcg(sp + 2 * SEG_CAP + j) : 0u;
        }
    }
    if (mlp_warp && lane < 8) {
        asm volatile("cp.async.bulk.wait_group 0;" ::: "memory");
        asm volatile("fence.proxy.async;" ::: "memory");
    }
    STAMP(9);
    uint2 xa[SEG_IT];
    uint32_t xb[SEG_IT];
#pragma unroll
    for (int it = 0; it < SEG_IT; it++) {
        const int cnt = rb[it][0] >> 23;
        const int b = 2 * warp + (lane >> 4) + 32 * it;
        const uint32_t* sp = g_seg + ((size_t)b * MAX_CTA + cta) * (SEG_CAP * 3);
        const bool has = 32 + (lane & 15) < cnt;
        xa[it] = has ? __ldcg((const uint2*)(sp + 2 * (32 + (lane & 15)))) : make_uint2(0u, 0u);
        xb[it] = has ? __ldcg(sp + 2 * SEG_CAP + 32 + (lane & 15)) : 0u;
    }
#pragma unroll
    for (int it = 0; it < SEG_IT; it++) {
        const int cnt = rb[it][0] >> 23;
        if (cnt > SEG_CAP) ctrl[1] = 1;
#pragma unroll
        for (int u = 0; u < 2; u++)
            rr[it][u] = (lane & 15) + 16 * u < cnt ? (uint32_t)atomicAdd(&nCnt[(rb[it][u] >> 16) & 0x7fu], 1) : 0xffffffffu;
    }
#pragma unroll
    for (int it = 0; it < SEG_IT; it++) {
        const int cnt = rb[it][0] >> 23;
        if (32 + (lane & 15) < cnt) {
            const int pos = atomicAdd((int*)&ctrl[8], 1);
            const uint32_t rank = (uint32_t)atomicAdd(&nCnt[(xb[it] >> 16) & 0x7fu], 1);
            if (pos < STAGE_CAP) sts128(sb + P1_REC + pos * 16, make_uint4(xa[it].x, xa[it].y, xb[it], rank));
        }
        if (cnt > 48) {
            const int b = 2 * warp + (lane >> 4) + 32 * it;
            const uint32_t* sp = g_seg + ((size_t)b * MAX_CTA + cta) * (SEG_CAP * 3);
            const int j = 48 + (lane & 15);
            if (j < min(cnt, SEG_CAP)) {
                const uint2 a = __ldcg((const uint2*)(sp + 2 * j));
                const uint32_t c = __ldcg(sp + 2 * SEG_CAP + j);
                const int pos = atomicAdd((int*)&ctrl[8], 1);
                const uint32_t rank = (uint32_t)atomicAdd(&nCnt[(c >> 16) & 0x7fu], 1);
                if (pos < STAGE_CAP) sts128(sb + P1_REC + pos * 16, make_uint4(a.x, a.y, c, rank));
            }
        }
    }
    STAMP(13);
    __syncthreads();
    if (tid == 64) asm volatile("red.add.release.gpu.global.u32 [%0], 1;" ::"l"(&g_bar[1]) : "memory");
    STAMP(14);
    const int total = ctrl[8];
    if (tid == 0 && total > STAGE_CAP) ctrl[1] = 1;
    if (warp == 0) {
        int c[3], s = 0;
#pragma unroll
        for (int i = 0; i < 3; i++) {
            int b = lane * 3 + i;
            c[i] = b < nnodes ? max(16, (nCnt[b] + 15) & ~15) : 0;
            s += c[i];
        }
        int x = s;
#pragma unroll
        for (int o = 1; o < 32; o <<= 1) { int y = __shfl_up_sync(0xffffffffu, x, o); if (lane >= o) x += y; }
        const int slots = __shfl_sync(0xffffffffu, x, 31);
        int off = x - s, below = 0;
#pragma unroll
        for (int i = 0; i < 3; i++) {
            int b = lane * 3 + i;
            if (b < nnodes) {
                nInfo[b] = (uint32_t)off | ((uint32_t)c[i] << 16);
                below += (2 * off + c[i] < slots);
            }
            off += c[i];
        }
        below = __reduce_add_sync(0xffffffffu, below);
        if (lane == 0) {
            ctrl[2] = below;
            ctrl[4] = slots;
            if (slots > SLOT_CAP) ctrl[1] = 1;
        }
    }
    __syncthreads();
    if (ctrl[1] == 0) {
        uint16_t* sid = (uint16_t*)(smem + SM_SID);
        uint2* meta = (uint2*)(smem + SM_META);
#pragma unroll
        for (int it = 0; it < SEG_IT; it++)
#pragma unroll
            for (int u = 0; u < 2; u++)
                if (rr[it][u] != 0xffffffffu) rr[it][u] += lds32(sb + SM_NINFO + ((rb[it][u] >> 16) & 0x7fu) * 4) & 0xffffu;
#pragma unroll
        for (int it = 0; it < SEG_IT; it++)
#pragma unroll
            for (int u = 0; u < 2; u++)
                if (rr[it][u] != 0xffffffffu) {
                    sid[rr[it][u]]  = (uint16_t)((ra[it][u].x & 0xffffu) << 2);
                    meta[rr[it][u]] = make_uint2(((ra[it][u].x >> 16) << 5) | (rb[it][u] << 16), ra[it][u].y);
                }
        for (int i = tid; i < total; i += NT) {
            const uint4 r = lds128(sb + P1_REC + i * 16);
            const int pos = (int)(lds32(sb + SM_NINFO + ((r.z >> 16) & 0x7fu) * 4) & 0xffffu) + (int)r.w;
            sid[pos]  = (uint16_t)((r.x & 0xffffu) << 2);
            meta[pos] = make_uint2(((r.x >> 16) << 5) | (r.z << 16), r.y);
        }
        if (tid >= NT - 128 && tid - (NT - 128) < nnodes) {
            const int b = tid - (NT - 128), split = ctrl[2];
            const int mid = split < nnodes ? (int)(nInfo[split] & 0xffffu) : ctrl[4];
            const int st = b >= split;
            const int mine = (int)(nInfo[b] & 0xffffu) + (int)(nInfo[b] >> 16) - (st ? mid : 0);
            int lo = st ? 0 : split, hi = st ? split : nnodes;
            const int first = lo;
            while (lo < hi) {
                const int o = (lo + hi) >> 1;
                const int other = (int)(nInfo[o] & 0xffffu) + (int)(nInfo[o] >> 16) - (st ? 0 : mid);
                if (st ? (other <= mine) : (other < mine)) lo = o + 1; else hi = o;
            }
            const int rank = (st ? b - split : b) + lo - first;
            smem[SM_ORDER + rank] = (uint8_t)(b | (st << 7));
        }
        for (int i = tid; i < nnodes * 16; i += NT) {
            int nl = i >> 4, c = nCnt[nl];
            int j = (c & ~15) + (i & 15);
            if (j >= c && (j < 16 || (c & 15))) {
                int pos = (int)(nInfo[nl] & 0xffffu) + j;
                sid[pos]  = 0xffffu;
                meta[pos] = make_uint2((uint32_t)TAB_ZERO << 5, 0u);
            }
        }
    }
    STAMP(15);
    if (tid == 32) {
        const unsigned target = (bar_seen / (unsigned)p.ncta + 1u) * (unsigned)p.ncta;
        unsigned cur;
        int spins = 0;
        do {
            asm volatile("ld.acquire.gpu.global.u32 %0, [%1];" : "=r"(cur) : "l"(&g_bar[1]) : "memory");
        } while ((int)(cur - target) < 0 && ++spins < (1 << 24));
        asm volatile("fence.proxy.async.global;" ::: "memory");
    }
    fence_async_smem();
    __syncthreads();
    STAMP(6);

    if (__shfl_sync(0xffffffffu, ctrl[1], 0) != 0) {
        float* acc = (float*)(smem + P1_POS);
        for (int i = tid; i < nnodes * 256; i += NT) acc[i] = 0.f;
        __syncthreads();
        const uint16_t* posu = (const uint16_t*)p.pos;
        const uint32_t* tabg = (const uint32_t*)g_table;
        const uint32_t* Fw = (const uint32_t*)g_F;
        for (int e0 = warp * 32; e0 < p.E; e0 += NT) {
            int e = e0 + lane;
            int s = 0, d = 0;
            uint32_t db = 0xffff, rxy = 0, rz = 0;
            bool act = false;
            if (e < p.E) {
                s = p.src[e]; d = p.dst[e];
                if (d >= node0 && d < node0 + nnodes) {
                    uint32_t sxy = posu[s * 3] | ((uint32_t)posu[s * 3 + 1] << 16), sz = posu[s * 3 + 2];
                    uint32_t dxy = posu[d * 3] | ((uint32_t)posu[d * 3 + 1] << 16), dz = posu[d * 3 + 2];
                    db  = edge_dist(sxy, sz, dxy, dz, rxy, rz);
                    act = db <= D_MAX_BITS;
                }
            }
            unsigned m = __ballot_sync(0xffffffffu, act);
            while (m) {
                int l = __ffs(m) - 1;
                m &= m - 1;
                int es = __shfl_sync(0xffffffffu, s, l), ed = __shfl_sync(0xffffffffu, d, l);
                uint32_t edb = __shfl_sync(0xffffffffu, db, l), exy = __shfl_sync(0xffffffffu, rxy, l), ez = __shfl_sync(0xffffffffu, rz, l);
                float inv = 1.0f / __uint_as_float(edb << 16);
                float rh[3] = {rbf(bf_lo(exy) * inv), rbf(bf_hi(exy) * inv), rbf(bf_lo(ez) * inv)};
                const uint32_t* fr = Fw + (size_t)es * 128 + lane;
                const uint32_t fh = __ldcg(fr);
                const uint32_t q[3] = {__ldcg(fr + 32), __ldcg(fr + 64), __ldcg(fr + 96)};
                float ps0 = 0.f, ps1 = 0.f, pr0 = 0.f, pr1 = 0.f;
                for (int j2 = 0; j2 < 32; j2++) {
                    uint32_t hj = __shfl_sync(0xffffffffu, fh, j2);
                    uint32_t a0 = *(const uint32_t*)(p.w2 + (2 * j2) * 192 + 2 * lane), a1 = *(const uint32_t*)(p.w2 + (2 * j2 + 1) * 192 + 2 * lane);
                    uint32_t b0 = *(const uint32_t*)(p.w2 + (2 * j2) * 192 + 128 + 2 * lane), b1 = *(const uint32_t*)(p.w2 + (2 * j2 + 1) * 192 + 128 + 2 * lane);
                    ps0 += bf_lo(hj) * bf_lo(a0) + bf_hi(hj) * bf_lo(a1);
                    ps1 += bf_lo(hj) * bf_hi(a0) + bf_hi(hj) * bf_hi(a1);
                    pr0 += bf_lo(hj) * bf_lo(b0) + bf_hi(hj) * bf_lo(b1);
                    pr1 += bf_lo(hj) * bf_hi(b0) + bf_hi(hj) * bf_hi(b1);
                }
                float ws0 = 0.f, ws1 = 0.f, wv0 = 0.f, wv1 = 0.f, wr0 = 0.f, wr1 = 0.f;
                for (int k2 = 0; k2 < 8; k2++) {
                    uint32_t rk2 = __ldcg(tabg + (edb - D_MIN_BITS) * 8 + k2);
#pragma unroll
                    for (int h = 0; h < 2; h++) {
                        float rv = h ? bf_hi(rk2) : bf_lo(rk2);
                        const __nv_bfloat16* wrow = p.wr + (2 * k2 + h) * 192 + 2 * lane;
                        uint32_t a = *(const uint32_t*)wrow, b = *(const uint32_t*)(wrow + 64), c = *(const uint32_t*)(wrow + 128);
                        ws0 += rv * bf_lo(a); ws1 += rv * bf_hi(a);
                        wv0 += rv * bf_lo(b); wv1 += rv * bf_hi(b);
                        wr0 += rv * bf_lo(c); wr1 += rv * bf_hi(c);
                    }
                }
                float* a = acc + (ed - node0) * 256 + 2 * lane;
                atomicAdd(a, ps0 * ws0); atomicAdd(a + 1, ps1 * ws1);
#pragma unroll
                for (int c = 0; c < 3; c++) {
                    atomicAdd(a + 64 * (c + 1), wv0 * bf_lo(q[c]) + pr0 * wr0 * rh[c]);
                    atomicAdd(a + 64 * (c + 1) + 1, wv1 * bf_hi(q[c]) + pr1 * wr1 * rh[c]);
                }
            }
        }
        __syncthreads();
        for (int i = tid; i < nnodes * 128; i += NT) {
            uint32_t r = *(const uint32_t*)(p.sv + (size_t)node0 * 256 + 2 * i);
            *(uint32_t*)(p.out + (size_t)node0 * 256 + 2 * i) = pack_bf(bf_lo(r) + acc[2 * i], bf_hi(r) + acc[2 * i + 1]);
        }
        return;
    }

    const int slots = __reduce_max_sync(0xffffffffu, ctrl[4]);
    const int split = __reduce_max_sync(0xffffffffu, ctrl[2]);
    constexpr int nstage = MAX_STAGE;
    const uint32_t ring = sb + SM_RING;
    const int mid = __reduce_max_sync(0xffffffffu, split < nnodes ? (int)(nInfo[split] & 0xffffu) : slots) >> 4;
    const int wgi = warp >> 2, w = warp & 3;
    uint32_t wp[3][4];
    if (wgi < 3) {
        const uint16_t* wr = (const uint16_t*)p.wr + 16 * w + g;
#pragma unroll
        for (int ty = 0; ty < 3; ty++) {
#pragma unroll
            for (int i = 0; i < 4; i++) {
                const uint16_t* q = wr + (8 * (i >> 1) + 2 * t) * 192 + ty * 64 + 8 * (i & 1);
                wp[ty][i] = (uint32_t)__ldg(q) | ((uint32_t)__ldg(q + 192) << 16);
            }
        }
    }
    constexpr uint32_t EMPTY_OFF = NCWG * MAX_STAGE * 8;
    if (wgi == 3) {
        const int sc = w >> 1, r = w & 1;
        const int g0 = (sc == 0 ? 0 : mid) + r, g1 = sc == 0 ? mid : slots >> 4;
        const uint32_t ring_wg = ring + sc * nstage * STAGE_B, full_wg = bar_full + sc * MAX_STAGE * 8;
        const int e = lane >> 1, half = lane & 1;
        const uint32_t coef_off = e * 128 + ((half ^ (e & 7)) << 4);
        const int vrot = (e & 3) ^ ((e >> 1) & 3);
        const uint8_t* tab = (const uint8_t*)g_table + half * 16;
        int stage = r;
        uint32_t phase = 1;
        uint32_t ma = sb + SM_META + (g0 * 16 + e) * 8, ida = sb + SM_SID + g0 * 32;
        uint2 m = make_uint2(0u, 0u);
        uint4 tv = make_uint4(0u, 0u, 0u, 0u), ia = tv, ib = tv;
        if (g0 < g1) {
            m  = lds64(ma);
            ia = lds128(ida);
            ib = lds128(ida + 16);
            tv = __ldg((const uint4*)(tab + (m.x & 0xffffu)));
        }
        for (int left = (g1 - g0 + 1) >> 1; left > 0; left--) {
            const uint32_t st = ring_wg + stage * STAGE_B, fb = full_wg + stage * 8;
            ma += 256; ida += 64;
            uint2 mn = m;
            if (left > 1) mn = lds64(ma);
            mbar_wait(fb + EMPTY_OFF, phase);
            uint32_t leader;
            asm volatile("{\n.reg .pred p;\nelect.sync _|p, 0xffffffff;\nselp.u32 %0, 1, 0, p;\n}" : "=r"(leader));
            if (leader) {
                const uint32_t id2[8] = {ia.x, ia.y, ia.z, ia.w, ib.x, ib.y, ib.z, ib.w};
                const uint32_t rows = st + 2048;
                if ((ib.w >> 16) != 0xffffu) {
                    mbar_expect_tx(fb, 16 * 512);
#pragma unroll
                    for (int i = 0; i < 8; i++) {
                        tma_load(rows + (2 * i) * 640, &tmF, (int)(id2[i] & 0xffffu), fb);
                        tma_load(rows + (2 * i + 1) * 640, &tmF, (int)(id2[i] >> 16), fb);
                    }
                } else {
                    int nv = 0;
#pragma unroll
                    for (int i = 0; i < 8; i++) nv += ((id2[i] & 0xffffu) != 0xffffu) + ((id2[i] >> 16) != 0xffffu);
                    mbar_expect_tx(fb, (uint32_t)nv * 512u);
#pragma unroll
                    for (int q = 0; q < 4; q++) {
                        if (4 * q + 4 <= nv) {
                            tma_load(rows + (4 * q) * 640, &tmF, (int)(id2[2 * q] & 0xffffu), fb);
                            tma_load(rows + (4 * q + 1) * 640, &tmF, (int)(id2[2 * q] >> 16), fb);
                            tma_load(rows + (4 * q + 2) * 640, &tmF, (int)(id2[2 * q + 1] & 0xffffu), fb);
                            tma_load(rows + (4 * q + 3) * 640, &tmF, (int)(id2[2 * q + 1] >> 16), fb);
                        } else {
                            if (4 * q < nv)     tma_load(rows + (4 * q) * 640, &tmF, (int)(id2[2 * q] & 0xffffu), fb);
                            if (4 * q + 1 < nv) tma_load(rows + (4 * q + 1) * 640, &tmF, (int)(id2[2 * q] >> 16), fb);
                            if (4 * q + 2 < nv) tma_load(rows + (4 * q + 2) * 640, &tmF, (int)(id2[2 * q + 1] & 0xffffu), fb);
                        }
                    }
                }
            }
            __syncwarp();
            uint4 o[4];
            {
                const uint32_t mul[4] = {0x3f803f80u, __byte_perm(m.y, 0, 0x1010), __byte_perm(m.y, 0, 0x3232), __byte_perm(m.x, 0, 0x3232)};
#pragma unroll
                for (int j = 0; j < 4; j++) {
                    const int v = j ^ vrot;
                    const uint32_t lo = (v & 1) ? mul[1] : mul[0], hi = (v & 1) ? mul[3] : mul[2];
                    const uint32_t mm = (v & 2) ? hi : lo;
                    o[j] = make_uint4(hmul2(tv.x, mm), hmul2(tv.y, mm), hmul2(tv.z, mm), hmul2(tv.w, mm));
                }
            }
            m = mn;
            if (left > 1) {
                ia = lds128(ida);
                ib = lds128(ida + 16);
                tv = __ldg((const uint4*)(tab + (m.x & 0xffffu)));
            }
            const uint32_t a = st + coef_off;
#pragma unroll
            for (int j = 0; j < 4; j++) sts128(a ^ ((j ^ vrot) << 5), o[j]);
            fence_async_smem();
            __syncwarp();
            mbar_arrive_elected(fb);
            stage += 2;
            if (stage >= nstage) { stage -= nstage; phase ^= 1; }
        }
    } else if (wgi == 2) {
        uint32_t wA[2][4][4];
        {
            const uint16_t* w2 = (const uint16_t*)p.w2 + 16 * w + g;
#pragma unroll
            for (int mk = 0; mk < 8; mk++) {
#pragma unroll
                for (int i = 0; i < 4; i++) {
                    const uint16_t* q = w2 + (16 * (mk & 3) + 2 * t + 8 * (i >> 1)) * 192 + (mk >> 2) * 128 + 8 * (i & 1);
                    wA[mk >> 2][mk & 3][i] = (uint32_t)__ldg(q) | ((uint32_t)__ldg(q + 192) << 16);
                }
            }
        }
        const uint32_t lane_off = (uint32_t)node0 * 512u + t * 128 + w * 32 + (g & 1) * 16 + (g >> 1) * 4;
        uint32_t hcnt[2] = {0u, 0u};
        float zs[8], zv[24], pvv[6], pr[4][2];
        uint32_t hbuf = 0;
        auto start = [&](int ent) {
            const int c = ent >> 7;
            const uint32_t k = c ? hcnt[1] : hcnt[0];
            hbuf = 2 * c + (k & 1);
            mbar_wait(bar_hfull + hbuf * 8, (k >> 1) & 1);
            if (c) hcnt[1]++; else hcnt[0]++;
            const uint32_t dht = desc_lo(sb + SM_HT + hbuf * 8192);
            wg_fence();
            wgmma_n16_first(zs, wA[0][0], dht);
            wgmma_n48_first(zv, wA[1][0], dht + 2);
#pragma unroll
            for (int ks = 1; ks < 4; ks++) {
                wgmma_n16(zs, wA[0][ks], dht + ks * 128);
                wgmma_n48(zv, wA[1][ks], dht + ks * 128 + 2);
            }
            wg_commit();
        };
        auto side = [&](int ent) {
            const uint32_t pa = sb + SM_PV + hbuf * 1536 + (tid & 127) * 4;
            const uint32_t a0 = lds32(pa), a1 = lds32(pa + 512), a2 = lds32(pa + 1024);
            pvv[0] = bf_lo(a0); pvv[1] = bf_hi(a0); pvv[2] = bf_lo(a1); pvv[3] = bf_hi(a1); pvv[4] = bf_lo(a2); pvv[5] = bf_hi(a2);
            __syncwarp();
            mbar_arrive_elected(bar_hempty + hbuf * 8);
        };
        auto weigh = [&]() {
#pragma unroll
            for (int i = 0; i < 12; i++) asm volatile("" : "+r"(wp[i >> 2][i & 3]));
            pr[0][0] = bf_lo(wp[0][0]) * zs[0] + bf_hi(wp[0][0]) * zs[1] + bf_lo(wp[0][2]) * zs[4] + bf_hi(wp[0][2]) * zs[5];
            pr[0][1] = bf_lo(wp[0][1]) * zs[2] + bf_hi(wp[0][1]) * zs[3] + bf_lo(wp[0][3]) * zs[6] + bf_hi(wp[0][3]) * zs[7];
#pragma unroll
            for (int a = 0; a < 3; a++) {
                const float* y = zv + 8 * a;
                pr[a + 1][0] = pvv[2 * a] + bf_lo(wp[2][0]) * y[0] + bf_hi(wp[2][0]) * y[1] + bf_lo(wp[2][2]) * y[4] + bf_hi(wp[2][2]) * y[5];
                pr[a + 1][1] = pvv[2 * a + 1] + bf_lo(wp[2][1]) * y[2] + bf_hi(wp[2][1]) * y[3] + bf_lo(wp[2][3]) * y[6] + bf_hi(wp[2][3]) * y[7];
            }
            asm volatile("" : "+f"(pr[0][0]), "+f"(pr[0][1]), "+f"(pr[1][0]), "+f"(pr[1][1]), "+f"(pr[2][0]), "+f"(pr[2][1]), "+f"(pr[3][0]), "+f"(pr[3][1]) :: "memory");
        };
        auto finish = [&](int ent, uint32_t resid) {
            const bool hi2 = t & 2, hi1 = t & 1, odd = g & 1;
            float ka0 = hi2 ? pr[2][0] : pr[0][0], ka1 = hi2 ? pr[2][1] : pr[0][1];
            float kb0 = hi2 ? pr[3][0] : pr[1][0], kb1 = hi2 ? pr[3][1] : pr[1][1];
            float sa0 = hi2 ? pr[0][0] : pr[2][0], sa1 = hi2 ? pr[0][1] : pr[2][1];
            float sb0 = hi2 ? pr[1][0] : pr[3][0], sb1 = hi2 ? pr[1][1] : pr[3][1];
            ka0 += __shfl_xor_sync(0xffffffffu, sa0, 2); ka1 += __shfl_xor_sync(0xffffffffu, sa1, 2);
            kb0 += __shfl_xor_sync(0xffffffffu, sb0, 2); kb1 += __shfl_xor_sync(0xffffffffu, sb1, 2);
            float k0 = hi1 ? kb0 : ka0, k1 = hi1 ? kb1 : ka1;
            float s0 = hi1 ? ka0 : kb0, s1 = hi1 ? ka1 : kb1;
            k0 += __shfl_xor_sync(0xffffffffu, s0, 1);
            k1 += __shfl_xor_sync(0xffffffffu, s1, 1);
            const float other = __shfl_xor_sync(0xffffffffu, odd ? k0 : k1, 4);
            const float lo = odd ? other : k0, hi = odd ? k1 : other;
            *(uint32_t*)((uint8_t*)p.out + (lane_off + (uint32_t)(ent & 127) * 512u)) = pack_bf(bf_lo(resid) + lo, bf_hi(resid) + hi);
        };
        auto entry = [&](int i) -> int { return __reduce_max_sync(0xffffffffu, (int)smem[SM_ORDER + i]); };
        auto load_resid = [&](int ent) -> uint32_t { return __ldg((const uint32_t*)((const uint8_t*)p.sv + (lane_off + (uint32_t)(ent & 127) * 512u))); };
        if (nnodes > 0) {
            int cur = entry(0), nxt = entry(1);
            uint32_t resid = load_resid(cur);
            start(cur);
#pragma unroll 1
            for (int i = 1; i < nnodes; i++) {
                wg_wait0();
                side(cur);
                weigh();
                start(nxt);
                finish(cur, resid);
                cur = nxt;
                resid = load_resid(cur);
                nxt = entry(i + 1);
            }
            wg_wait0();
            side(cur);
            weigh();
            finish(cur, resid);
        }
    } else {
        const int wg = wgi;
        uint32_t aoff[4];
        {
            const int e = (lane & 7) + 8 * (lane >> 4), ch = 2 * w + ((lane >> 3) & 1);
#pragma unroll
            for (int b = 0; b < 4; b++) aoff[b] = 2048 + e * 640 + b * 128 + ((ch ^ ((5 * e + b) & 7)) << 4);
        }
        const uint32_t stsm_0 = sb + SM_HT + wg * 16384 + (16 * w + (lane & 15)) * 128 + (((lane >> 4) ^ (lane & 7)) << 4);
        const uint32_t pv_0 = sb + SM_PV + wg * 3072 + (tid & 127) * 4;
        uint32_t hk = 0;
        const uint32_t ring_wg = ring + wg * nstage * STAGE_B;
        const uint32_t full_wg = bar_full + wg * MAX_STAGE * 8;

        float ys[8], yv[24], dQ[3][8];
#pragma unroll
        for (int i = 0; i < 24; i++) yv[i] = 0.f;
#pragma unroll
        for (int i = 0; i < 8; i++) { ys[i] = 0.f; dQ[0][i] = 0.f; dQ[1][i] = 0.f; dQ[2][i] = 0.f; }
        uint32_t phase = 0, st = ring_wg, fb = full_wg;
        const uint32_t st_end = ring_wg + nstage * STAGE_B;
        uint32_t ninfo_a = sb + SM_NINFO + (wg == 0 ? 0 : split) * 4;
        const uint32_t ninfo_end = sb + SM_NINFO + (wg == 0 ? split : nnodes) * 4;
        int G = __reduce_max_sync(0xffffffffu, (int)(lds32(ninfo_a) >> 20));
        uint32_t notify = 0;
#pragma unroll 1
        while (ninfo_a < ninfo_end) {
            ninfo_a += 4;
            const uint32_t info_next = lds32(ninfo_a);
#pragma unroll 1
            for (int gi = 0; gi < G; gi++) {
                uint32_t A[4][4];
                mbar_wait(fb, phase);
#pragma unroll
                for (int b = 0; b < 4; b++) ldsm4t(A[b], st + aoff[b]);
                const uint32_t bd = desc_lo(st), eb = fb + EMPTY_OFF;
                wg_fence();
                wgmma_n64_p(ys, yv, A[0], bd, gi);
                wgmma_n16_p(dQ[0], A[1], bd, gi);
                wgmma_n16_p(dQ[1], A[2], bd, gi);
                wgmma_n16_p(dQ[2], A[3], bd, gi);
                wg_commit();
                st += STAGE_B; fb += 8;
                if (st == st_end) { phase ^= 1; st = ring_wg; fb = full_wg; }
                if (notify) {
                    fence_async_smem();
                    __syncwarp();
                    mbar_arrive_elected(notify);
                    notify = 0;
                }
                wg_wait0();
                mbar_arrive_elected(eb);
            }
            const uint32_t hb = hk & 1;
            mbar_wait(bar_hempty + (2 * wg + hb) * 8, ((hk >> 1) & 1) ^ 1);
            hk++;
            const uint32_t stsm_a = stsm_0 + hb * 8192, pv_a = pv_0 + hb * 1536;
            stsm4(stsm_a, pack_bf(ys[0], ys[1]), pack_bf(ys[2], ys[3]), pack_bf(ys[4], ys[5]), pack_bf(ys[6], ys[7]));
#pragma unroll
            for (int i = 0; i < 6; i += 2) {
                stsm4(stsm_a ^ ((i + 2) << 4),
                      pack_bf(yv[4 * i], yv[4 * i + 1]), pack_bf(yv[4 * i + 2], yv[4 * i + 3]),
                      pack_bf(yv[4 * i + 4], yv[4 * i + 5]), pack_bf(yv[4 * i + 6], yv[4 * i + 7]));
            }
#pragma unroll
            for (int i = 0; i < 4; i++) asm volatile("" : "+r"(wp[1][i]));
#pragma unroll
            for (int a = 0; a < 3; a++) {
                const float* q = dQ[a];
                const float p0 = bf_lo(wp[1][0]) * q[0] + bf_hi(wp[1][0]) * q[1] + bf_lo(wp[1][2]) * q[4] + bf_hi(wp[1][2]) * q[5];
                const float p1 = bf_lo(wp[1][1]) * q[2] + bf_hi(wp[1][1]) * q[3] + bf_lo(wp[1][3]) * q[6] + bf_hi(wp[1][3]) * q[7];
                sts32(pv_a + a * 512, pack_bf(p0, p1));
            }
            notify = bar_hfull + (2 * wg + hb) * 8;
            G = __reduce_max_sync(0xffffffffu, (int)(info_next >> 20));
        }
        if (notify) {
            fence_async_smem();
            __syncwarp();
            mbar_arrive_elected(notify);
        }
    }
    STAMP(8);
}

typedef CUresult (*EncodeFn)(CUtensorMap*, CUtensorMapDataType, cuuint32_t, void*, const cuuint64_t*, const cuuint64_t*,
                             const cuuint32_t*, const cuuint32_t*, CUtensorMapInterleave, CUtensorMapSwizzle,
                             CUtensorMapL2promotion, CUtensorMapFloatOOBfill);

void make_map(EncodeFn enc, CUtensorMap* tm, const void* base, uint64_t lines, uint32_t box) {
    cuuint64_t gd[2] = {64, lines};
    cuuint64_t gs[1] = {128};
    cuuint32_t bd[2] = {64, box};
    cuuint32_t es[2] = {1, 1};
    enc(tm, CU_TENSOR_MAP_DATA_TYPE_BFLOAT16, 2, const_cast<void*>(base), gd, gs, bd, es, CU_TENSOR_MAP_INTERLEAVE_NONE,
        CU_TENSOR_MAP_SWIZZLE_128B, CU_TENSOR_MAP_L2_PROMOTION_L2_128B, CU_TENSOR_MAP_FLOAT_OOB_FILL_NONE);
}

void make_map3(EncodeFn enc, CUtensorMap* tm, const void* base, uint64_t nodes, uint32_t box) {
    cuuint64_t gd[3] = {64, 4, nodes};
    cuuint64_t gs[2] = {128, 512};
    cuuint32_t bd[3] = {64, 1, box};
    cuuint32_t es[3] = {1, 1, 1};
    enc(tm, CU_TENSOR_MAP_DATA_TYPE_BFLOAT16, 3, const_cast<void*>(base), gd, gs, bd, es, CU_TENSOR_MAP_INTERLEAVE_NONE,
        CU_TENSOR_MAP_SWIZZLE_128B, CU_TENSOR_MAP_L2_PROMOTION_L2_128B, CU_TENSOR_MAP_FLOAT_OOB_FILL_NONE);
}

}

extern "C" void kernel_launch(void* const* d_in, const int* in_sizes, int n_in, void* d_out, int out_size) {
    (void)n_in; (void)out_size;
    static int n_sm = 0;
    static EncodeFn enc = nullptr;
    static void* f_ptr = nullptr;
    if (n_sm == 0) {
        int dev = 0;
        cudaGetDevice(&dev);
        cudaDeviceGetAttribute(&n_sm, cudaDevAttrMultiProcessorCount, dev);
        cudaFuncSetAttribute(painn_kernel, cudaFuncAttributeMaxDynamicSharedMemorySize, SM_TOTAL);
        void* fn = nullptr;
        cudaDriverEntryPointQueryResult qr;
        cudaGetDriverEntryPoint("cuTensorMapEncodeTiled", &fn, cudaEnableDefault, &qr);
        enc = (EncodeFn)fn;
        cudaGetSymbolAddress(&f_ptr, g_F);
    }
    Params p;
    p.sv    = (const __nv_bfloat16*)d_in[0];
    p.pos   = (const __nv_bfloat16*)d_in[1];
    p.src   = (const int*)d_in[2];
    p.dst   = (const int*)d_in[3];
    p.freqs = (const __nv_bfloat16*)d_in[4];
    p.w1    = (const __nv_bfloat16*)d_in[5];
    p.w2    = (const __nv_bfloat16*)d_in[6];
    p.wr    = (const __nv_bfloat16*)d_in[7];
    p.out   = (__nv_bfloat16*)d_out;
    p.N = in_sizes[1] / 3;
    p.E = in_sizes[2];
    p.ncta = n_sm < MAX_CTA ? n_sm : MAX_CTA;
    p.npc = ((p.N + p.ncta - 1) / p.ncta + 3) & ~3;
    p.npc_magic = (uint32_t)(0x100000000ull / (uint32_t)p.npc) + 1u;
    p.quads_per_cta = ((p.E >> 2) + p.ncta - 1) / p.ncta;
    if (!enc || p.N > MAX_N || p.npc > MAX_NPC || (p.E & 3) || p.quads_per_cta > MAX_ROUNDS * 32) return;

    CUtensorMap tmF, tmFs;
    make_map(enc, &tmF, f_ptr, (uint64_t)p.N * 4, 4);
    make_map3(enc, &tmFs, f_ptr, (uint64_t)p.N, 4);

    cudaLaunchConfig_t cfg = {};
    cfg.gridDim = dim3(p.ncta);
    cfg.blockDim = dim3(NT);
    cfg.dynamicSmemBytes = SM_TOTAL;
    cfg.stream = cudaStreamPerThread;
    cudaLaunchAttribute attr[1];
    attr[0].id = cudaLaunchAttributeCooperative;
        attr[0].val.cooperative = 1;
    cfg.attrs = attr;
    cfg.numAttrs = 1;
    cudaLaunchKernelEx(&cfg, painn_kernel, p, tmF, tmFs);
}
```

```cpp
#include <cuda_runtime.h>
#include <cuda.h>
#include <cuda_bf16.h>
#include <stdint.h>

namespace {

constexpr int NT        = 512;
constexpr int NCWG      = 2;
constexpr int MAX_N     = 10240;
constexpr int MAX_CTA   = 136;
constexpr int MAX_NPC   = 80;
constexpr int MAX_ROUNDS = 38;
constexpr int SEG_CAP   = 64;
constexpr int SLOT_CAP  = 6144;
constexpr int MAX_STAGE = 6;
constexpr int STAGE_B   = 11264;
__host__ __device__ constexpr int row_line(int e) { return 36 * (e >> 3) + 9 * ((e & 7) >> 1) + 4 * (e & 1); }

constexpr uint32_t D_MIN_BITS = 0x38D2;
constexpr uint32_t D_MAX_BITS = 0x409C;
constexpr int TAB_ROWS  = (int)(D_MAX_BITS - D_MIN_BITS) + 1;
constexpr int TAB_ZERO  = TAB_ROWS;
constexpr int TAB_BYTES = (TAB_ROWS + 1) * 32;

constexpr int SM_BINCNT = 0;
constexpr int SM_NCNT   = SM_BINCNT + MAX_CTA * 4;
constexpr int SM_NINFO  = SM_NCNT + MAX_NPC * 4;
constexpr int SM_ORDER  = SM_NINFO + (MAX_NPC + 1) * 4;
constexpr int SM_CTRL   = SM_ORDER + MAX_NPC + 12;
constexpr int SM_BARS   = SM_CTRL + 64;
constexpr int SM_SID    = 2048 + 256;
constexpr int SM_META   = SM_SID + SLOT_CAP * 2;
constexpr int SM_TOTAL  = 232448;
constexpr int SM_HT     = (SM_TOTAL - 4 * 8192 - 4 * 1536) / 1024 * 1024;
constexpr int SM_PV     = SM_HT + 4 * 8192;
constexpr int SM_RING6  = SM_HT - NCWG * 6 * STAGE_B;
constexpr int SM_RING   = SM_HT - NCWG * 5 * STAGE_B;
constexpr int SLOT_CAP6 = (SM_RING6 - SM_META) / 8;
constexpr int P1_POS    = 3072;
constexpr int P1_SEGA   = P1_POS + 61440;
constexpr int P1_SEGB   = P1_SEGA + MAX_CTA * SEG_CAP * 8;
constexpr int P1_SV     = P1_SEGB + MAX_CTA * SEG_CAP * 4;
constexpr int P1_W1     = P1_SV + 4 * MAX_NPC * 128;
constexpr int P1_W2     = P1_W1 + 8192;
constexpr int P1_END    = P1_W2 + 8192;
constexpr int P1_REC    = P1_SEGA;
constexpr int STAGE_CAP = (P1_SV - P1_REC) / 16;
static_assert(SM_BARS + (12 + 2 * NCWG * MAX_STAGE) * 8 <= SM_SID, "misc block");
static_assert(SM_BARS + 256 <= P1_POS, "misc block");
static_assert(P1_END <= SM_TOTAL && P1_SV % 1024 == 0 && P1_REC % 16 == 0, "phase 1 overlay");
static_assert(SM_META + SLOT_CAP * 8 <= SM_RING && SM_PV + 4 * 1536 <= SM_TOTAL, "CSR");
static_assert(SM_RING % 1024 == 0 && SM_HT % 1024 == 0, "alignment");
static_assert(SM_BARS % 8 == 0 && SM_META % 8 == 0 && SM_CTRL % 4 == 0, "alignment");
static_assert(MAX_N * 6 <= 61440, "pos");
static_assert(SM_RING6 >= P1_POS && SM_RING6 % 1024 == 0 && STAGE_B % 1024 == 0 && SM_HT <= P1_END, "every byte of the stages is written (finite) during phase 1");
static_assert(SM_SID + MAX_NPC * 1024 <= SM_TOTAL, "slow path accumulators");

__device__ __align__(1024) uint4 g_F[MAX_N * 32];
__device__ __align__(128) uint32_t g_seg[MAX_CTA * MAX_CTA * SEG_CAP * 3];
__device__ uint4    g_table[(TAB_BYTES + 15) / 16];
__device__ unsigned g_bar[2];
#define STAMP(k)
#define STAMPT(k, T)

struct Params {
    const __nv_bfloat16* sv;
    const __nv_bfloat16* pos;
    const int*           src;
    const int*           dst;
    const __nv_bfloat16* freqs;
    const __nv_bfloat16* w1;
    const __nv_bfloat16* w2;
    const __nv_bfloat16* wr;
    __nv_bfloat16*       out;
    int N, E, ncta, npc;
    uint32_t npc_magic;
    int quads_per_cta;
};

__device__ __forceinline__ uint32_t smem_u32(const void* p) { return (uint32_t)__cvta_generic_to_shared(p); }
__device__ __forceinline__ float bf_lo(uint32_t v) { return __uint_as_float(v << 16); }
__device__ __forceinline__ float bf_hi(uint32_t v) { return __uint_as_float(v & 0xffff0000u); }
__device__ __forceinline__ uint32_t pack_bf(float lo, float hi) {
    uint32_t r;
    asm("cvt.rn.bf16x2.f32 %0, %1, %2;" : "=r"(r) : "f"(hi), "f"(lo));
    return r;
}
__device__ __forceinline__ float rbf(float x) { return bf_lo(pack_bf(x, 0.f)); }
__device__ __forceinline__ uint32_t hmul2(uint32_t a, uint32_t b) {
    uint32_t r;
    asm("mul.rn.bf16x2 %0, %1, %2;" : "=r"(r) : "r"(a), "r"(b));
    return r;
}
__device__ __forceinline__ uint32_t hsub2(uint32_t a, uint32_t b) {
    uint32_t r;
    asm("sub.rn.bf16x2 %0, %1, %2;" : "=r"(r) : "r"(a), "r"(b));
    return r;
}
__device__ __forceinline__ uint32_t lds32(uint32_t a) { uint32_t v; asm volatile("ld.shared.u32 %0, [%1];" : "=r"(v) : "r"(a)); return v; }
__device__ __forceinline__ uint2 lds64(uint32_t a) { uint2 v; asm volatile("ld.shared.v2.u32 {%0,%1}, [%2];" : "=r"(v.x), "=r"(v.y) : "r"(a)); return v; }
__device__ __forceinline__ uint4 lds128(uint32_t a) { uint4 v; asm volatile("ld.shared.v4.u32 {%0,%1,%2,%3}, [%4];" : "=r"(v.x), "=r"(v.y), "=r"(v.z), "=r"(v.w) : "r"(a)); return v; }
__device__ __forceinline__ void sts32(uint32_t a, uint32_t v) { asm volatile("st.shared.u32 [%0], %1;" ::"r"(a), "r"(v) : "memory"); }
__device__ __forceinline__ void sts128(uint32_t a, uint4 v) { asm volatile("st.shared.v4.u32 [%0], {%1,%2,%3,%4};" ::"r"(a), "r"(v.x), "r"(v.y), "r"(v.z), "r"(v.w) : "memory"); }
__device__ __forceinline__ void mbar_init(uint32_t bar, int cnt) { asm volatile("mbarrier.init.shared::cta.b64 [%0], %1;" ::"r"(bar), "r"(cnt) : "memory"); }
__device__ __forceinline__ void mbar_expect_tx(uint32_t bar, uint32_t bytes) { asm volatile("mbarrier.arrive.expect_tx.shared::cta.b64 _, [%0], %1;" ::"r"(bar), "r"(bytes) : "memory"); }
__device__ __forceinline__ void mbar_wait(uint32_t bar, uint32_t parity) {
    asm volatile("{\n.reg .pred p;\n.reg .u32 c;\n"
                 "mbarrier.try_wait.parity.shared::cta.b64 p, [%0], %1;\n"
                 "@p bra DONE_%=;\n"
                 "mov.u32 c, 0;\n"
                 "LOOP_%=:\n"
                 "mbarrier.try_wait.parity.shared::cta.b64 p, [%0], %1;\n"
                 "@p bra DONE_%=;\n"
                 "add.u32 c, c, 1;\n"
                 "setp.lt.u32 p, c, 4194304;\n"
                 "@p bra LOOP_%=;\n"
                 "DONE_%=:\n}"
                 ::"r"(bar), "r"(parity) : "memory");
}
__device__ __forceinline__ void mbar_arrive_elected(uint32_t bar) {
    asm volatile("{\n.reg .pred p;\nelect.sync _|p, 0xffffffff;\n@p mbarrier.arrive.shared::cta.b64 _, [%0];\n}" ::"r"(bar) : "memory");
}
__device__ __forceinline__ void bulk_g2s(uint32_t dst, const void* src, uint32_t bytes, uint32_t bar) {
    asm volatile("cp.async.bulk.shared::cluster.global.mbarrier::complete_tx::bytes [%0], [%1], %2, [%3];"
                 ::"r"(dst), "l"(src), "r"(bytes), "r"(bar) : "memory");
}
__device__ __forceinline__ void cp_async16(uint32_t dst, const void* src) {
    asm volatile("cp.async.cg.shared.global [%0], [%1], 16;" ::"r"(dst), "l"(src) : "memory");
}
__device__ __forceinline__ void tma_load(uint32_t dst, const CUtensorMap* tm, int line, uint32_t bar) {
    asm volatile("cp.async.bulk.tensor.2d.shared::cluster.global.mbarrier::complete_tx::bytes [%0], [%1, {%3, %4}], [%2];"
                 ::"r"(dst), "l"(tm), "r"(bar), "r"(0), "r"(line) : "memory");
}
__device__ __forceinline__ void tma_store3(const CUtensorMap* tm, int comp, int node, uint32_t src) {
    asm volatile("cp.async.bulk.tensor.3d.global.shared::cta.bulk_group [%0, {%2, %3, %4}], [%1];"
                 ::"l"(tm), "r"(src), "r"(0), "r"(comp), "r"(node) : "memory");
}
__device__ __forceinline__ void fence_async_smem() { asm volatile("fence.proxy.async.shared::cta;" ::: "memory"); }
__device__ __forceinline__ void ldsm4(uint32_t (&r)[4], uint32_t a) {
    asm volatile("ldmatrix.sync.aligned.m8n8.x4.shared.b16 {%0,%1,%2,%3}, [%4];" : "=r"(r[0]), "=r"(r[1]), "=r"(r[2]), "=r"(r[3]) : "r"(a) : "memory");
}
__device__ __forceinline__ void ldsm4t(uint32_t (&r)[4], uint32_t a) {
    asm volatile("ldmatrix.sync.aligned.m8n8.x4.trans.shared.b16 {%0,%1,%2,%3}, [%4];" : "=r"(r[0]), "=r"(r[1]), "=r"(r[2]), "=r"(r[3]) : "r"(a) : "memory");
}
__device__ __forceinline__ uint32_t ldsm4t_x4_probe(uint32_t (&A)[4][4], uint32_t a0, uint32_t a1, uint32_t a2, uint32_t a3,
                                                    uint32_t bar, uint32_t parity) {
    uint32_t ok;
    asm volatile("{\n.reg .pred p;\n"
                 "mbarrier.test_wait.parity.shared::cta.b64 p, [%21], %22;\n"
                 "ldmatrix.sync.aligned.m8n8.x4.trans.shared.b16 {%0,%1,%2,%3}, [%17];\n"
                 "ldmatrix.sync.aligned.m8n8.x4.trans.shared.b16 {%4,%5,%6,%7}, [%18];\n"
                 "ldmatrix.sync.aligned.m8n8.x4.trans.shared.b16 {%8,%9,%10,%11}, [%19];\n"
                 "ldmatrix.sync.aligned.m8n8.x4.trans.shared.b16 {%12,%13,%14,%15}, [%20];\n"
                 "selp.u32 %16, 1, 0, p;\n}"
                 : "=r"(A[0][0]), "=r"(A[0][1]), "=r"(A[0][2]), "=r"(A[0][3]), "=r"(A[1][0]), "=r"(A[1][1]), "=r"(A[1][2]), "=r"(A[1][3]),
                   "=r"(A[2][0]), "=r"(A[2][1]), "=r"(A[2][2]), "=r"(A[2][3]), "=r"(A[3][0]), "=r"(A[3][1]), "=r"(A[3][2]), "=r"(A[3][3]),
                   "=r"(ok)
                 : "r"(a0), "r"(a1), "r"(a2), "r"(a3), "r"(bar), "r"(parity) : "memory");
    return ok;
}
__device__ __forceinline__ void stsm4(uint32_t a, uint32_t r0, uint32_t r1, uint32_t r2, uint32_t r3) {
    asm volatile("stmatrix.sync.aligned.m8n8.x4.shared.b16 [%0], {%1,%2,%3,%4};" ::"r"(a), "r"(r0), "r"(r1), "r"(r2), "r"(r3) : "memory");
}
__device__ __forceinline__ void mma16816(float (&c)[4], const uint32_t (&a)[4], uint32_t b0, uint32_t b1) {
    asm volatile("mma.sync.aligned.m16n8k16.row.col.f32.bf16.bf16.f32 {%0,%1,%2,%3}, {%4,%5,%6,%7}, {%8,%9}, {%0,%1,%2,%3};"
                 : "+f"(c[0]), "+f"(c[1]), "+f"(c[2]), "+f"(c[3])
                 : "r"(a[0]), "r"(a[1]), "r"(a[2]), "r"(a[3]), "r"(b0), "r"(b1));
}

__device__ __forceinline__ uint32_t desc_lo(uint32_t saddr) { return ((saddr & 0x3FFFF) >> 4) | (1u << 16); }
#define DESC_HI "0x40000040"
__device__ __forceinline__ void wg_fence() { asm volatile("wgmma.fence.sync.aligned;" ::: "memory"); }
__device__ __forceinline__ void wg_commit() { asm volatile("wgmma.commit_group.sync.aligned;" ::: "memory"); }
__device__ __forceinline__ void wg_wait0() { asm volatile("wgmma.wait_group.sync.aligned 0;" ::: "memory"); }

__device__ __forceinline__ void wgmma_n48_first(float (&e)[24], const uint32_t (&a)[4], uint32_t bdesc) {
    asm volatile("{\n.reg .b64 b;\nmov.b64 b, {%28, " DESC_HI "};\n"
                 "wgmma.mma_async.sync.aligned.m64n48k16.f32.bf16.bf16 {%0,%1,%2,%3,%4,%5,%6,%7,%8,%9,%10,%11,%12,%13,%14,%15,%16,%17,%18,%19,%20,%21,%22,%23}, {%24,%25,%26,%27}, b, 0, 1, 1, 1;\n}"
                 : "=f"(e[0]), "=f"(e[1]), "=f"(e[2]), "=f"(e[3]), "=f"(e[4]), "=f"(e[5]), "=f"(e[6]), "=f"(e[7]), "=f"(e[8]), "=f"(e[9]), "=f"(e[10]), "=f"(e[11]), "=f"(e[12]), "=f"(e[13]), "=f"(e[14]), "=f"(e[15]), "=f"(e[16]), "=f"(e[17]), "=f"(e[18]), "=f"(e[19]), "=f"(e[20]), "=f"(e[21]), "=f"(e[22]), "=f"(e[23])
                 : "r"(a[0]), "r"(a[1]), "r"(a[2]), "r"(a[3]), "r"(bdesc));
}
__device__ __forceinline__ void wgmma_n48(float (&e)[24], const uint32_t (&a)[4], uint32_t bdesc) {
    asm volatile("{\n.reg .b64 b;\nmov.b64 b, {%28, " DESC_HI "};\n"
                 "wgmma.mma_async.sync.aligned.m64n48k16.f32.bf16.bf16 {%0,%1,%2,%3,%4,%5,%6,%7,%8,%9,%10,%11,%12,%13,%14,%15,%16,%17,%18,%19,%20,%21,%22,%23}, {%24,%25,%26,%27}, b, 1, 1, 1, 1;\n}"
                 : "+f"(e[0]), "+f"(e[1]), "+f"(e[2]), "+f"(e[3]), "+f"(e[4]), "+f"(e[5]), "+f"(e[6]), "+f"(e[7]), "+f"(e[8]), "+f"(e[9]), "+f"(e[10]), "+f"(e[11]), "+f"(e[12]), "+f"(e[13]), "+f"(e[14]), "+f"(e[15]), "+f"(e[16]), "+f"(e[17]), "+f"(e[18]), "+f"(e[19]), "+f"(e[20]), "+f"(e[21]), "+f"(e[22]), "+f"(e[23])
                 : "r"(a[0]), "r"(a[1]), "r"(a[2]), "r"(a[3]), "r"(bdesc));
}
__device__ __forceinline__ void wgmma_n16_first(float (&d)[8], const uint32_t (&a)[4], uint32_t bdesc) {
    asm volatile("{\n.reg .b64 b;\nmov.b64 b, {%12, " DESC_HI "};\n"
                 "wgmma.mma_async.sync.aligned.m64n16k16.f32.bf16.bf16 {%0,%1,%2,%3,%4,%5,%6,%7}, {%8,%9,%10,%11}, b, 0, 1, 1, 1;\n}"
                 : "=f"(d[0]), "=f"(d[1]), "=f"(d[2]), "=f"(d[3]), "=f"(d[4]), "=f"(d[5]), "=f"(d[6]), "=f"(d[7])
                 : "r"(a[0]), "r"(a[1]), "r"(a[2]), "r"(a[3]), "r"(bdesc));
}
__device__ __forceinline__ void wgmma_n16(float (&d)[8], const uint32_t (&a)[4], uint32_t bdesc) {
    asm volatile("{\n.reg .b64 b;\nmov.b64 b, {%12, " DESC_HI "};\n"
                 "wgmma.mma_async.sync.aligned.m64n16k16.f32.bf16.bf16 {%0,%1,%2,%3,%4,%5,%6,%7}, {%8,%9,%10,%11}, b, 1, 1, 1, 1;\n}"
                 : "+f"(d[0]), "+f"(d[1]), "+f"(d[2]), "+f"(d[3]), "+f"(d[4]), "+f"(d[5]), "+f"(d[6]), "+f"(d[7])
                 : "r"(a[0]), "r"(a[1]), "r"(a[2]), "r"(a[3]), "r"(bdesc));
}

__device__ __forceinline__ void wgmma_n64_p(float (&d)[8], float (&e)[24], const uint32_t (&a)[4], uint32_t bdesc, int acc) {
    asm volatile("{\n.reg .pred p;\n.reg .b64 b;\nsetp.ne.b32 p, %37, 0;\nmov.b64 b, {%36, " DESC_HI "};\n"
                 "wgmma.mma_async.sync.aligned.m64n64k16.f32.bf16.bf16 {%0,%1,%2,%3,%4,%5,%6,%7,%8,%9,%10,%11,%12,%13,%14,%15,%16,%17,%18,%19,%20,%21,%22,%23,%24,%25,%26,%27,%28,%29,%30,%31}, {%32,%33,%34,%35}, b, p, 1, 1, 1;\n}"
                 : "+f"(d[0]), "+f"(d[1]), "+f"(d[2]), "+f"(d[3]), "+f"(d[4]), "+f"(d[5]), "+f"(d[6]), "+f"(d[7]),
                   "+f"(e[0]), "+f"(e[1]), "+f"(e[2]), "+f"(e[3]), "+f"(e[4]), "+f"(e[5]), "+f"(e[6]), "+f"(e[7]), "+f"(e[8]), "+f"(e[9]), "+f"(e[10]), "+f"(e[11]), "+f"(e[12]), "+f"(e[13]), "+f"(e[14]), "+f"(e[15]), "+f"(e[16]), "+f"(e[17]), "+f"(e[18]), "+f"(e[19]), "+f"(e[20]), "+f"(e[21]), "+f"(e[22]), "+f"(e[23])
                 : "r"(a[0]), "r"(a[1]), "r"(a[2]), "r"(a[3]), "r"(bdesc), "r"(acc));
}
__device__ __forceinline__ void wgmma_n16_p(float (&d)[8], const uint32_t (&a)[4], uint32_t bdesc, int acc) {
    asm volatile("{\n.reg .pred p;\n.reg .b64 b;\nsetp.ne.b32 p, %13, 0;\nmov.b64 b, {%12, " DESC_HI "};\n"
                 "wgmma.mma_async.sync.aligned.m64n16k16.f32.bf16.bf16 {%0,%1,%2,%3,%4,%5,%6,%7}, {%8,%9,%10,%11}, b, p, 1, 1, 1;\n}"
                 : "+f"(d[0]), "+f"(d[1]), "+f"(d[2]), "+f"(d[3]), "+f"(d[4]), "+f"(d[5]), "+f"(d[6]), "+f"(d[7])
                 : "r"(a[0]), "r"(a[1]), "r"(a[2]), "r"(a[3]), "r"(bdesc), "r"(acc));
}

__device__ __forceinline__ uint32_t edge_dist(uint32_t sxy, uint32_t sz, uint32_t dxy, uint32_t dz, uint32_t& rxy, uint32_t& rz) {
    rxy = hsub2(sxy, dxy);
    rz  = hsub2(sz, dz);
    uint32_t qxy = hmul2(rxy, rxy), qz = hmul2(rz, rz);
    float ss = rbf((bf_lo(qxy) + bf_hi(qxy)) + bf_lo(qz));
    float s2 = rbf(ss + 1e-8f);
    float d;
    asm("sqrt.approx.ftz.f32 %0, %1;" : "=f"(d) : "f"(s2));
    return pack_bf(d, 0.f) & 0xffffu;
}

__device__ __noinline__ float radial_value(float d, float f) {
    float arg = rbf(d * f);
    float sn  = rbf(sinf(arg));
    float rb  = rbf(__fdiv_rn(sn, d));
    float c   = rbf(cosf(rbf(__fdiv_rn(rbf(d * 3.14159265358979323846f), 5.0f))));
    float fc  = rbf(0.5f * rbf(c + 1.0f));
    return rb * fc;
}

__global__ void __launch_bounds__(NT, 1)
painn_kernel(const Params p, const __grid_constant__ CUtensorMap tmF, const __grid_constant__ CUtensorMap tmFs) {
    extern __shared__ __align__(1024) uint8_t smem[];
    const uint32_t sb   = smem_u32(smem);
    const int tid  = threadIdx.x, lane = tid & 31, warp = __shfl_sync(0xffffffffu, tid >> 5, 0);
    const int cta  = blockIdx.x;
    const int g    = lane >> 2, t = lane & 3;
    int* binCnt = (int*)(smem + SM_BINCNT);
    int* nCnt   = (int*)(smem + SM_NCNT);
    uint32_t* nInfo = (uint32_t*)(smem + SM_NINFO);
    volatile int* ctrl = (volatile int*)(smem + SM_CTRL);
    const uint32_t bar_pos = sb + SM_BARS;
    const uint32_t bar_full = bar_pos + 32, bar_empty = bar_full + NCWG * MAX_STAGE * 8;
    const uint32_t bar_hfull = bar_empty + NCWG * MAX_STAGE * 8, bar_hempty = bar_hfull + 32;

    const int node0  = cta * p.npc;
    const int nnodes = max(0, min(p.npc, p.N - node0));

    STAMP(0);
    if (tid == 32) {
        mbar_init(bar_pos, 1);
        asm volatile("fence.mbarrier_init.release.cluster;" ::: "memory");
        uint32_t pos_bytes = (uint32_t)(p.N * 6 + 15) & ~15u;
        mbar_expect_tx(bar_pos, pos_bytes);
        bulk_g2s(sb + P1_POS, p.pos, pos_bytes, bar_pos);
    } else if (tid == 64) {
        for (int i = 0; i < 4; i++) { mbar_init(bar_hfull + 8 * i, 4); mbar_init(bar_hempty + 8 * i, 4); }
        asm volatile("prefetch.tensormap [%0];" ::"l"(&tmF) : "memory");
        asm volatile("prefetch.tensormap [%0];" ::"l"(&tmFs) : "memory");
    } else if (tid >= 96 && tid < 96 + NCWG * MAX_STAGE) {
        mbar_init(bar_full + 8 * (tid - 96), 2);
        mbar_init(bar_empty + 8 * (tid - 96), 4);
    }
    unsigned bar_seen = 0;
    if (tid == 0 || tid == 32) asm volatile("ld.relaxed.gpu.global.u32 %0, [%1];" : "=r"(bar_seen) : "l"(&g_bar[tid >> 5]) : "memory");
    const bool mlp_warp = warp >= 6;
    int4 s4[3], d4[3];
    const int q0 = cta * p.quads_per_cta;
    const int qend = min(q0 + p.quads_per_cta, p.E >> 2);
#pragma unroll
    for (int k = 0; k < 3; k++) {
        const int q = q0 + (k < 2 ? warp + 16 * k : 32 + warp) * 32 + lane;
        const bool ok = q < qend && (k < 2 || !mlp_warp);
        s4[k] = ok ? __ldg((const int4*)p.src + q) : make_int4(-1, -1, -1, -1);
        d4[k] = ok ? __ldg((const int4*)p.dst + q) : make_int4(0, 0, 0, 0);
    }
    if (tid < MAX_CTA) binCnt[tid] = 0;
    if (tid < MAX_NPC) nCnt[tid] = 0;
    if (tid < 16) ctrl[tid] = 0;
    if (tid >= 256 && tid < 256 + 240) {
        const int i = tid - 256;
        asm volatile("prefetch.global.L2 [%0];" ::"l"(i < 48 ? (const uint8_t*)p.wr + i * 128 : (const uint8_t*)p.w2 + (i - 48) * 128));
    }
    for (int i = (P1_POS + ((p.N * 6 + 15) & ~15)) / 16 + tid; i < P1_SV / 16; i += NT) sts128(sb + i * 16, make_uint4(0u, 0u, 0u, 0u));
    for (int i = tid; i < 4 * (MAX_NPC - nnodes) * 8; i += NT)
        sts128(sb + P1_SV + (i / ((MAX_NPC - nnodes) * 8)) * (MAX_NPC * 128) + nnodes * 128 + (i % ((MAX_NPC - nnodes) * 8)) * 16, make_uint4(0u, 0u, 0u, 0u));
    __syncthreads();

    mbar_wait(bar_pos, 0);
    if (s4[0].x == 0x7fffffff) ctrl[15] = 1;
    for (int i = tid; i < nnodes * 32; i += NT) {
        const int r = i >> 5, b = (i >> 3) & 3, c = i & 7;
        cp_async16(sb + P1_SV + b * (MAX_NPC * 128) + r * 128 + ((c ^ (r & 7)) << 4), (const uint8_t*)p.sv + (size_t)node0 * 512 + i * 16);
    }
    for (int i = tid; i < 1024; i += NT) {
        const int m = i >> 9, k = (i >> 3) & 63, c = i & 7;
        cp_async16(sb + P1_W1 + m * 8192 + k * 128 + ((c ^ (k & 7)) << 4),
                   m == 0 ? (const uint8_t*)p.w1 + k * 128 + c * 16 : (const uint8_t*)p.w2 + k * 384 + 128 + c * 16);
    }
    asm volatile("cp.async.commit_group;" ::: "memory");
    STAMP(1);
#pragma unroll
    for (int k = 0; k < 3; k++) {
        const int ss[4] = {s4[k].x, s4[k].y, s4[k].z, s4[k].w};
        const int dd[4] = {d4[k].x, d4[k].y, d4[k].z, d4[k].w};
        if (ss[0] >= 0) {
            uint32_t w0[4], w1[4], v0[4], v1[4], r0[4], r1[4], r2[4], bin[4], rank[4];
#pragma unroll
            for (int j = 0; j < 4; j++) {
                const uint32_t a = (sb + P1_POS + 6u * (uint32_t)ss[j]) & ~3u, c = (sb + P1_POS + 6u * (uint32_t)dd[j]) & ~3u;
                w0[j] = lds32(a); w1[j] = lds32(a + 4); v0[j] = lds32(c); v1[j] = lds32(c + 4);
            }
#pragma unroll
            for (int j = 0; j < 4; j++) {
                const uint32_t sh = (uint32_t)ss[j] << 4, dh = (uint32_t)dd[j] << 4;
                uint32_t rxy, rz;
                const uint32_t db = edge_dist(__funnelshift_r(w0[j], w1[j], sh), __funnelshift_r(w1[j], w1[j], sh),
                                              __funnelshift_r(v0[j], v1[j], dh), __funnelshift_r(v1[j], v1[j], dh), rxy, rz);
                float inv;
                asm("rcp.approx.ftz.f32 %0, %1;" : "=f"(inv) : "f"(__uint_as_float(db << 16)));
                bin[j] = __umulhi((uint32_t)dd[j], p.npc_magic);
                r0[j] = (uint32_t)ss[j] | ((db - D_MIN_BITS) << 16);
                r1[j] = pack_bf(bf_lo(rxy) * inv, bf_hi(rxy) * inv);
                r2[j] = __byte_perm(pack_bf(bf_lo(rz) * inv, 0.f), (uint32_t)dd[j] - bin[j] * (uint32_t)p.npc, 0x5410);
                rank[j] = db <= D_MAX_BITS ? (uint32_t)atomicAdd(&binCnt[bin[j]], 1) : 0xffffu;
            }
#pragma unroll
            for (int j = 0; j < 4; j++) {
                if (rank[j] < SEG_CAP) {
                    const uint32_t slot = bin[j] * SEG_CAP + rank[j];
                    asm volatile("st.shared.v2.u32 [%0], {%1, %2};" ::"r"(sb + P1_SEGA + slot * 8), "r"(r0[j]), "r"(r1[j]) : "memory");
                    sts32(sb + P1_SEGB + slot * 4, r2[j]);
                }
            }
        }
    }
    __syncthreads();
    STAMP(2);
    {
        constexpr int IT = (MAX_CTA + 31) / 32;
        uint2 ca[IT][2];
        uint32_t cb[IT][2];
        int cn[IT];
#pragma unroll
        for (int it = 0; it < IT; it++) {
            const int b = min(2 * warp + (lane >> 4) + 32 * it, MAX_CTA - 1);
            cn[it] = binCnt[b];
#pragma unroll
            for (int u = 0; u < 2; u++) {
                const int j = (lane & 15) + 16 * u;
                ca[it][u] = lds64(sb + P1_SEGA + (b * SEG_CAP + j) * 8);
                cb[it][u] = lds32(sb + P1_SEGB + (b * SEG_CAP + j) * 4);
            }
        }
#pragma unroll
        for (int it = 0; it < IT; it++) {
            const int b = 2 * warp + (lane >> 4) + 32 * it;
            if (b < p.ncta) {
                uint32_t* dstp = g_seg + ((size_t)cta * MAX_CTA + b) * (SEG_CAP * 3);
                const uint32_t tag = (uint32_t)min(cn[it], 511) << 23;
#pragma unroll
                for (int u = 0; u < 2; u++) {
                    const int j = (lane & 15) + 16 * u;
                    *(uint2*)(dstp + 2 * j) = ca[it][u];
                    dstp[2 * SEG_CAP + j] = cb[it][u] | tag;
                }
                for (int j = 32 + (lane & 15); j < ((min(cn[it], SEG_CAP) + 7) & ~7); j += 16) {
                    *(uint2*)(dstp + 2 * j) = lds64(sb + P1_SEGA + (b * SEG_CAP + j) * 8);
                    dstp[2 * SEG_CAP + j] = lds32(sb + P1_SEGB + (b * SEG_CAP + j) * 4);
                }
            }
        }
    }
    STAMP(7);
    asm volatile("cp.async.wait_group 0;" ::: "memory");
    __syncthreads();
    STAMP(3);
    if (tid == 64) asm volatile("red.add.release.gpu.global.u32 [%0], 1;" ::"l"(&g_bar[0]) : "memory");

    if (!mlp_warp) {
        const int rows_per = (TAB_ROWS + 1 + p.ncta - 1) / p.ncta;
        for (int i = tid; i < rows_per * 8; i += 6 * 32) {
            int row = cta * rows_per + (i >> 3), kp = i & 7;
            if (row <= TAB_ROWS) {
                uint32_t val = 0;
                if (row < TAB_ROWS) {
                    float d = __uint_as_float((D_MIN_BITS + row) << 16);
                    uint32_t f2 = __ldg((const uint32_t*)p.freqs + kp);
                    val = pack_bf(radial_value(d, bf_lo(f2)), radial_value(d, bf_hi(f2)));
                }
                ((uint32_t*)g_table)[row * 8 + kp] = val;
            }
        }
    } else {
        const int mt = (warp - 6) >> 1, hf = (warp - 6) & 1;
        if (mt * 16 < nnodes) {
            STAMPT(10, 6 * 32);
            const int lrow = lane & 15, lch = lane >> 4;
            const uint32_t rowb = sb + P1_SV + (mt * 16 + lrow) * 128;
            const uint32_t key0 = lrow & 7;
            float acc[4][4];
#pragma unroll
            for (int i = 0; i < 4; i++) { acc[i][0] = acc[i][1] = acc[i][2] = acc[i][3] = 0.f; }
#pragma unroll
            for (int ks = 0; ks < 4; ks++) {
                uint32_t a[4];
                ldsm4(a, rowb + (((2 * ks + lch) ^ key0) << 4));
                const int kk = 16 * ks + lrow;
#pragma unroll
                for (int nt = 0; nt < 4; nt += 2) {
                    uint32_t b[4];
                    ldsm4t(b, sb + P1_W1 + kk * 128 + (((4 * hf + nt + lch) ^ (kk & 7)) << 4));
                    mma16816(acc[nt], a, b[0], b[1]);
                    mma16816(acc[nt + 1], a, b[2], b[3]);
                }
            }
            uint32_t hp[4][2];
#pragma unroll
            for (int i = 0; i < 4; i++) {
                float h[4];
#pragma unroll
                for (int q = 0; q < 4; q++) {
                    float x = rbf(acc[i][q]);
                    h[q] = __fdividef(x, 1.0f + __expf(-x));
                    acc[i][q] = 0.f;
                }
                hp[i][0] = pack_bf(h[0], h[1]);
                hp[i][1] = pack_bf(h[2], h[3]);
            }
            asm volatile("bar.sync %0, 64;" ::"r"(4 + mt) : "memory");
#pragma unroll
            for (int i = 0; i < 4; i += 2)
                stsm4(rowb + (((4 * hf + i + lch) ^ key0) << 4), hp[i][0], hp[i][1], hp[i + 1][0], hp[i + 1][1]);
            asm volatile("bar.sync %0, 64;" ::"r"(4 + mt) : "memory");
#pragma unroll
            for (int ks = 0; ks < 4; ks++) {
                uint32_t a[4];
                ldsm4(a, rowb + (((2 * ks + lch) ^ key0) << 4));
                const int kk = 16 * ks + lrow;
#pragma unroll
                for (int nt = 0; nt < 4; nt += 2) {
                    uint32_t b[4];
                    ldsm4t(b, sb + P1_W2 + kk * 128 + (((4 * hf + nt + lch) ^ (kk & 7)) << 4));
                    mma16816(acc[nt], a, b[0], b[1]);
                    mma16816(acc[nt + 1], a, b[2], b[3]);
                }
            }
            uint32_t vq[2][3][4];
            const uint32_t vb = sb + P1_SV + (mt * 16 + g) * 128 + 4 * t;
#pragma unroll
            for (int rh = 0; rh < 2; rh++)
#pragma unroll
                for (int a = 0; a < 3; a++)
#pragma unroll
                    for (int i = 0; i < 4; i++) vq[rh][a][i] = lds32(vb + (a + 1) * (MAX_NPC * 128) + rh * 1024 + (((4 * hf + i) ^ g) << 4));
#pragma unroll
            for (int rh = 0; rh < 2; rh++)
#pragma unroll
                for (int a = 0; a < 3; a++)
#pragma unroll
                    for (int i = 0; i < 4; i++)
                        sts32(vb + (a + 1) * (MAX_NPC * 128) + rh * 1024 + (((4 * hf + i) ^ g) << 4),
                              hmul2(pack_bf(acc[i][2 * rh], acc[i][2 * rh + 1]), vq[rh][a][i]));
            fence_async_smem();
            asm volatile("bar.sync %0, 64;" ::"r"(4 + mt) : "memory");
            {
                const int r4 = mt * 16 + 8 * hf + 4 * (lane >> 2), comp = lane & 3;
                if (lane < 8 && r4 < nnodes) tma_store3(&tmFs, comp, node0 + r4, sb + P1_SV + comp * (MAX_NPC * 128) + r4 * 128);
            }
            asm volatile("cp.async.bulk.commit_group;" ::: "memory");
        }
        STAMPT(11, 6 * 32);
    }
    if (tid == 0) {
        const unsigned target = (bar_seen / (unsigned)p.ncta + 1u) * (unsigned)p.ncta;
        unsigned cur;
        int spins = 0;
        do {
            asm volatile("ld.acquire.gpu.global.u32 %0, [%1];" : "=r"(cur) : "l"(&g_bar[0]) : "memory");
        } while ((int)(cur - target) < 0 && ++spins < (1 << 24));
    }
    STAMP(4);
    __syncthreads();
    STAMP(5);

    constexpr int SEG_IT = (MAX_CTA + 31) / 32;
    uint2 ra[SEG_IT][2];
    uint32_t rb[SEG_IT][2], rr[SEG_IT][2];
#pragma unroll
    for (int it = 0; it < SEG_IT; it++) {
        const int b = 2 * warp + (lane >> 4) + 32 * it;
        const uint32_t* sp = g_seg + ((size_t)b * MAX_CTA + cta) * (SEG_CAP * 3);
#pragma unroll
        for (int u = 0; u < 2; u++) {
            const int j = (lane & 15) + 16 * u;
            ra[it][u] = b < p.ncta ? __ldcg((const uint2*)(sp + 2 * j)) : make_uint2(0u, 0u);
            rb[it][u] = b < p.ncta ? __ldcg(sp + 2 * SEG_CAP + j) : 0u;
        }
    }
    if (mlp_warp && lane < 8) {
        asm volatile("cp.async.bulk.wait_group 0;" ::: "memory");
        asm volatile("fence.proxy.async;" ::: "memory");
    }
    STAMP(9);
    uint2 xa[SEG_IT];
    uint32_t xb[SEG_IT];
#pragma unroll
    for (int it = 0; it < SEG_IT; it++) {
        const int cnt = rb[it][0] >> 23;
        const int b = 2 * warp + (lane >> 4) + 32 * it;
        const uint32_t* sp = g_seg + ((size_t)b * MAX_CTA + cta) * (SEG_CAP * 3);
        const bool has = 32 + (lane & 15) < cnt;
        xa[it] = has ? __ldcg((const uint2*)(sp + 2 * (32 + (lane & 15)))) : make_uint2(0u, 0u);
        xb[it] = has ? __ldcg(sp + 2 * SEG_CAP + 32 + (lane & 15)) : 0u;
    }
#pragma unroll
    for (int it = 0; it < SEG_IT; it++) {
        const int cnt = rb[it][0] >> 23;
        if (cnt > SEG_CAP) ctrl[1] = 1;
#pragma unroll
        for (int u = 0; u < 2; u++)
            rr[it][u] = (lane & 15) + 16 * u < cnt ? (uint32_t)atomicAdd(&nCnt[(rb[it][u] >> 16) & 0x7fu], 1) : 0xffffffffu;
    }
#pragma unroll
    for (int it = 0; it < SEG_IT; it++) {
        const int cnt = rb[it][0] >> 23;
        if (32 + (lane & 15) < cnt) {
            const int pos = atomicAdd((int*)&ctrl[8], 1);
            const uint32_t rank = (uint32_t)atomicAdd(&nCnt[(xb[it] >> 16) & 0x7fu], 1);
            if (pos < STAGE_CAP) sts128(sb + P1_REC + pos * 16, make_uint4(xa[it].x, xa[it].y, xb[it], rank));
        }
        if (cnt > 48) {
            const int b = 2 * warp + (lane >> 4) + 32 * it;
            const uint32_t* sp = g_seg + ((size_t)b * MAX_CTA + cta) * (SEG_CAP * 3);
            const int j = 48 + (lane & 15);
            if (j < min(cnt, SEG_CAP)) {
                const uint2 a = __ldcg((const uint2*)(sp + 2 * j));
                const uint32_t c = __ldcg(sp + 2 * SEG_CAP + j);
                const int pos = atomicAdd((int*)&ctrl[8], 1);
                const uint32_t rank = (uint32_t)atomicAdd(&nCnt[(c >> 16) & 0x7fu], 1);
                if (pos < STAGE_CAP) sts128(sb + P1_REC + pos * 16, make_uint4(a.x, a.y, c, rank));
            }
        }
    }
    STAMP(13);
    __syncthreads();
    if (tid == 64) asm volatile("red.add.release.gpu.global.u32 [%0], 1;" ::"l"(&g_bar[1]) : "memory");
    STAMP(14);
    const int total = ctrl[8];
    if (tid == 0 && total > STAGE_CAP) ctrl[1] = 1;
    if (warp == 0) {
        int c[3], s = 0;
#pragma unroll
        for (int i = 0; i < 3; i++) {
            int b = lane * 3 + i;
            c[i] = b < nnodes ? max(16, (nCnt[b] + 15) & ~15) : 0;
            s += c[i];
        }
        int x = s;
#pragma unroll
        for (int o = 1; o < 32; o <<= 1) { int y = __shfl_up_sync(0xffffffffu, x, o); if (lane >= o) x += y; }
        const int slots = __shfl_sync(0xffffffffu, x, 31);
        int off = x - s, below = 0;
#pragma unroll
        for (int i = 0; i < 3; i++) {
            int b = lane * 3 + i;
            if (b < nnodes) {
                nInfo[b] = (uint32_t)off | ((uint32_t)c[i] << 16);
                below += (2 * off + c[i] < slots);
            }
            off += c[i];
        }
        below = __reduce_add_sync(0xffffffffu, below);
        if (lane == 0) {
            ctrl[2] = below;
            ctrl[4] = slots;
            if (slots > SLOT_CAP) ctrl[1] = 1;
        }
    }
    __syncthreads();
    if (ctrl[1] == 0) {
        uint16_t* sid = (uint16_t*)(smem + SM_SID);
        uint2* meta = (uint2*)(smem + SM_META);
#pragma unroll
        for (int it = 0; it < SEG_IT; it++)
#pragma unroll
            for (int u = 0; u < 2; u++)
                if (rr[it][u] != 0xffffffffu) rr[it][u] += lds32(sb + SM_NINFO + ((rb[it][u] >> 16) & 0x7fu) * 4) & 0xffffu;
#pragma unroll
        for (int it = 0; it < SEG_IT; it++)
#pragma unroll
            for (int u = 0; u < 2; u++)
                if (rr[it][u] != 0xffffffffu) {
                    sid[rr[it][u]]  = (uint16_t)((ra[it][u].x & 0xffffu) << 2);
                    meta[rr[it][u]] = make_uint2(((ra[it][u].x >> 16) << 5) | (rb[it][u] << 16), ra[it][u].y);
                }
        for (int i = tid; i < total; i += NT) {
            const uint4 r = lds128(sb + P1_REC + i * 16);
            const int pos = (int)(lds32(sb + SM_NINFO + ((r.z >> 16) & 0x7fu) * 4) & 0xffffu) + (int)r.w;
            sid[pos]  = (uint16_t)((r.x & 0xffffu) << 2);
            meta[pos] = make_uint2(((r.x >> 16) << 5) | (r.z << 16), r.y);
        }
        if (tid >= NT - 128 && tid - (NT - 128) < nnodes) {
            const int b = tid - (NT - 128), split = ctrl[2];
            const int mid = split < nnodes ? (int)(nInfo[split] & 0xffffu) : ctrl[4];
            const int st = b >= split;
            const int mine = (int)(nInfo[b] & 0xffffu) + (int)(nInfo[b] >> 16) - (st ? mid : 0);
            int lo = st ? 0 : split, hi = st ? split : nnodes;
            const int first = lo;
            while (lo < hi) {
                const int o = (lo + hi) >> 1;
                const int other = (int)(nInfo[o] & 0xffffu) + (int)(nInfo[o] >> 16) - (st ? 0 : mid);
                if (st ? (other <= mine) : (other < mine)) lo = o + 1; else hi = o;
            }
            const int rank = (st ? b - split : b) + lo - first;
            smem[SM_ORDER + rank] = (uint8_t)(b | (st << 7));
        }
        for (int i = tid; i < nnodes * 16; i += NT) {
            int nl = i >> 4, c = nCnt[nl];
            int j = (c & ~15) + (i & 15);
            if (j >= c && (j < 16 || (c & 15))) {
                int pos = (int)(nInfo[nl] & 0xffffu) + j;
                sid[pos]  = 0xffffu;
                meta[pos] = make_uint2((uint32_t)TAB_ZERO << 5, 0u);
            }
        }
    }
    STAMP(15);
    if (tid == 32) {
        const unsigned target = (bar_seen / (unsigned)p.ncta + 1u) * (unsigned)p.ncta;
        unsigned cur;
        int spins = 0;
        do {
            asm volatile("ld.acquire.gpu.global.u32 %0, [%1];" : "=r"(cur) : "l"(&g_bar[1]) : "memory");
        } while ((int)(cur - target) < 0 && ++spins < (1 << 24));
        asm volatile("fence.proxy.async.global;" ::: "memory");
    }
    fence_async_smem();
    __syncthreads();
    STAMP(6);

    if (__shfl_sync(0xffffffffu, ctrl[1], 0) != 0) {
        float* acc = (float*)(smem + P1_POS);
        for (int i = tid; i < nnodes * 256; i += NT) acc[i] = 0.f;
        __syncthreads();
        const uint16_t* posu = (const uint16_t*)p.pos;
        const uint32_t* tabg = (const uint32_t*)g_table;
        const uint32_t* Fw = (const uint32_t*)g_F;
        for (int e0 = warp * 32; e0 < p.E; e0 += NT) {
            int e = e0 + lane;
            int s = 0, d = 0;
            uint32_t db = 0xffff, rxy = 0, rz = 0;
            bool act = false;
            if (e < p.E) {
                s = p.src[e]; d = p.dst[e];
                if (d >= node0 && d < node0 + nnodes) {
                    uint32_t sxy = posu[s * 3] | ((uint32_t)posu[s * 3 + 1] << 16), sz = posu[s * 3 + 2];
                    uint32_t dxy = posu[d * 3] | ((uint32_t)posu[d * 3 + 1] << 16), dz = posu[d * 3 + 2];
                    db  = edge_dist(sxy, sz, dxy, dz, rxy, rz);
                    act = db <= D_MAX_BITS;
                }
            }
            unsigned m = __ballot_sync(0xffffffffu, act);
            while (m) {
                int l = __ffs(m) - 1;
                m &= m - 1;
                int es = __shfl_sync(0xffffffffu, s, l), ed = __shfl_sync(0xffffffffu, d, l);
                uint32_t edb = __shfl_sync(0xffffffffu, db, l), exy = __shfl_sync(0xffffffffu, rxy, l), ez = __shfl_sync(0xffffffffu, rz, l);
                float inv = 1.0f / __uint_as_float(edb << 16);
                float rh[3] = {rbf(bf_lo(exy) * inv), rbf(bf_hi(exy) * inv), rbf(bf_lo(ez) * inv)};
                const uint32_t* fr = Fw + (size_t)es * 128 + lane;
                const uint32_t fh = __ldcg(fr);
                const uint32_t q[3] = {__ldcg(fr + 32), __ldcg(fr + 64), __ldcg(fr + 96)};
                float ps0 = 0.f, ps1 = 0.f, pr0 = 0.f, pr1 = 0.f;
                for (int j2 = 0; j2 < 32; j2++) {
                    uint32_t hj = __shfl_sync(0xffffffffu, fh, j2);
                    uint32_t a0 = *(const uint32_t*)(p.w2 + (2 * j2) * 192 + 2 * lane), a1 = *(const uint32_t*)(p.w2 + (2 * j2 + 1) * 192 + 2 * lane);
                    uint32_t b0 = *(const uint32_t*)(p.w2 + (2 * j2) * 192 + 128 + 2 * lane), b1 = *(const uint32_t*)(p.w2 + (2 * j2 + 1) * 192 + 128 + 2 * lane);
                    ps0 += bf_lo(hj) * bf_lo(a0) + bf_hi(hj) * bf_lo(a1);
                    ps1 += bf_lo(hj) * bf_hi(a0) + bf_hi(hj) * bf_hi(a1);
                    pr0 += bf_lo(hj) * bf_lo(b0) + bf_hi(hj) * bf_lo(b1);
                    pr1 += bf_lo(hj) * bf_hi(b0) + bf_hi(hj) * bf_hi(b1);
                }
                float ws0 = 0.f, ws1 = 0.f, wv0 = 0.f, wv1 = 0.f, wr0 = 0.f, wr1 = 0.f;
                for (int k2 = 0; k2 < 8; k2++) {
                    uint32_t rk2 = __ldcg(tabg + (edb - D_MIN_BITS) * 8 + k2);
#pragma unroll
                    for (int h = 0; h < 2; h++) {
                        float rv = h ? bf_hi(rk2) : bf_lo(rk2);
                        const __nv_bfloat16* wrow = p.wr + (2 * k2 + h) * 192 + 2 * lane;
                        uint32_t a = *(const uint32_t*)wrow, b = *(const uint32_t*)(wrow + 64), c = *(const uint32_t*)(wrow + 128);
                        ws0 += rv * bf_lo(a); ws1 += rv * bf_hi(a);
                        wv0 += rv * bf_lo(b); wv1 += rv * bf_hi(b);
                        wr0 += rv * bf_lo(c); wr1 += rv * bf_hi(c);
                    }
                }
                float* a = acc + (ed - node0) * 256 + 2 * lane;
                atomicAdd(a, ps0 * ws0); atomicAdd(a + 1, ps1 * ws1);
#pragma unroll
                for (int c = 0; c < 3; c++) {
                    atomicAdd(a + 64 * (c + 1), wv0 * bf_lo(q[c]) + pr0 * wr0 * rh[c]);
                    atomicAdd(a + 64 * (c + 1) + 1, wv1 * bf_hi(q[c]) + pr1 * wr1 * rh[c]);
                }
            }
        }
        __syncthreads();
        for (int i = tid; i < nnodes * 128; i += NT) {
            uint32_t r = *(const uint32_t*)(p.sv + (size_t)node0 * 256 + 2 * i);
            *(uint32_t*)(p.out + (size_t)node0 * 256 + 2 * i) = pack_bf(bf_lo(r) + acc[2 * i], bf_hi(r) + acc[2 * i + 1]);
        }
        return;
    }

    const int slots = __reduce_max_sync(0xffffffffu, ctrl[4]);
    const int split = __reduce_max_sync(0xffffffffu, ctrl[2]);
    const int nstage = slots <= SLOT_CAP6 ? 6 : 5;
    const uint32_t ring = sb + (nstage == 6 ? SM_RING6 : SM_RING);
    const int mid = __reduce_max_sync(0xffffffffu, split < nnodes ? (int)(nInfo[split] & 0xffffu) : slots) >> 4;
    const int wgi = warp >> 2, w = warp & 3;
    uint32_t wp[3][4];
    if (wgi < 3) {
        const uint16_t* wr = (const uint16_t*)p.wr + 16 * w + g;
#pragma unroll
        for (int ty = 0; ty < 3; ty++) {
#pragma unroll
            for (int i = 0; i < 4; i++) {
                const uint16_t* q = wr + (8 * (i >> 1) + 2 * t) * 192 + ty * 64 + 8 * (i & 1);
                wp[ty][i] = (uint32_t)__ldg(q) | ((uint32_t)__ldg(q + 192) << 16);
            }
        }
    }
    constexpr uint32_t EMPTY_OFF = NCWG * MAX_STAGE * 8;
    if (wgi == 3) {
        const int sc = w >> 1, r = w & 1;
        const int g0 = (sc == 0 ? 0 : mid) + r, g1 = sc == 0 ? mid : slots >> 4;
        const uint32_t ring_wg = ring + sc * nstage * STAGE_B, full_wg = bar_full + sc * MAX_STAGE * 8;
        const int e = lane >> 1, half = lane & 1;
        const uint32_t coef_off = e * 128 + ((half ^ (e & 7)) << 4);
        const int vrot = (e & 3) ^ ((e >> 1) & 3);
        const uint8_t* tab = (const uint8_t*)g_table + half * 16;
        int stage = r;
        uint32_t phase = 1;
        uint32_t ma = sb + SM_META + (g0 * 16 + e) * 8, ida = sb + SM_SID + g0 * 32;
        uint2 m = make_uint2(0u, 0u);
        uint4 tv = make_uint4(0u, 0u, 0u, 0u), ia = tv, ib = tv;
        if (g0 < g1) {
            m  = lds64(ma);
            ia = lds128(ida);
            ib = lds128(ida + 16);
            tv = __ldg((const uint4*)(tab + (m.x & 0xffffu)));
        }
        for (int left = (g1 - g0 + 1) >> 1; left > 0; left--) {
            const uint32_t st = ring_wg + stage * STAGE_B, fb = full_wg + stage * 8;
            ma += 256; ida += 64;
            uint2 mn = m;
            if (left > 1) mn = lds64(ma);
            mbar_wait(fb + EMPTY_OFF, phase);
            uint32_t leader;
            asm volatile("{\n.reg .pred p;\nelect.sync _|p, 0xffffffff;\nselp.u32 %0, 1, 0, p;\n}" : "=r"(leader));
            if (leader) {
                const uint32_t id2[8] = {ia.x, ia.y, ia.z, ia.w, ib.x, ib.y, ib.z, ib.w};
                const uint32_t rows = st + 2048;
                if ((ib.w >> 16) != 0xffffu) {
                    mbar_expect_tx(fb, 16 * 512);
#pragma unroll
                    for (int i = 0; i < 8; i++) {
                        tma_load(rows + row_line(2 * i) * 128, &tmF, (int)(id2[i] & 0xffffu), fb);
                        tma_load(rows + row_line(2 * i + 1) * 128, &tmF, (int)(id2[i] >> 16), fb);
                    }
                } else {
                    int nv = 0;
#pragma unroll
                    for (int i = 0; i < 8; i++) nv += ((id2[i] & 0xffffu) != 0xffffu) + ((id2[i] >> 16) != 0xffffu);
                    mbar_expect_tx(fb, (uint32_t)nv * 512u);
#pragma unroll
                    for (int q = 0; q < 4; q++) {
                        if (4 * q + 4 <= nv) {
                            tma_load(rows + row_line(4 * q) * 128, &tmF, (int)(id2[2 * q] & 0xffffu), fb);
                            tma_load(rows + row_line(4 * q + 1) * 128, &tmF, (int)(id2[2 * q] >> 16), fb);
                            tma_load(rows + row_line(4 * q + 2) * 128, &tmF, (int)(id2[2 * q + 1] & 0xffffu), fb);
                            tma_load(rows + row_line(4 * q + 3) * 128, &tmF, (int)(id2[2 * q + 1] >> 16), fb);
                        } else {
                            if (4 * q < nv)     tma_load(rows + row_line(4 * q) * 128, &tmF, (int)(id2[2 * q] & 0xffffu), fb);
                            if (4 * q + 1 < nv) tma_load(rows + row_line(4 * q + 1) * 128, &tmF, (int)(id2[2 * q] >> 16), fb);
                            if (4 * q + 2 < nv) tma_load(rows + row_line(4 * q + 2) * 128, &tmF, (int)(id2[2 * q + 1] & 0xffffu), fb);
                        }
                    }
                }
            }
            __syncwarp();
            uint4 o[4];
            {
                const uint32_t mul[4] = {0x3f803f80u, __byte_perm(m.y, 0, 0x1010), __byte_perm(m.y, 0, 0x3232), __byte_perm(m.x, 0, 0x3232)};
#pragma unroll
                for (int j = 0; j < 4; j++) {
                    const int v = j ^ vrot;
                    const uint32_t lo = (v & 1) ? mul[1] : mul[0], hi = (v & 1) ? mul[3] : mul[2];
                    const uint32_t mm = (v & 2) ? hi : lo;
                    o[j] = make_uint4(hmul2(tv.x, mm), hmul2(tv.y, mm), hmul2(tv.z, mm), hmul2(tv.w, mm));
                }
            }
            m = mn;
            if (left > 1) {
                ia = lds128(ida);
                ib = lds128(ida + 16);
                tv = __ldg((const uint4*)(tab + (m.x & 0xffffu)));
            }
            const uint32_t a = st + coef_off;
#pragma unroll
            for (int j = 0; j < 4; j++) sts128(a ^ ((j ^ vrot) << 5), o[j]);
            fence_async_smem();
            __syncwarp();
            mbar_arrive_elected(fb);
            stage += 2;
            if (stage >= nstage) { stage -= nstage; phase ^= 1; }
        }
    } else if (wgi == 2) {
        uint32_t wA[2][4][4];
        {
            const uint16_t* w2 = (const uint16_t*)p.w2 + 16 * w + g;
#pragma unroll
            for (int mk = 0; mk < 8; mk++) {
#pragma unroll
                for (int i = 0; i < 4; i++) {
                    const uint16_t* q = w2 + (16 * (mk & 3) + 2 * t + 8 * (i >> 1)) * 192 + (mk >> 2) * 128 + 8 * (i & 1);
                    wA[mk >> 2][mk & 3][i] = (uint32_t)__ldg(q) | ((uint32_t)__ldg(q + 192) << 16);
                }
            }
        }
        const uint32_t lane_off = (uint32_t)node0 * 512u + t * 128 + w * 32 + (g & 1) * 16 + (g >> 1) * 4;
        uint32_t hcnt[2] = {0u, 0u};
        float zs[8], zv[24], pvv[6], pr[4][2];
        uint32_t hbuf = 0;
        auto start = [&](int ent) {
            const int c = ent >> 7;
            const uint32_t k = c ? hcnt[1] : hcnt[0];
            hbuf = 2 * c + (k & 1);
            mbar_wait(bar_hfull + hbuf * 8, (k >> 1) & 1);
            if (c) hcnt[1]++; else hcnt[0]++;
            const uint32_t dht = desc_lo(sb + SM_HT + hbuf * 8192);
            wg_fence();
            wgmma_n16_first(zs, wA[0][0], dht);
            wgmma_n48_first(zv, wA[1][0], dht + 2);
#pragma unroll
            for (int ks = 1; ks < 4; ks++) {
                wgmma_n16(zs, wA[0][ks], dht + ks * 128);
                wgmma_n48(zv, wA[1][ks], dht + ks * 128 + 2);
            }
            wg_commit();
        };
        auto side = [&](int ent) {
            const uint32_t pa = sb + SM_PV + hbuf * 1536 + (tid & 127) * 4;
            const uint32_t a0 = lds32(pa), a1 = lds32(pa + 512), a2 = lds32(pa + 1024);
            pvv[0] = bf_lo(a0); pvv[1] = bf_hi(a0); pvv[2] = bf_lo(a1); pvv[3] = bf_hi(a1); pvv[4] = bf_lo(a2); pvv[5] = bf_hi(a2);
            __syncwarp();
            mbar_arrive_elected(bar_hempty + hbuf * 8);
        };
        auto weigh = [&]() {
#pragma unroll
            for (int i = 0; i < 12; i++) asm volatile("" : "+r"(wp[i >> 2][i & 3]));
            pr[0][0] = bf_lo(wp[0][0]) * zs[0] + bf_hi(wp[0][0]) * zs[1] + bf_lo(wp[0][2]) * zs[4] + bf_hi(wp[0][2]) * zs[5];
            pr[0][1] = bf_lo(wp[0][1]) * zs[2] + bf_hi(wp[0][1]) * zs[3] + bf_lo(wp[0][3]) * zs[6] + bf_hi(wp[0][3]) * zs[7];
#pragma unroll
            for (int a = 0; a < 3; a++) {
                const float* y = zv + 8 * a;
                pr[a + 1][0] = pvv[2 * a] + bf_lo(wp[2][0]) * y[0] + bf_hi(wp[2][0]) * y[1] + bf_lo(wp[2][2]) * y[4] + bf_hi(wp[2][2]) * y[5];
                pr[a + 1][1] = pvv[2 * a + 1] + bf_lo(wp[2][1]) * y[2] + bf_hi(wp[2][1]) * y[3] + bf_lo(wp[2][3]) * y[6] + bf_hi(wp[2][3]) * y[7];
            }
            asm volatile("" : "+f"(pr[0][0]), "+f"(pr[0][1]), "+f"(pr[1][0]), "+f"(pr[1][1]), "+f"(pr[2][0]), "+f"(pr[2][1]), "+f"(pr[3][0]), "+f"(pr[3][1]) :: "memory");
        };
        auto finish = [&](int ent, uint32_t resid) {
            const bool hi2 = t & 2, hi1 = t & 1, odd = g & 1;
            float ka0 = hi2 ? pr[2][0] : pr[0][0], ka1 = hi2 ? pr[2][1] : pr[0][1];
            float kb0 = hi2 ? pr[3][0] : pr[1][0], kb1 = hi2 ? pr[3][1] : pr[1][1];
            float sa0 = hi2 ? pr[0][0] : pr[2][0], sa1 = hi2 ? pr[0][1] : pr[2][1];
            float sb0 = hi2 ? pr[1][0] : pr[3][0], sb1 = hi2 ? pr[1][1] : pr[3][1];
            ka0 += __shfl_xor_sync(0xffffffffu, sa0, 2); ka1 += __shfl_xor_sync(0xffffffffu, sa1, 2);
            kb0 += __shfl_xor_sync(0xffffffffu, sb0, 2); kb1 += __shfl_xor_sync(0xffffffffu, sb1, 2);
            float k0 = hi1 ? kb0 : ka0, k1 = hi1 ? kb1 : ka1;
            float s0 = hi1 ? ka0 : kb0, s1 = hi1 ? ka1 : kb1;
            k0 += __shfl_xor_sync(0xffffffffu, s0, 1);
            k1 += __shfl_xor_sync(0xffffffffu, s1, 1);
            const float other = __shfl_xor_sync(0xffffffffu, odd ? k0 : k1, 4);
            const float lo = odd ? other : k0, hi = odd ? k1 : other;
            *(uint32_t*)((uint8_t*)p.out + (lane_off + (uint32_t)(ent & 127) * 512u)) = pack_bf(bf_lo(resid) + lo, bf_hi(resid) + hi);
        };
        auto entry = [&](int i) -> int { return __reduce_max_sync(0xffffffffu, (int)smem[SM_ORDER + i]); };
        auto load_resid = [&](int ent) -> uint32_t { return __ldg((const uint32_t*)((const uint8_t*)p.sv + (lane_off + (uint32_t)(ent & 127) * 512u))); };
        if (nnodes > 0) {
            int cur = entry(0), nxt = entry(1);
            uint32_t resid = load_resid(cur);
            start(cur);
#pragma unroll 1
            for (int i = 1; i < nnodes; i++) {
                wg_wait0();
                side(cur);
                weigh();
                start(nxt);
                finish(cur, resid);
                cur = nxt;
                resid = load_resid(cur);
                nxt = entry(i + 1);
            }
            wg_wait0();
            side(cur);
            weigh();
            finish(cur, resid);
        }
    } else {
        const int wg = wgi;
        uint32_t aoff[4];
        {
            const int e = (lane & 7) + 8 * (lane >> 4), ch = 2 * w + ((lane >> 3) & 1);
#pragma unroll
            for (int b = 0; b < 4; b++) aoff[b] = 2048 + (row_line(e) + b) * 128 + ((ch ^ ((row_line(e) + b) & 7)) << 4);
        }
        const uint32_t stsm_0 = sb + SM_HT + wg * 16384 + (16 * w + (lane & 15)) * 128 + (((lane >> 4) ^ (lane & 7)) << 4);
        const uint32_t pv_0 = sb + SM_PV + wg * 3072 + (tid & 127) * 4;
        uint32_t hk = 0;
        const uint32_t ring_wg = ring + wg * nstage * STAGE_B;
        const uint32_t full_wg = bar_full + wg * MAX_STAGE * 8;

        float ys[8], yv[24], dQ[3][8];
        uint32_t A0[4][4], A1[4][4];
#pragma unroll
        for (int i = 0; i < 24; i++) yv[i] = 0.f;
#pragma unroll
        for (int i = 0; i < 8; i++) { ys[i] = 0.f; dQ[0][i] = 0.f; dQ[1][i] = 0.f; dQ[2][i] = 0.f; }
        int left = wg == 0 ? mid : (slots >> 4) - mid;
        int fstage = 0;
        uint32_t fphase = 0, fst = ring_wg, fbar = full_wg;
        uint32_t ninfo_a = sb + SM_NINFO + (wg == 0 ? 0 : split) * 4;
        int gi = 0, G = __reduce_max_sync(0xffffffffu, (int)(lds32(ninfo_a) >> 20));

        uint32_t ready = 0;
        auto fetch = [&](uint32_t (&A)[4][4], uint32_t& bd, uint32_t& eb) {
            if (!ready) mbar_wait(fbar, fphase);
            const uint32_t st = fst;
            bd = desc_lo(st);
            eb = fbar + EMPTY_OFF;
            fst += STAGE_B; fbar += 8;
            if (++fstage == nstage) { fstage = 0; fphase ^= 1; fst = ring_wg; fbar = full_wg; }
            ready = __all_sync(0xffffffffu, ldsm4t_x4_probe(A, st + aoff[0], st + aoff[1], st + aoff[2], st + aoff[3], fbar, fphase));
        };
        uint32_t notify = 0;
        auto signal = [&]() {
            fence_async_smem();
            __syncwarp();
            mbar_arrive_elected(notify);
            notify = 0;
        };
        auto step = [&](uint32_t (&Ac)[4][4], uint32_t bdc, uint32_t ebc, uint32_t (&An)[4][4], uint32_t& bdn, uint32_t& ebn) {
            wg_fence();
            wgmma_n64_p(ys, yv, Ac[0], bdc, gi);
            wgmma_n16_p(dQ[0], Ac[1], bdc, gi);
            wgmma_n16_p(dQ[1], Ac[2], bdc, gi);
            wgmma_n16_p(dQ[2], Ac[3], bdc, gi);
            wg_commit();
            if (--left > 0) fetch(An, bdn, ebn);
            if (notify) signal();
            const bool last = ++gi == G;
            uint32_t info_next = 0;
            if (last) { ninfo_a += 4; info_next = lds32(ninfo_a); }
            wg_wait0();
            mbar_arrive_elected(ebc);
            if (last) {
                const uint32_t hb = hk & 1;
                mbar_wait(bar_hempty + (2 * wg + hb) * 8, ((hk >> 1) & 1) ^ 1);
                hk++;
                const uint32_t stsm_a = stsm_0 + hb * 8192, pv_a = pv_0 + hb * 1536;
                stsm4(stsm_a, pack_bf(ys[0], ys[1]), pack_bf(ys[2], ys[3]), pack_bf(ys[4], ys[5]), pack_bf(ys[6], ys[7]));
#pragma unroll
                for (int i = 0; i < 6; i += 2) {
                    stsm4(stsm_a ^ ((i + 2) << 4),
                          pack_bf(yv[4 * i], yv[4 * i + 1]), pack_bf(yv[4 * i + 2], yv[4 * i + 3]),
                          pack_bf(yv[4 * i + 4], yv[4 * i + 5]), pack_bf(yv[4 * i + 6], yv[4 * i + 7]));
                }
#pragma unroll
                for (int i = 0; i < 4; i++) asm volatile("" : "+r"(wp[1][i]));
#pragma unroll
                for (int a = 0; a < 3; a++) {
                    const float* q = dQ[a];
                    const float p0 = bf_lo(wp[1][0]) * q[0] + bf_hi(wp[1][0]) * q[1] + bf_lo(wp[1][2]) * q[4] + bf_hi(wp[1][2]) * q[5];
                    const float p1 = bf_lo(wp[1][1]) * q[2] + bf_hi(wp[1][1]) * q[3] + bf_lo(wp[1][3]) * q[6] + bf_hi(wp[1][3]) * q[7];
                    sts32(pv_a + a * 512, pack_bf(p0, p1));
                }
                notify = bar_hfull + (2 * wg + hb) * 8;
                G = __reduce_max_sync(0xffffffffu, (int)(info_next >> 20));
                gi = 0;
            }
        };
        if (left > 0) {
            uint32_t bd0, eb0, bd1 = 0, eb1 = 0;
            fetch(A0, bd0, eb0);
            while (true) {
                step(A0, bd0, eb0, A1, bd1, eb1);
                if (left <= 0) break;
                step(A1, bd1, eb1, A0, bd0, eb0);
                if (left <= 0) break;
            }
            if (notify) signal();
        }
    }
    STAMP(8);
}

typedef CUresult (*EncodeFn)(CUtensorMap*, CUtensorMapDataType, cuuint32_t, void*, const cuuint64_t*, const cuuint64_t*,
                             const cuuint32_t*, const cuuint32_t*, CUtensorMapInterleave, CUtensorMapSwizzle,
                             CUtensorMapL2promotion, CUtensorMapFloatOOBfill);

void make_map(EncodeFn enc, CUtensorMap* tm, const void* base, uint64_t lines, uint32_t box) {
    cuuint64_t gd[2] = {64, lines};
    cuuint64_t gs[1] = {128};
    cuuint32_t bd[2] = {64, box};
    cuuint32_t es[2] = {1, 1};
    enc(tm, CU_TENSOR_MAP_DATA_TYPE_BFLOAT16, 2, const_cast<void*>(base), gd, gs, bd, es, CU_TENSOR_MAP_INTERLEAVE_NONE,
        CU_TENSOR_MAP_SWIZZLE_128B, CU_TENSOR_MAP_L2_PROMOTION_L2_128B, CU_TENSOR_MAP_FLOAT_OOB_FILL_NONE);
}

void make_map3(EncodeFn enc, CUtensorMap* tm, const void* base, uint64_t nodes, uint32_t box) {
    cuuint64_t gd[3] = {64, 4, nodes};
    cuuint64_t gs[2] = {128, 512};
    cuuint32_t bd[3] = {64, 1, box};
    cuuint32_t es[3] = {1, 1, 1};
    enc(tm, CU_TENSOR_MAP_DATA_TYPE_BFLOAT16, 3, const_cast<void*>(base), gd, gs, bd, es, CU_TENSOR_MAP_INTERLEAVE_NONE,
        CU_TENSOR_MAP_SWIZZLE_128B, CU_TENSOR_MAP_L2_PROMOTION_L2_128B, CU_TENSOR_MAP_FLOAT_OOB_FILL_NONE);
}

}

extern "C" void kernel_launch(void* const* d_in, const int* in_sizes, int n_in, void* d_out, int out_size) {
    (void)n_in; (void)out_size;
    static int n_sm = 0;
    static EncodeFn enc = nullptr;
    static void* f_ptr = nullptr;
    if (n_sm == 0) {
        int dev = 0;
        cudaGetDevice(&dev);
        cudaDeviceGetAttribute(&n_sm, cudaDevAttrMultiProcessorCount, dev);
        cudaFuncSetAttribute(painn_kernel, cudaFuncAttributeMaxDynamicSharedMemorySize, SM_TOTAL);
        void* fn = nullptr;
        cudaDriverEntryPointQueryResult qr;
        cudaGetDriverEntryPoint("cuTensorMapEncodeTiled", &fn, cudaEnableDefault, &qr);
        enc = (EncodeFn)fn;
        cudaGetSymbolAddress(&f_ptr, g_F);
    }
    Params p;
    p.sv    = (const __nv_bfloat16*)d_in[0];
    p.pos   = (const __nv_bfloat16*)d_in[1];
    p.src   = (const int*)d_in[2];
    p.dst   = (const int*)d_in[3];
    p.freqs = (const __nv_bfloat16*)d_in[4];
    p.w1    = (const __nv_bfloat16*)d_in[5];
    p.w2    = (const __nv_bfloat16*)d_in[6];
    p.wr    = (const __nv_bfloat16*)d_in[7];
    p.out   = (__nv_bfloat16*)d_out;
    p.N = in_sizes[1] / 3;
    p.E = in_sizes[2];
    p.ncta = n_sm < MAX_CTA ? n_sm : MAX_CTA;
    p.npc = ((p.N + p.ncta - 1) / p.ncta + 3) & ~3;
    p.npc_magic = (uint32_t)(0x100000000ull / (uint32_t)p.npc) + 1u;
    p.quads_per_cta = ((p.E >> 2) + p.ncta - 1) / p.ncta;
    if (!enc || p.N > MAX_N || p.npc > MAX_NPC || (p.E & 3) || p.quads_per_cta > MAX_ROUNDS * 32) return;

    CUtensorMap tmF, tmFs;
    make_map(enc, &tmF, f_ptr, (uint64_t)p.N * 4, 4);
    make_map3(enc, &tmFs, f_ptr, (uint64_t)p.N, 4);

    cudaLaunchConfig_t cfg = {};
    cfg.gridDim = dim3(p.ncta);
    cfg.blockDim = dim3(NT);
    cfg.dynamicSmemBytes = SM_TOTAL;
    cfg.stream = cudaStreamPerThread;
    cudaLaunchAttribute attr[1];
    attr[0].id = cudaLaunchAttributeCooperative;
        attr[0].val.cooperative = 1;
    cfg.attrs = attr;
    cfg.numAttrs = 1;
    cudaLaunchKernelEx(&cfg, painn_kernel, p, tmF, tmFs);
}
```

```cpp
#include <cuda_runtime.h>
#include <cuda.h>
#include <cuda_bf16.h>
#include <stdint.h>

namespace {

constexpr int NT        = 512;
constexpr int NCWG      = 2;
constexpr int MAX_N     = 10240;
constexpr int MAX_CTA   = 136;
constexpr int MAX_NPC   = 80;
constexpr int MAX_ROUNDS = 38;
constexpr int SEG_CAP   = 64;
constexpr int SLOT_CAP  = 6144;
constexpr int MAX_STAGE = 5;
constexpr int STAGE_B   = 12288;

constexpr uint32_t D_MIN_BITS = 0x38D2;
constexpr uint32_t D_MAX_BITS = 0x409C;
constexpr int TAB_ROWS  = (int)(D_MAX_BITS - D_MIN_BITS) + 1;
constexpr int TAB_ZERO  = TAB_ROWS;
constexpr int TAB_BYTES = (TAB_ROWS + 1) * 32;

constexpr int SM_BINCNT = 0;
constexpr int SM_NCNT   = SM_BINCNT + MAX_CTA * 4;
constexpr int SM_NINFO  = SM_NCNT + MAX_NPC * 4;
constexpr int SM_ORDER  = SM_NINFO + (MAX_NPC + 1) * 4;
constexpr int SM_CTRL   = SM_ORDER + MAX_NPC + 12;
constexpr int SM_BARS   = SM_CTRL + 64;
constexpr int SM_SID    = 2048 + 256;
constexpr int SM_META   = SM_SID + SLOT_CAP * 2;
constexpr int SM_TOTAL  = 232448;
constexpr int SM_HT     = (SM_TOTAL - 4 * 8192 - 4 * 1536) / 1024 * 1024;
constexpr int SM_PV     = SM_HT + 4 * 8192;
constexpr int SM_RING   = SM_HT - NCWG * MAX_STAGE * STAGE_B;
constexpr int P1_POS    = 3072;
constexpr int P1_SEGA   = P1_POS + 61440;
constexpr int P1_SEGB   = P1_SEGA + MAX_CTA * SEG_CAP * 8;
constexpr int P1_SV     = P1_SEGB + MAX_CTA * SEG_CAP * 4;
constexpr int P1_W1     = P1_SV + 4 * MAX_NPC * 128;
constexpr int P1_W2     = P1_W1 + 8192;
constexpr int P1_END    = P1_W2 + 8192;
constexpr int P1_REC    = P1_SEGA;
constexpr int STAGE_CAP = (P1_SV - P1_REC) / 16;
static_assert(SM_BARS + (12 + 2 * NCWG * MAX_STAGE) * 8 <= SM_SID, "misc block");
static_assert(SM_BARS + 256 <= P1_POS, "misc block");
static_assert(P1_END <= SM_TOTAL && P1_SV % 1024 == 0 && P1_REC % 16 == 0, "phase 1 overlay");
static_assert(SM_META + SLOT_CAP * 8 <= SM_RING && SM_PV + 4 * 1536 <= SM_TOTAL, "CSR");
static_assert(SM_RING % 1024 == 0 && SM_HT % 1024 == 0, "alignment");
static_assert(SM_BARS % 8 == 0 && SM_META % 8 == 0 && SM_CTRL % 4 == 0, "alignment");
static_assert(MAX_N * 6 <= 61440, "pos");
static_assert(SM_RING >= P1_SEGA && SM_HT <= P1_END, "every byte of the stages is written (finite) during phase 1");
static_assert(SM_SID + MAX_NPC * 1024 <= SM_TOTAL, "slow path accumulators");

__device__ __align__(1024) uint4 g_F[MAX_N * 32];
__device__ __align__(128) uint32_t g_seg[MAX_CTA * MAX_CTA * SEG_CAP * 3];
__device__ uint4    g_table[(TAB_BYTES + 15) / 16];
__device__ unsigned g_bar[2];
#define STAMP(k)
#define STAMPT(k, T)

struct Params {
    const __nv_bfloat16* sv;
    const __nv_bfloat16* pos;
    const int*           src;
    const int*           dst;
    const __nv_bfloat16* freqs;
    const __nv_bfloat16* w1;
    const __nv_bfloat16* w2;
    const __nv_bfloat16* wr;
    __nv_bfloat16*       out;
    int N, E, ncta, npc;
    uint32_t npc_magic;
    int quads_per_cta;
};

__device__ __forceinline__ uint32_t smem_u32(const void* p) { return (uint32_t)__cvta_generic_to_shared(p); }
__device__ __forceinline__ float bf_lo(uint32_t v) { return __uint_as_float(v << 16); }
__device__ __forceinline__ float bf_hi(uint32_t v) { return __uint_as_float(v & 0xffff0000u); }
__device__ __forceinline__ uint32_t pack_bf(float lo, float hi) {
    uint32_t r;
    asm("cvt.rn.bf16x2.f32 %0, %1, %2;" : "=r"(r) : "f"(hi), "f"(lo));
    return r;
}
__device__ __forceinline__ float rbf(float x) { return bf_lo(pack_bf(x, 0.f)); }
__device__ __forceinline__ uint32_t hmul2(uint32_t a, uint32_t b) {
    uint32_t r;
    asm("mul.rn.bf16x2 %0, %1, %2;" : "=r"(r) : "r"(a), "r"(b));
    return r;
}
__device__ __forceinline__ uint32_t hsub2(uint32_t a, uint32_t b) {
    uint32_t r;
    asm("sub.rn.bf16x2 %0, %1, %2;" : "=r"(r) : "r"(a), "r"(b));
    return r;
}
__device__ __forceinline__ uint32_t lds32(uint32_t a) { uint32_t v; asm volatile("ld.shared.u32 %0, [%1];" : "=r"(v) : "r"(a)); return v; }
__device__ __forceinline__ uint2 lds64(uint32_t a) { uint2 v; asm volatile("ld.shared.v2.u32 {%0,%1}, [%2];" : "=r"(v.x), "=r"(v.y) : "r"(a)); return v; }
__device__ __forceinline__ uint4 lds128(uint32_t a) { uint4 v; asm volatile("ld.shared.v4.u32 {%0,%1,%2,%3}, [%4];" : "=r"(v.x), "=r"(v.y), "=r"(v.z), "=r"(v.w) : "r"(a)); return v; }
__device__ __forceinline__ void sts32(uint32_t a, uint32_t v) { asm volatile("st.shared.u32 [%0], %1;" ::"r"(a), "r"(v) : "memory"); }
__device__ __forceinline__ void sts128(uint32_t a, uint4 v) { asm volatile("st.shared.v4.u32 [%0], {%1,%2,%3,%4};" ::"r"(a), "r"(v.x), "r"(v.y), "r"(v.z), "r"(v.w) : "memory"); }
__device__ __forceinline__ void mbar_init(uint32_t bar, int cnt) { asm volatile("mbarrier.init.shared::cta.b64 [%0], %1;" ::"r"(bar), "r"(cnt) : "memory"); }
__device__ __forceinline__ void mbar_expect_tx(uint32_t bar, uint32_t bytes) { asm volatile("mbarrier.arrive.expect_tx.shared::cta.b64 _, [%0], %1;" ::"r"(bar), "r"(bytes) : "memory"); }
__device__ __forceinline__ void mbar_wait(uint32_t bar, uint32_t parity) {
    asm volatile("{\n.reg .pred p;\n.reg .u32 c;\n"
                 "mbarrier.try_wait.parity.shared::cta.b64 p, [%0], %1;\n"
                 "@p bra DONE_%=;\n"
                 "mov.u32 c, 0;\n"
                 "LOOP_%=:\n"
                 "mbarrier.try_wait.parity.shared::cta.b64 p, [%0], %1;\n"
                 "@p bra DONE_%=;\n"
                 "add.u32 c, c, 1;\n"
                 "setp.lt.u32 p, c, 4194304;\n"
                 "@p bra LOOP_%=;\n"
                 "DONE_%=:\n}"
                 ::"r"(bar), "r"(parity) : "memory");
}
__device__ __forceinline__ void mbar_arrive_elected(uint32_t bar) {
    asm volatile("{\n.reg .pred p;\nelect.sync _|p, 0xffffffff;\n@p mbarrier.arrive.shared::cta.b64 _, [%0];\n}" ::"r"(bar) : "memory");
}
__device__ __forceinline__ void bulk_g2s(uint32_t dst, const void* src, uint32_t bytes, uint32_t bar) {
    asm volatile("cp.async.bulk.shared::cluster.global.mbarrier::complete_tx::bytes [%0], [%1], %2, [%3];"
                 ::"r"(dst), "l"(src), "r"(bytes), "r"(bar) : "memory");
}
__device__ __forceinline__ void cp_async16(uint32_t dst, const void* src) {
    asm volatile("cp.async.cg.shared.global [%0], [%1], 16;" ::"r"(dst), "l"(src) : "memory");
}
__device__ __forceinline__ void tma_load(uint32_t dst, const CUtensorMap* tm, int line, uint32_t bar) {
    asm volatile("cp.async.bulk.tensor.2d.shared::cluster.global.mbarrier::complete_tx::bytes [%0], [%1, {%3, %4}], [%2];"
                 ::"r"(dst), "l"(tm), "r"(bar), "r"(0), "r"(line) : "memory");
}
__device__ __forceinline__ void tma_store3(const CUtensorMap* tm, int comp, int node, uint32_t src) {
    asm volatile("cp.async.bulk.tensor.3d.global.shared::cta.bulk_group [%0, {%2, %3, %4}], [%1];"
                 ::"l"(tm), "r"(src), "r"(0), "r"(comp), "r"(node) : "memory");
}
__device__ __forceinline__ void fence_async_smem() { asm volatile("fence.proxy.async.shared::cta;" ::: "memory"); }
__device__ __forceinline__ void ldsm4(uint32_t (&r)[4], uint32_t a) {
    asm volatile("ldmatrix.sync.aligned.m8n8.x4.shared.b16 {%0,%1,%2,%3}, [%4];" : "=r"(r[0]), "=r"(r[1]), "=r"(r[2]), "=r"(r[3]) : "r"(a) : "memory");
}
__device__ __forceinline__ void ldsm4t(uint32_t (&r)[4], uint32_t a) {
    asm volatile("ldmatrix.sync.aligned.m8n8.x4.trans.shared.b16 {%0,%1,%2,%3}, [%4];" : "=r"(r[0]), "=r"(r[1]), "=r"(r[2]), "=r"(r[3]) : "r"(a) : "memory");
}
__device__ __forceinline__ void stsm4(uint32_t a, uint32_t r0, uint32_t r1, uint32_t r2, uint32_t r3) {
    asm volatile("stmatrix.sync.aligned.m8n8.x4.shared.b16 [%0], {%1,%2,%3,%4};" ::"r"(a), "r"(r0), "r"(r1), "r"(r2), "r"(r3) : "memory");
}
__device__ __forceinline__ void mma16816(float (&c)[4], const uint32_t (&a)[4], uint32_t b0, uint32_t b1) {
    asm volatile("mma.sync.aligned.m16n8k16.row.col.f32.bf16.bf16.f32 {%0,%1,%2,%3}, {%4,%5,%6,%7}, {%8,%9}, {%0,%1,%2,%3};"
                 : "+f"(c[0]), "+f"(c[1]), "+f"(c[2]), "+f"(c[3])
                 : "r"(a[0]), "r"(a[1]), "r"(a[2]), "r"(a[3]), "r"(b0), "r"(b1));
}

__device__ __forceinline__ uint32_t desc_lo(uint32_t saddr) { return ((saddr & 0x3FFFF) >> 4) | (1u << 16); }
#define DESC_HI "0x40000040"
__device__ __forceinline__ void wg_fence() { asm volatile("wgmma.fence.sync.aligned;" ::: "memory"); }
__device__ __forceinline__ void wg_commit() { asm volatile("wgmma.commit_group.sync.aligned;" ::: "memory"); }
__device__ __forceinline__ void wg_wait0() { asm volatile("wgmma.wait_group.sync.aligned 0;" ::: "memory"); }

__device__ __forceinline__ void wgmma_n48_first(float (&e)[24], const uint32_t (&a)[4], uint32_t bdesc) {
    asm volatile("{\n.reg .b64 b;\nmov.b64 b, {%28, " DESC_HI "};\n"
                 "wgmma.mma_async.sync.aligned.m64n48k16.f32.bf16.bf16 {%0,%1,%2,%3,%4,%5,%6,%7,%8,%9,%10,%11,%12,%13,%14,%15,%16,%17,%18,%19,%20,%21,%22,%23}, {%24,%25,%26,%27}, b, 0, 1, 1, 1;\n}"
                 : "=f"(e[0]), "=f"(e[1]), "=f"(e[2]), "=f"(e[3]), "=f"(e[4]), "=f"(e[5]), "=f"(e[6]), "=f"(e[7]), "=f"(e[8]), "=f"(e[9]), "=f"(e[10]), "=f"(e[11]), "=f"(e[12]), "=f"(e[13]), "=f"(e[14]), "=f"(e[15]), "=f"(e[16]), "=f"(e[17]), "=f"(e[18]), "=f"(e[19]), "=f"(e[20]), "=f"(e[21]), "=f"(e[22]), "=f"(e[23])
                 : "r"(a[0]), "r"(a[1]), "r"(a[2]), "r"(a[3]), "r"(bdesc));
}
__device__ __forceinline__ void wgmma_n48(float (&e)[24], const uint32_t (&a)[4], uint32_t bdesc) {
    asm volatile("{\n.reg .b64 b;\nmov.b64 b, {%28, " DESC_HI "};\n"
                 "wgmma.mma_async.sync.aligned.m64n48k16.f32.bf16.bf16 {%0,%1,%2,%3,%4,%5,%6,%7,%8,%9,%10,%11,%12,%13,%14,%15,%16,%17,%18,%19,%20,%21,%22,%23}, {%24,%25,%26,%27}, b, 1, 1, 1, 1;\n}"
                 : "+f"(e[0]), "+f"(e[1]), "+f"(e[2]), "+f"(e[3]), "+f"(e[4]), "+f"(e[5]), "+f"(e[6]), "+f"(e[7]), "+f"(e[8]), "+f"(e[9]), "+f"(e[10]), "+f"(e[11]), "+f"(e[12]), "+f"(e[13]), "+f"(e[14]), "+f"(e[15]), "+f"(e[16]), "+f"(e[17]), "+f"(e[18]), "+f"(e[19]), "+f"(e[20]), "+f"(e[21]), "+f"(e[22]), "+f"(e[23])
                 : "r"(a[0]), "r"(a[1]), "r"(a[2]), "r"(a[3]), "r"(bdesc));
}
__device__ __forceinline__ void wgmma_n16_first(float (&d)[8], const uint32_t (&a)[4], uint32_t bdesc) {
    asm volatile("{\n.reg .b64 b;\nmov.b64 b, {%12, " DESC_HI "};\n"
                 "wgmma.mma_async.sync.aligned.m64n16k16.f32.bf16.bf16 {%0,%1,%2,%3,%4,%5,%6,%7}, {%8,%9,%10,%11}, b, 0, 1, 1, 1;\n}"
                 : "=f"(d[0]), "=f"(d[1]), "=f"(d[2]), "=f"(d[3]), "=f"(d[4]), "=f"(d[5]), "=f"(d[6]), "=f"(d[7])
                 : "r"(a[0]), "r"(a[1]), "r"(a[2]), "r"(a[3]), "r"(bdesc));
}
__device__ __forceinline__ void wgmma_n16(float (&d)[8], const uint32_t (&a)[4], uint32_t bdesc) {
    asm volatile("{\n.reg .b64 b;\nmov.b64 b, {%12, " DESC_HI "};\n"
                 "wgmma.mma_async.sync.aligned.m64n16k16.f32.bf16.bf16 {%0,%1,%2,%3,%4,%5,%6,%7}, {%8,%9,%10,%11}, b, 1, 1, 1, 1;\n}"
                 : "+f"(d[0]), "+f"(d[1]), "+f"(d[2]), "+f"(d[3]), "+f"(d[4]), "+f"(d[5]), "+f"(d[6]), "+f"(d[7])
                 : "r"(a[0]), "r"(a[1]), "r"(a[2]), "r"(a[3]), "r"(bdesc));
}

__device__ __forceinline__ void wgmma_n64_p(float (&d)[8], float (&e)[24], const uint32_t (&a)[4], uint32_t bdesc, int acc) {
    asm volatile("{\n.reg .pred p;\n.reg .b64 b;\nsetp.ne.b32 p, %37, 0;\nmov.b64 b, {%36, " DESC_HI "};\n"
                 "wgmma.mma_async.sync.aligned.m64n64k16.f32.bf16.bf16 {%0,%1,%2,%3,%4,%5,%6,%7,%8,%9,%10,%11,%12,%13,%14,%15,%16,%17,%18,%19,%20,%21,%22,%23,%24,%25,%26,%27,%28,%29,%30,%31}, {%32,%33,%34,%35}, b, p, 1, 1, 1;\n}"
                 : "+f"(d[0]), "+f"(d[1]), "+f"(d[2]), "+f"(d[3]), "+f"(d[4]), "+f"(d[5]), "+f"(d[6]), "+f"(d[7]),
                   "+f"(e[0]), "+f"(e[1]), "+f"(e[2]), "+f"(e[3]), "+f"(e[4]), "+f"(e[5]), "+f"(e[6]), "+f"(e[7]), "+f"(e[8]), "+f"(e[9]), "+f"(e[10]), "+f"(e[11]), "+f"(e[12]), "+f"(e[13]), "+f"(e[14]), "+f"(e[15]), "+f"(e[16]), "+f"(e[17]), "+f"(e[18]), "+f"(e[19]), "+f"(e[20]), "+f"(e[21]), "+f"(e[22]), "+f"(e[23])
                 : "r"(a[0]), "r"(a[1]), "r"(a[2]), "r"(a[3]), "r"(bdesc), "r"(acc));
}
__device__ __forceinline__ void wgmma_n16_p(float (&d)[8], const uint32_t (&a)[4], uint32_t bdesc, int acc) {
    asm volatile("{\n.reg .pred p;\n.reg .b64 b;\nsetp.ne.b32 p, %13, 0;\nmov.b64 b, {%12, " DESC_HI "};\n"
                 "wgmma.mma_async.sync.aligned.m64n16k16.f32.bf16.bf16 {%0,%1,%2,%3,%4,%5,%6,%7}, {%8,%9,%10,%11}, b, p, 1, 1, 1;\n}"
                 : "+f"(d[0]), "+f"(d[1]), "+f"(d[2]), "+f"(d[3]), "+f"(d[4]), "+f"(d[5]), "+f"(d[6]), "+f"(d[7])
                 : "r"(a[0]), "r"(a[1]), "r"(a[2]), "r"(a[3]), "r"(bdesc), "r"(acc));
}

__device__ __forceinline__ uint32_t edge_dist(uint32_t sxy, uint32_t sz, uint32_t dxy, uint32_t dz, uint32_t& rxy, uint32_t& rz) {
    rxy = hsub2(sxy, dxy);
    rz  = hsub2(sz, dz);
    uint32_t qxy = hmul2(rxy, rxy), qz = hmul2(rz, rz);
    float ss = rbf((bf_lo(qxy) + bf_hi(qxy)) + bf_lo(qz));
    float s2 = rbf(ss + 1e-8f);
    float d;
    asm("sqrt.approx.ftz.f32 %0, %1;" : "=f"(d) : "f"(s2));
    return pack_bf(d, 0.f) & 0xffffu;
}

__device__ __noinline__ float radial_value(float d, float f) {
    float arg = rbf(d * f);
    float sn  = rbf(sinf(arg));
    float rb  = rbf(__fdiv_rn(sn, d));
    float c   = rbf(cosf(rbf(__fdiv_rn(rbf(d * 3.14159265358979323846f), 5.0f))));
    float fc  = rbf(0.5f * rbf(c + 1.0f));
    return rb * fc;
}

__global__ void __launch_bounds__(NT, 1)
painn_kernel(const Params p, const __grid_constant__ CUtensorMap tmF, const __grid_constant__ CUtensorMap tmFs) {
    extern __shared__ __align__(1024) uint8_t smem[];
    const uint32_t sb   = smem_u32(smem);
    const int tid  = threadIdx.x, lane = tid & 31, warp = __shfl_sync(0xffffffffu, tid >> 5, 0);
    const int cta  = blockIdx.x;
    const int g    = lane >> 2, t = lane & 3;
    int* binCnt = (int*)(smem + SM_BINCNT);
    int* nCnt   = (int*)(smem + SM_NCNT);
    uint32_t* nInfo = (uint32_t*)(smem + SM_NINFO);
    volatile int* ctrl = (volatile int*)(smem + SM_CTRL);
    const uint32_t bar_pos = sb + SM_BARS;
    const uint32_t bar_full = bar_pos + 32, bar_empty = bar_full + NCWG * MAX_STAGE * 8;
    const uint32_t bar_hfull = bar_empty + NCWG * MAX_STAGE * 8, bar_hempty = bar_hfull + 32;

    const int node0  = cta * p.npc;
    const int nnodes = max(0, min(p.npc, p.N - node0));

    STAMP(0);
    if (tid == 32) {
        mbar_init(bar_pos, 1);
        asm volatile("fence.mbarrier_init.release.cluster;" ::: "memory");
        uint32_t pos_bytes = (uint32_t)(p.N * 6 + 15) & ~15u;
        mbar_expect_tx(bar_pos, pos_bytes);
        bulk_g2s(sb + P1_POS, p.pos, pos_bytes, bar_pos);
    } else if (tid == 64) {
        for (int i = 0; i < 4; i++) { mbar_init(bar_hfull + 8 * i, 4); mbar_init(bar_hempty + 8 * i, 4); }
        asm volatile("prefetch.tensormap [%0];" ::"l"(&tmF) : "memory");
        asm volatile("prefetch.tensormap [%0];" ::"l"(&tmFs) : "memory");
    } else if (tid >= 96 && tid < 96 + NCWG * MAX_STAGE) {
        mbar_init(bar_full + 8 * (tid - 96), 2);
        mbar_init(bar_empty + 8 * (tid - 96), 4);
    }
    unsigned bar_seen = 0;
    if (tid == 0 || tid == 32) asm volatile("ld.relaxed.gpu.global.u32 %0, [%1];" : "=r"(bar_seen) : "l"(&g_bar[tid >> 5]) : "memory");
    const bool mlp_warp = warp >= 6;
    int4 s4[3], d4[3];
    const int q0 = cta * p.quads_per_cta;
    const int qend = min(q0 + p.quads_per_cta, p.E >> 2);
#pragma unroll
    for (int k = 0; k < 3; k++) {
        const int q = q0 + (k < 2 ? warp + 16 * k : 32 + warp) * 32 + lane;
        const bool ok = q < qend && (k < 2 || !mlp_warp);
        s4[k] = ok ? __ldg((const int4*)p.src + q) : make_int4(-1, -1, -1, -1);
        d4[k] = ok ? __ldg((const int4*)p.dst + q) : make_int4(0, 0, 0, 0);
    }
    if (tid < MAX_CTA) binCnt[tid] = 0;
    if (tid < MAX_NPC) nCnt[tid] = 0;
    if (tid < 16) ctrl[tid] = 0;
    if (tid >= 256 && tid < 256 + 240) {
        const int i = tid - 256;
        asm volatile("prefetch.global.L2 [%0];" ::"l"(i < 48 ? (const uint8_t*)p.wr + i * 128 : (const uint8_t*)p.w2 + (i - 48) * 128));
    }
    for (int i = P1_SEGA / 16 + tid; i < P1_SV / 16; i += NT) sts128(sb + i * 16, make_uint4(0u, 0u, 0u, 0u));
    for (int i = tid; i < 4 * (MAX_NPC - nnodes) * 8; i += NT)
        sts128(sb + P1_SV + (i / ((MAX_NPC - nnodes) * 8)) * (MAX_NPC * 128) + nnodes * 128 + (i % ((MAX_NPC - nnodes) * 8)) * 16, make_uint4(0u, 0u, 0u, 0u));
    __syncthreads();

    mbar_wait(bar_pos, 0);
    if (s4[0].x == 0x7fffffff) ctrl[15] = 1;
    for (int i = tid; i < nnodes * 32; i += NT) {
        const int r = i >> 5, b = (i >> 3) & 3, c = i & 7;
        cp_async16(sb + P1_SV + b * (MAX_NPC * 128) + r * 128 + ((c ^ (r & 7)) << 4), (const uint8_t*)p.sv + (size_t)node0 * 512 + i * 16);
    }
    for (int i = tid; i < 1024; i += NT) {
        const int m = i >> 9, k = (i >> 3) & 63, c = i & 7;
        cp_async16(sb + P1_W1 + m * 8192 + k * 128 + ((c ^ (k & 7)) << 4),
                   m == 0 ? (const uint8_t*)p.w1 + k * 128 + c * 16 : (const uint8_t*)p.w2 + k * 384 + 128 + c * 16);
    }
    asm volatile("cp.async.commit_group;" ::: "memory");
    STAMP(1);
#pragma unroll
    for (int k = 0; k < 3; k++) {
        const int ss[4] = {s4[k].x, s4[k].y, s4[k].z, s4[k].w};
        const int dd[4] = {d4[k].x, d4[k].y, d4[k].z, d4[k].w};
        if (ss[0] >= 0) {
            uint32_t w0[4], w1[4], v0[4], v1[4], r0[4], r1[4], r2[4], bin[4], rank[4];
#pragma unroll
            for (int j = 0; j < 4; j++) {
                const uint32_t a = (sb + P1_POS + 6u * (uint32_t)ss[j]) & ~3u, c = (sb + P1_POS + 6u * (uint32_t)dd[j]) & ~3u;
                w0[j] = lds32(a); w1[j] = lds32(a + 4); v0[j] = lds32(c); v1[j] = lds32(c + 4);
            }
#pragma unroll
            for (int j = 0; j < 4; j++) {
                const uint32_t sh = (uint32_t)ss[j] << 4, dh = (uint32_t)dd[j] << 4;
                uint32_t rxy, rz;
                const uint32_t db = edge_dist(__funnelshift_r(w0[j], w1[j], sh), __funnelshift_r(w1[j], w1[j], sh),
                                              __funnelshift_r(v0[j], v1[j], dh), __funnelshift_r(v1[j], v1[j], dh), rxy, rz);
                float inv;
                asm("rcp.approx.ftz.f32 %0, %1;" : "=f"(inv) : "f"(__uint_as_float(db << 16)));
                bin[j] = __umulhi((uint32_t)dd[j], p.npc_magic);
                r0[j] = (uint32_t)ss[j] | ((db - D_MIN_BITS) << 16);
                r1[j] = pack_bf(bf_lo(rxy) * inv, bf_hi(rxy) * inv);
                r2[j] = __byte_perm(pack_bf(bf_lo(rz) * inv, 0.f), (uint32_t)dd[j] - bin[j] * (uint32_t)p.npc, 0x5410);
                rank[j] = db <= D_MAX_BITS ? (uint32_t)atomicAdd(&binCnt[bin[j]], 1) : 0xffffu;
            }
#pragma unroll
            for (int j = 0; j < 4; j++) {
                if (rank[j] < SEG_CAP) {
                    const uint32_t slot = bin[j] * SEG_CAP + rank[j];
                    asm volatile("st.shared.v2.u32 [%0], {%1, %2};" ::"r"(sb + P1_SEGA + slot * 8), "r"(r0[j]), "r"(r1[j]) : "memory");
                    sts32(sb + P1_SEGB + slot * 4, r2[j]);
                }
            }
        }
    }
    __syncthreads();
    STAMP(2);
    {
        constexpr int IT = (MAX_CTA + 31) / 32;
        uint2 ca[IT][2];
        uint32_t cb[IT][2];
        int cn[IT];
#pragma unroll
        for (int it = 0; it < IT; it++) {
            const int b = min(2 * warp + (lane >> 4) + 32 * it, MAX_CTA - 1);
            cn[it] = binCnt[b];
#pragma unroll
            for (int u = 0; u < 2; u++) {
                const int j = (lane & 15) + 16 * u;
                ca[it][u] = lds64(sb + P1_SEGA + (b * SEG_CAP + j) * 8);
                cb[it][u] = lds32(sb + P1_SEGB + (b * SEG_CAP + j) * 4);
            }
        }
#pragma unroll
        for (int it = 0; it < IT; it++) {
            const int b = 2 * warp + (lane >> 4) + 32 * it;
            if (b < p.ncta) {
                uint32_t* dstp = g_seg + ((size_t)cta * MAX_CTA + b) * (SEG_CAP * 3);
                const uint32_t tag = (uint32_t)min(cn[it], 511) << 23;
#pragma unroll
                for (int u = 0; u < 2; u++) {
                    const int j = (lane & 15) + 16 * u;
                    *(uint2*)(dstp + 2 * j) = ca[it][u];
                    dstp[2 * SEG_CAP + j] = cb[it][u] | tag;
                }
                for (int j = 32 + (lane & 15); j < ((min(cn[it], SEG_CAP) + 7) & ~7); j += 16) {
                    *(uint2*)(dstp + 2 * j) = lds64(sb + P1_SEGA + (b * SEG_CAP + j) * 8);
                    dstp[2 * SEG_CAP + j] = lds32(sb + P1_SEGB + (b * SEG_CAP + j) * 4);
                }
            }
        }
    }
    STAMP(7);
    asm volatile("cp.async.wait_group 0;" ::: "memory");
    __syncthreads();
    STAMP(3);
    if (tid == 64) asm volatile("red.add.release.gpu.global.u32 [%0], 1;" ::"l"(&g_bar[0]) : "memory");

    if (!mlp_warp) {
        const int rows_per = (TAB_ROWS + 1 + p.ncta - 1) / p.ncta;
        for (int i = tid; i < rows_per * 8; i += 6 * 32) {
            int row = cta * rows_per + (i >> 3), kp = i & 7;
            if (row <= TAB_ROWS) {
                uint32_t val = 0;
                if (row < TAB_ROWS) {
                    float d = __uint_as_float((D_MIN_BITS + row) << 16);
                    uint32_t f2 = __ldg((const uint32_t*)p.freqs + kp);
                    val = pack_bf(radial_value(d, bf_lo(f2)), radial_value(d, bf_hi(f2)));
                }
                ((uint32_t*)g_table)[row * 8 + kp] = val;
            }
        }
    } else {
        const int mt = (warp - 6) >> 1, hf = (warp - 6) & 1;
        if (mt * 16 < nnodes) {
            STAMPT(10, 6 * 32);
            const int lrow = lane & 15, lch = lane >> 4;
            const uint32_t rowb = sb + P1_SV + (mt * 16 + lrow) * 128;
            const uint32_t key0 = lrow & 7;
            float acc[4][4];
#pragma unroll
            for (int i = 0; i < 4; i++) { acc[i][0] = acc[i][1] = acc[i][2] = acc[i][3] = 0.f; }
#pragma unroll
            for (int ks = 0; ks < 4; ks++) {
                uint32_t a[4];
                ldsm4(a, rowb + (((2 * ks + lch) ^ key0) << 4));
                const int kk = 16 * ks + lrow;
#pragma unroll
                for (int nt = 0; nt < 4; nt += 2) {
                    uint32_t b[4];
                    ldsm4t(b, sb + P1_W1 + kk * 128 + (((4 * hf + nt + lch) ^ (kk & 7)) << 4));
                    mma16816(acc[nt], a, b[0], b[1]);
                    mma16816(acc[nt + 1], a, b[2], b[3]);
                }
            }
            uint32_t hp[4][2];
#pragma unroll
            for (int i = 0; i < 4; i++) {
                float h[4];
#pragma unroll
                for (int q = 0; q < 4; q++) {
                    float x = rbf(acc[i][q]);
                    h[q] = __fdividef(x, 1.0f + __expf(-x));
                    acc[i][q] = 0.f;
                }
                hp[i][0] = pack_bf(h[0], h[1]);
                hp[i][1] = pack_bf(h[2], h[3]);
            }
            asm volatile("bar.sync %0, 64;" ::"r"(4 + mt) : "memory");
#pragma unroll
            for (int i = 0; i < 4; i += 2)
                stsm4(rowb + (((4 * hf + i + lch) ^ key0) << 4), hp[i][0], hp[i][1], hp[i + 1][0], hp[i + 1][1]);
            asm volatile("bar.sync %0, 64;" ::"r"(4 + mt) : "memory");
#pragma unroll
            for (int ks = 0; ks < 4; ks++) {
                uint32_t a[4];
                ldsm4(a, rowb + (((2 * ks + lch) ^ key0) << 4));
                const int kk = 16 * ks + lrow;
#pragma unroll
                for (int nt = 0; nt < 4; nt += 2) {
                    uint32_t b[4];
                    ldsm4t(b, sb + P1_W2 + kk * 128 + (((4 * hf + nt + lch) ^ (kk & 7)) << 4));
                    mma16816(acc[nt], a, b[0], b[1]);
                    mma16816(acc[nt + 1], a, b[2], b[3]);
                }
            }
            uint32_t vq[2][3][4];
            const uint32_t vb = sb + P1_SV + (mt * 16 + g) * 128 + 4 * t;
#pragma unroll
            for (int rh = 0; rh < 2; rh++)
#pragma unroll
                for (int a = 0; a < 3; a++)
#pragma unroll
                    for (int i = 0; i < 4; i++) vq[rh][a][i] = lds32(vb + (a + 1) * (MAX_NPC * 128) + rh * 1024 + (((4 * hf + i) ^ g) << 4));
#pragma unroll
            for (int rh = 0; rh < 2; rh++)
#pragma unroll
                for (int a = 0; a < 3; a++)
#pragma unroll
                    for (int i = 0; i < 4; i++)
                        sts32(vb + (a + 1) * (MAX_NPC * 128) + rh * 1024 + (((4 * hf + i) ^ g) << 4),
                              hmul2(pack_bf(acc[i][2 * rh], acc[i][2 * rh + 1]), vq[rh][a][i]));
            fence_async_smem();
            asm volatile("bar.sync %0, 64;" ::"r"(4 + mt) : "memory");
            {
                const int r4 = mt * 16 + 8 * hf + 4 * (lane >> 2), comp = lane & 3;
                if (lane < 8 && r4 < nnodes) tma_store3(&tmFs, comp, node0 + r4, sb + P1_SV + comp * (MAX_NPC * 128) + r4 * 128);
            }
            asm volatile("cp.async.bulk.commit_group;" ::: "memory");
        }
        STAMPT(11, 6 * 32);
    }
    if (tid == 0) {
        const unsigned target = (bar_seen / (unsigned)p.ncta + 1u) * (unsigned)p.ncta;
        unsigned cur;
        int spins = 0;
        do {
            asm volatile("ld.acquire.gpu.global.u32 %0, [%1];" : "=r"(cur) : "l"(&g_bar[0]) : "memory");
        } while ((int)(cur - target) < 0 && ++spins < (1 << 24));
    }
    STAMP(4);
    __syncthreads();
    STAMP(5);

    constexpr int SEG_IT = (MAX_CTA + 31) / 32;
    uint2 ra[SEG_IT][2];
    uint32_t rb[SEG_IT][2], rr[SEG_IT][2];
#pragma unroll
    for (int it = 0; it < SEG_IT; it++) {
        const int b = 2 * warp + (lane >> 4) + 32 * it;
        const uint32_t* sp = g_seg + ((size_t)b * MAX_CTA + cta) * (SEG_CAP * 3);
#pragma unroll
        for (int u = 0; u < 2; u++) {
            const int j = (lane & 15) + 16 * u;
            ra[it][u] = b < p.ncta ? __ldcg((const uint2*)(sp + 2 * j)) : make_uint2(0u, 0u);
            rb[it][u] = b < p.ncta ? __ldcg(sp + 2 * SEG_CAP + j) : 0u;
        }
    }
    if (mlp_warp && lane < 8) {
        asm volatile("cp.async.bulk.wait_group 0;" ::: "memory");
        asm volatile("fence.proxy.async;" ::: "memory");
    }
    STAMP(9);
    uint2 xa[SEG_IT];
    uint32_t xb[SEG_IT];
#pragma unroll
    for (int it = 0; it < SEG_IT; it++) {
        const int cnt = rb[it][0] >> 23;
        const int b = 2 * warp + (lane >> 4) + 32 * it;
        const uint32_t* sp = g_seg + ((size_t)b * MAX_CTA + cta) * (SEG_CAP * 3);
        const bool has = 32 + (lane & 15) < cnt;
        xa[it] = has ? __ldcg((const uint2*)(sp + 2 * (32 + (lane & 15)))) : make_uint2(0u, 0u);
        xb[it] = has ? __ldcg(sp + 2 * SEG_CAP + 32 + (lane & 15)) : 0u;
    }
#pragma unroll
    for (int it = 0; it < SEG_IT; it++) {
        const int cnt = rb[it][0] >> 23;
        if (cnt > SEG_CAP) ctrl[1] = 1;
#pragma unroll
        for (int u = 0; u < 2; u++)
            rr[it][u] = (lane & 15) + 16 * u < cnt ? (uint32_t)atomicAdd(&nCnt[(rb[it][u] >> 16) & 0x7fu], 1) : 0xffffffffu;
    }
#pragma unroll
    for (int it = 0; it < SEG_IT; it++) {
        const int cnt = rb[it][0] >> 23;
        if (32 + (lane & 15) < cnt) {
            const int pos = atomicAdd((int*)&ctrl[8], 1);
            const uint32_t rank = (uint32_t)atomicAdd(&nCnt[(xb[it] >> 16) & 0x7fu], 1);
            if (pos < STAGE_CAP) sts128(sb + P1_REC + pos * 16, make_uint4(xa[it].x, xa[it].y, xb[it], rank));
        }
        if (cnt > 48) {
            const int b = 2 * warp + (lane >> 4) + 32 * it;
            const uint32_t* sp = g_seg + ((size_t)b * MAX_CTA + cta) * (SEG_CAP * 3);
            const int j = 48 + (lane & 15);
            if (j < min(cnt, SEG_CAP)) {
                const uint2 a = __ldcg((const uint2*)(sp + 2 * j));
                const uint32_t c = __ldcg(sp + 2 * SEG_CAP + j);
                const int pos = atomicAdd((int*)&ctrl[8], 1);
                const uint32_t rank = (uint32_t)atomicAdd(&nCnt[(c >> 16) & 0x7fu], 1);
                if (pos < STAGE_CAP) sts128(sb + P1_REC + pos * 16, make_uint4(a.x, a.y, c, rank));
            }
        }
    }
    STAMP(13);
    __syncthreads();
    if (tid == 64) asm volatile("red.add.release.gpu.global.u32 [%0], 1;" ::"l"(&g_bar[1]) : "memory");
    STAMP(14);
    const int total = ctrl[8];
    if (tid == 0 && total > STAGE_CAP) ctrl[1] = 1;
    if (warp == 0) {
        int c[3], s = 0;
#pragma unroll
        for (int i = 0; i < 3; i++) {
            int b = lane * 3 + i;
            c[i] = b < nnodes ? max(16, (nCnt[b] + 15) & ~15) : 0;
            s += c[i];
        }
        int x = s;
#pragma unroll
        for (int o = 1; o < 32; o <<= 1) { int y = __shfl_up_sync(0xffffffffu, x, o); if (lane >= o) x += y; }
        const int slots = __shfl_sync(0xffffffffu, x, 31);
        int off = x - s, below = 0;
#pragma unroll
        for (int i = 0; i < 3; i++) {
            int b = lane * 3 + i;
            if (b < nnodes) {
                nInfo[b] = (uint32_t)off | ((uint32_t)c[i] << 16);
                below += (2 * off + c[i] < slots);
            }
            off += c[i];
        }
        below = __reduce_add_sync(0xffffffffu, below);
        if (lane == 0) {
            ctrl[2] = below;
            ctrl[4] = slots;
            if (slots > SLOT_CAP) ctrl[1] = 1;
        }
    }
    __syncthreads();
    if (ctrl[1] == 0) {
        uint16_t* sid = (uint16_t*)(smem + SM_SID);
        uint2* meta = (uint2*)(smem + SM_META);
#pragma unroll
        for (int it = 0; it < SEG_IT; it++)
#pragma unroll
            for (int u = 0; u < 2; u++)
                if (rr[it][u] != 0xffffffffu) rr[it][u] += lds32(sb + SM_NINFO + ((rb[it][u] >> 16) & 0x7fu) * 4) & 0xffffu;
#pragma unroll
        for (int it = 0; it < SEG_IT; it++)
#pragma unroll
            for (int u = 0; u < 2; u++)
                if (rr[it][u] != 0xffffffffu) {
                    sid[rr[it][u]]  = (uint16_t)((ra[it][u].x & 0xffffu) << 2);
                    meta[rr[it][u]] = make_uint2(((ra[it][u].x >> 16) << 5) | (rb[it][u] << 16), ra[it][u].y);
                }
        for (int i = tid; i < total; i += NT) {
            const uint4 r = lds128(sb + P1_REC + i * 16);
            const int pos = (int)(lds32(sb + SM_NINFO + ((r.z >> 16) & 0x7fu) * 4) & 0xffffu) + (int)r.w;
            sid[pos]  = (uint16_t)((r.x & 0xffffu) << 2);
            meta[pos] = make_uint2(((r.x >> 16) << 5) | (r.z << 16), r.y);
        }
        if (tid >= NT - 128 && tid - (NT - 128) < nnodes) {
            const int b = tid - (NT - 128), split = ctrl[2];
            const int mid = split < nnodes ? (int)(nInfo[split] & 0xffffu) : ctrl[4];
            const int st = b >= split;
            const int mine = (int)(nInfo[b] & 0xffffu) + (int)(nInfo[b] >> 16) - (st ? mid : 0);
            int lo = st ? 0 : split, hi = st ? split : nnodes;
            const int first = lo;
            while (lo < hi) {
                const int o = (lo + hi) >> 1;
                const int other = (int)(nInfo[o] & 0xffffu) + (int)(nInfo[o] >> 16) - (st ? 0 : mid);
                if (st ? (other <= mine) : (other < mine)) lo = o + 1; else hi = o;
            }
            const int rank = (st ? b - split : b) + lo - first;
            smem[SM_ORDER + rank] = (uint8_t)(b | (st << 7));
        }
        for (int i = tid; i < nnodes * 16; i += NT) {
            int nl = i >> 4, c = nCnt[nl];
            int j = (c & ~15) + (i & 15);
            if (j >= c && (j < 16 || (c & 15))) {
                int pos = (int)(nInfo[nl] & 0xffffu) + j;
                sid[pos]  = 0xffffu;
                meta[pos] = make_uint2((uint32_t)TAB_ZERO << 5, 0u);
            }
        }
    }
    STAMP(15);
    if (tid == 32) {
        const unsigned target = (bar_seen / (unsigned)p.ncta + 1u) * (unsigned)p.ncta;
        unsigned cur;
        int spins = 0;
        do {
            asm volatile("ld.acquire.gpu.global.u32 %0, [%1];" : "=r"(cur) : "l"(&g_bar[1]) : "memory");
        } while ((int)(cur - target) < 0 && ++spins < (1 << 24));
        asm volatile("fence.proxy.async.global;" ::: "memory");
    }
    fence_async_smem();
    __syncthreads();
    STAMP(6);

    if (__shfl_sync(0xffffffffu, ctrl[1], 0) != 0) {
        float* acc = (float*)(smem + P1_POS);
        for (int i = tid; i < nnodes * 256; i += NT) acc[i] = 0.f;
        __syncthreads();
        const uint16_t* posu = (const uint16_t*)p.pos;
        const uint32_t* tabg = (const uint32_t*)g_table;
        const uint32_t* Fw = (const uint32_t*)g_F;
        for (int e0 = warp * 32; e0 < p.E; e0 += NT) {
            int e = e0 + lane;
            int s = 0, d = 0;
            uint32_t db = 0xffff, rxy = 0, rz = 0;
            bool act = false;
            if (e < p.E) {
                s = p.src[e]; d = p.dst[e];
                if (d >= node0 && d < node0 + nnodes) {
                    uint32_t sxy = posu[s * 3] | ((uint32_t)posu[s * 3 + 1] << 16), sz = posu[s * 3 + 2];
                    uint32_t dxy = posu[d * 3] | ((uint32_t)posu[d * 3 + 1] << 16), dz = posu[d * 3 + 2];
                    db  = edge_dist(sxy, sz, dxy, dz, rxy, rz);
                    act = db <= D_MAX_BITS;
                }
            }
            unsigned m = __ballot_sync(0xffffffffu, act);
            while (m) {
                int l = __ffs(m) - 1;
                m &= m - 1;
                int es = __shfl_sync(0xffffffffu, s, l), ed = __shfl_sync(0xffffffffu, d, l);
                uint32_t edb = __shfl_sync(0xffffffffu, db, l), exy = __shfl_sync(0xffffffffu, rxy, l), ez = __shfl_sync(0xffffffffu, rz, l);
                float inv = 1.0f / __uint_as_float(edb << 16);
                float rh[3] = {rbf(bf_lo(exy) * inv), rbf(bf_hi(exy) * inv), rbf(bf_lo(ez) * inv)};
                const uint32_t* fr = Fw + (size_t)es * 128 + lane;
                const uint32_t fh = __ldcg(fr);
                const uint32_t q[3] = {__ldcg(fr + 32), __ldcg(fr + 64), __ldcg(fr + 96)};
                float ps0 = 0.f, ps1 = 0.f, pr0 = 0.f, pr1 = 0.f;
                for (int j2 = 0; j2 < 32; j2++) {
                    uint32_t hj = __shfl_sync(0xffffffffu, fh, j2);
                    uint32_t a0 = *(const uint32_t*)(p.w2 + (2 * j2) * 192 + 2 * lane), a1 = *(const uint32_t*)(p.w2 + (2 * j2 + 1) * 192 + 2 * lane);
                    uint32_t b0 = *(const uint32_t*)(p.w2 + (2 * j2) * 192 + 128 + 2 * lane), b1 = *(const uint32_t*)(p.w2 + (2 * j2 + 1) * 192 + 128 + 2 * lane);
                    ps0 += bf_lo(hj) * bf_lo(a0) + bf_hi(hj) * bf_lo(a1);
                    ps1 += bf_lo(hj) * bf_hi(a0) + bf_hi(hj) * bf_hi(a1);
                    pr0 += bf_lo(hj) * bf_lo(b0) + bf_hi(hj) * bf_lo(b1);
                    pr1 += bf_lo(hj) * bf_hi(b0) + bf_hi(hj) * bf_hi(b1);
                }
                float ws0 = 0.f, ws1 = 0.f, wv0 = 0.f, wv1 = 0.f, wr0 = 0.f, wr1 = 0.f;
                for (int k2 = 0; k2 < 8; k2++) {
                    uint32_t rk2 = __ldcg(tabg + (edb - D_MIN_BITS) * 8 + k2);
#pragma unroll
                    for (int h = 0; h < 2; h++) {
                        float rv = h ? bf_hi(rk2) : bf_lo(rk2);
                        const __nv_bfloat16* wrow = p.wr + (2 * k2 + h) * 192 + 2 * lane;
                        uint32_t a = *(const uint32_t*)wrow, b = *(const uint32_t*)(wrow + 64), c = *(const uint32_t*)(wrow + 128);
                        ws0 += rv * bf_lo(a); ws1 += rv * bf_hi(a);
                        wv0 += rv * bf_lo(b); wv1 += rv * bf_hi(b);
                        wr0 += rv * bf_lo(c); wr1 += rv * bf_hi(c);
                    }
                }
                float* a = acc + (ed - node0) * 256 + 2 * lane;
                atomicAdd(a, ps0 * ws0); atomicAdd(a + 1, ps1 * ws1);
#pragma unroll
                for (int c = 0; c < 3; c++) {
                    atomicAdd(a + 64 * (c + 1), wv0 * bf_lo(q[c]) + pr0 * wr0 * rh[c]);
                    atomicAdd(a + 64 * (c + 1) + 1, wv1 * bf_hi(q[c]) + pr1 * wr1 * rh[c]);
                }
            }
        }
        __syncthreads();
        for (int i = tid; i < nnodes * 128; i += NT) {
            uint32_t r = *(const uint32_t*)(p.sv + (size_t)node0 * 256 + 2 * i);
            *(uint32_t*)(p.out + (size_t)node0 * 256 + 2 * i) = pack_bf(bf_lo(r) + acc[2 * i], bf_hi(r) + acc[2 * i + 1]);
        }
        return;
    }

    const int slots = __reduce_max_sync(0xffffffffu, ctrl[4]);
    const int split = __reduce_max_sync(0xffffffffu, ctrl[2]);
    constexpr int nstage = MAX_STAGE;
    const uint32_t ring = sb + SM_RING;
    const int mid = __reduce_max_sync(0xffffffffu, split < nnodes ? (int)(nInfo[split] & 0xffffu) : slots) >> 4;
    const int wgi = warp >> 2, w = warp & 3;
    uint32_t wp[3][4];
    if (wgi < 3) {
        const uint16_t* wr = (const uint16_t*)p.wr + 16 * w + g;
#pragma unroll
        for (int ty = 0; ty < 3; ty++) {
#pragma unroll
            for (int i = 0; i < 4; i++) {
                const uint16_t* q = wr + (8 * (i >> 1) + 2 * t) * 192 + ty * 64 + 8 * (i & 1);
                wp[ty][i] = (uint32_t)__ldg(q) | ((uint32_t)__ldg(q + 192) << 16);
            }
        }
    }
    constexpr uint32_t EMPTY_OFF = NCWG * MAX_STAGE * 8;
    if (wgi == 3) {
        const int sc = w >> 1, r = w & 1;
        const int g0 = (sc == 0 ? 0 : mid) + r, g1 = sc == 0 ? mid : slots >> 4;
        const uint32_t ring_wg = ring + sc * nstage * STAGE_B, full_wg = bar_full + sc * MAX_STAGE * 8;
        const int e = lane >> 1, half = lane & 1;
        const uint32_t coef_off = e * 128 + ((half ^ (e & 7)) << 4);
        const int vrot = (e & 3) ^ ((e >> 1) & 3);
        const uint8_t* tab = (const uint8_t*)g_table + half * 16;
        int stage = r;
        uint32_t phase = 1;
        uint32_t ma = sb + SM_META + (g0 * 16 + e) * 8, ida = sb + SM_SID + g0 * 32;
        uint2 m = make_uint2(0u, 0u);
        uint4 tv = make_uint4(0u, 0u, 0u, 0u), ia = tv, ib = tv;
        if (g0 < g1) {
            m  = lds64(ma);
            ia = lds128(ida);
            ib = lds128(ida + 16);
            tv = __ldg((const uint4*)(tab + (m.x & 0xffffu)));
        }
        for (int left = (g1 - g0 + 1) >> 1; left > 0; left--) {
            const uint32_t st = ring_wg + stage * STAGE_B, fb = full_wg + stage * 8;
            ma += 256; ida += 64;
            uint2 mn = m;
            if (left > 1) mn = lds64(ma);
            mbar_wait(fb + EMPTY_OFF, phase);
            uint32_t leader;
            asm volatile("{\n.reg .pred p;\nelect.sync _|p, 0xffffffff;\nselp.u32 %0, 1, 0, p;\n}" : "=r"(leader));
            if (leader) {
                const uint32_t id2[8] = {ia.x, ia.y, ia.z, ia.w, ib.x, ib.y, ib.z, ib.w};
                const uint32_t rows = st + 2048;
                if ((ib.w >> 16) != 0xffffu) {
                    mbar_expect_tx(fb, 16 * 512);
#pragma unroll
                    for (int i = 0; i < 8; i++) {
                        tma_load(rows + (2 * i) * 640, &tmF, (int)(id2[i] & 0xffffu), fb);
                        tma_load(rows + (2 * i + 1) * 640, &tmF, (int)(id2[i] >> 16), fb);
                    }
                } else {
                    int nv = 0;
#pragma unroll
                    for (int i = 0; i < 8; i++) nv += ((id2[i] & 0xffffu) != 0xffffu) + ((id2[i] >> 16) != 0xffffu);
                    mbar_expect_tx(fb, (uint32_t)nv * 512u);
#pragma unroll
                    for (int q = 0; q < 4; q++) {
                        if (4 * q + 4 <= nv) {
                            tma_load(rows + (4 * q) * 640, &tmF, (int)(id2[2 * q] & 0xffffu), fb);
                            tma_load(rows + (4 * q + 1) * 640, &tmF, (int)(id2[2 * q] >> 16), fb);
                            tma_load(rows + (4 * q + 2) * 640, &tmF, (int)(id2[2 * q + 1] & 0xffffu), fb);
                            tma_load(rows + (4 * q + 3) * 640, &tmF, (int)(id2[2 * q + 1] >> 16), fb);
                        } else {
                            if (4 * q < nv)     tma_load(rows + (4 * q) * 640, &tmF, (int)(id2[2 * q] & 0xffffu), fb);
                            if (4 * q + 1 < nv) tma_load(rows + (4 * q + 1) * 640, &tmF, (int)(id2[2 * q] >> 16), fb);
                            if (4 * q + 2 < nv) tma_load(rows + (4 * q + 2) * 640, &tmF, (int)(id2[2 * q + 1] & 0xffffu), fb);
                        }
                    }
                }
            }
            __syncwarp();
            uint4 o[4];
            {
                const uint32_t mul[4] = {0x3f803f80u, __byte_perm(m.y, 0, 0x1010), __byte_perm(m.y, 0, 0x3232), __byte_perm(m.x, 0, 0x3232)};
#pragma unroll
                for (int j = 0; j < 4; j++) {
                    const int v = j ^ vrot;
                    const uint32_t lo = (v & 1) ? mul[1] : mul[0], hi = (v & 1) ? mul[3] : mul[2];
                    const uint32_t mm = (v & 2) ? hi : lo;
                    o[j] = make_uint4(hmul2(tv.x, mm), hmul2(tv.y, mm), hmul2(tv.z, mm), hmul2(tv.w, mm));
                }
            }
            m = mn;
            if (left > 1) {
                ia = lds128(ida);
                ib = lds128(ida + 16);
                tv = __ldg((const uint4*)(tab + (m.x & 0xffffu)));
            }
            const uint32_t a = st + coef_off;
#pragma unroll
            for (int j = 0; j < 4; j++) sts128(a ^ ((j ^ vrot) << 5), o[j]);
            fence_async_smem();
            __syncwarp();
            mbar_arrive_elected(fb);
            stage += 2;
            if (stage >= nstage) { stage -= nstage; phase ^= 1; }
        }
    } else if (wgi == 2) {
        uint32_t wA[2][4][4];
        {
            const uint16_t* w2 = (const uint16_t*)p.w2 + 16 * w + g;
#pragma unroll
            for (int mk = 0; mk < 8; mk++) {
#pragma unroll
                for (int i = 0; i < 4; i++) {
                    const uint16_t* q = w2 + (16 * (mk & 3) + 2 * t + 8 * (i >> 1)) * 192 + (mk >> 2) * 128 + 8 * (i & 1);
                    wA[mk >> 2][mk & 3][i] = (uint32_t)__ldg(q) | ((uint32_t)__ldg(q + 192) << 16);
                }
            }
        }
        const uint32_t lane_off = (uint32_t)node0 * 512u + t * 128 + w * 32 + (g & 1) * 16 + (g >> 1) * 4;
        uint32_t hcnt[2] = {0u, 0u};
        float zs[8], zv[24], pvv[6], pr[4][2];
        uint32_t hbuf = 0;
        auto start = [&](int ent) {
            const int c = ent >> 7;
            const uint32_t k = c ? hcnt[1] : hcnt[0];
            hbuf = 2 * c + (k & 1);
            mbar_wait(bar_hfull + hbuf * 8, (k >> 1) & 1);
            if (c) hcnt[1]++; else hcnt[0]++;
            const uint32_t dht = desc_lo(sb + SM_HT + hbuf * 8192);
            wg_fence();
            wgmma_n16_first(zs, wA[0][0], dht);
            wgmma_n48_first(zv, wA[1][0], dht + 2);
#pragma unroll
            for (int ks = 1; ks < 4; ks++) {
                wgmma_n16(zs, wA[0][ks], dht + ks * 128);
                wgmma_n48(zv, wA[1][ks], dht + ks * 128 + 2);
            }
            wg_commit();
        };
        auto side = [&](int ent) {
            const uint32_t pa = sb + SM_PV + hbuf * 1536 + (tid & 127) * 4;
            const uint32_t a0 = lds32(pa), a1 = lds32(pa + 512), a2 = lds32(pa + 1024);
            pvv[0] = bf_lo(a0); pvv[1] = bf_hi(a0); pvv[2] = bf_lo(a1); pvv[3] = bf_hi(a1); pvv[4] = bf_lo(a2); pvv[5] = bf_hi(a2);
            __syncwarp();
            mbar_arrive_elected(bar_hempty + hbuf * 8);
        };
        auto weigh = [&]() {
#pragma unroll
            for (int i = 0; i < 12; i++) asm volatile("" : "+r"(wp[i >> 2][i & 3]));
            pr[0][0] = bf_lo(wp[0][0]) * zs[0] + bf_hi(wp[0][0]) * zs[1] + bf_lo(wp[0][2]) * zs[4] + bf_hi(wp[0][2]) * zs[5];
            pr[0][1] = bf_lo(wp[0][1]) * zs[2] + bf_hi(wp[0][1]) * zs[3] + bf_lo(wp[0][3]) * zs[6] + bf_hi(wp[0][3]) * zs[7];
#pragma unroll
            for (int a = 0; a < 3; a++) {
                const float* y = zv + 8 * a;
                pr[a + 1][0] = pvv[2 * a] + bf_lo(wp[2][0]) * y[0] + bf_hi(wp[2][0]) * y[1] + bf_lo(wp[2][2]) * y[4] + bf_hi(wp[2][2]) * y[5];
                pr[a + 1][1] = pvv[2 * a + 1] + bf_lo(wp[2][1]) * y[2] + bf_hi(wp[2][1]) * y[3] + bf_lo(wp[2][3]) * y[6] + bf_hi(wp[2][3]) * y[7];
            }
            asm volatile("" : "+f"(pr[0][0]), "+f"(pr[0][1]), "+f"(pr[1][0]), "+f"(pr[1][1]), "+f"(pr[2][0]), "+f"(pr[2][1]), "+f"(pr[3][0]), "+f"(pr[3][1]) :: "memory");
        };
        auto finish = [&](int ent, uint32_t resid) {
            const bool hi2 = t & 2, hi1 = t & 1, odd = g & 1;
            float ka0 = hi2 ? pr[2][0] : pr[0][0], ka1 = hi2 ? pr[2][1] : pr[0][1];
            float kb0 = hi2 ? pr[3][0] : pr[1][0], kb1 = hi2 ? pr[3][1] : pr[1][1];
            float sa0 = hi2 ? pr[0][0] : pr[2][0], sa1 = hi2 ? pr[0][1] : pr[2][1];
            float sb0 = hi2 ? pr[1][0] : pr[3][0], sb1 = hi2 ? pr[1][1] : pr[3][1];
            ka0 += __shfl_xor_sync(0xffffffffu, sa0, 2); ka1 += __shfl_xor_sync(0xffffffffu, sa1, 2);
            kb0 += __shfl_xor_sync(0xffffffffu, sb0, 2); kb1 += __shfl_xor_sync(0xffffffffu, sb1, 2);
            float k0 = hi1 ? kb0 : ka0, k1 = hi1 ? kb1 : ka1;
            float s0 = hi1 ? ka0 : kb0, s1 = hi1 ? ka1 : kb1;
            k0 += __shfl_xor_sync(0xffffffffu, s0, 1);
            k1 += __shfl_xor_sync(0xffffffffu, s1, 1);
            const float other = __shfl_xor_sync(0xffffffffu, odd ? k0 : k1, 4);
            const float lo = odd ? other : k0, hi = odd ? k1 : other;
            *(uint32_t*)((uint8_t*)p.out + (lane_off + (uint32_t)(ent & 127) * 512u)) = pack_bf(bf_lo(resid) + lo, bf_hi(resid) + hi);
        };
        auto entry = [&](int i) -> int { return __reduce_max_sync(0xffffffffu, (int)smem[SM_ORDER + i]); };
        auto load_resid = [&](int ent) -> uint32_t { return __ldg((const uint32_t*)((const uint8_t*)p.sv + (lane_off + (uint32_t)(ent & 127) * 512u))); };
        if (nnodes > 0) {
            int cur = entry(0), nxt = entry(1);
            uint32_t resid = load_resid(cur);
            start(cur);
#pragma unroll 1
            for (int i = 1; i < nnodes; i++) {
                wg_wait0();
                side(cur);
                weigh();
                start(nxt);
                finish(cur, resid);
                cur = nxt;
                resid = load_resid(cur);
                nxt = entry(i + 1);
            }
            wg_wait0();
            side(cur);
            weigh();
            finish(cur, resid);
        }
    } else {
        const int wg = wgi;
        uint32_t aoff[4];
        {
            const int e = (lane & 7) + 8 * (lane >> 4), ch = 2 * w + ((lane >> 3) & 1);
#pragma unroll
            for (int b = 0; b < 4; b++) aoff[b] = 2048 + e * 640 + b * 128 + ((ch ^ ((5 * e + b) & 7)) << 4);
        }
        const uint32_t stsm_0 = sb + SM_HT + wg * 16384 + (16 * w + (lane & 15)) * 128 + (((lane >> 4) ^ (lane & 7)) << 4);
        const uint32_t pv_0 = sb + SM_PV + wg * 3072 + (tid & 127) * 4;
        uint32_t hk = 0;
        const uint32_t ring_wg = ring + wg * nstage * STAGE_B;
        const uint32_t full_wg = bar_full + wg * MAX_STAGE * 8;

        float ys[8], yv[24], dQ[3][8];
        uint32_t A0[4][4], A1[4][4];
#pragma unroll
        for (int i = 0; i < 24; i++) yv[i] = 0.f;
#pragma unroll
        for (int i = 0; i < 8; i++) { ys[i] = 0.f; dQ[0][i] = 0.f; dQ[1][i] = 0.f; dQ[2][i] = 0.f; }
        int left = wg == 0 ? mid : (slots >> 4) - mid;
        int fstage = 0;
        uint32_t fphase = 0, fst = ring_wg, fbar = full_wg;
        uint32_t ninfo_a = sb + SM_NINFO + (wg == 0 ? 0 : split) * 4;
        int gi = 0, G = __reduce_max_sync(0xffffffffu, (int)(lds32(ninfo_a) >> 20));

        auto fetch = [&](uint32_t (&A)[4][4], uint32_t& bd, uint32_t& eb) {
            mbar_wait(fbar, fphase);
#pragma unroll
            for (int b = 0; b < 4; b++) ldsm4t(A[b], fst + aoff[b]);
            bd = desc_lo(fst);
            eb = fbar + EMPTY_OFF;
            fst += STAGE_B; fbar += 8;
            if (++fstage == nstage) { fstage = 0; fphase ^= 1; fst = ring_wg; fbar = full_wg; }
        };
        auto step = [&](uint32_t (&Ac)[4][4], uint32_t bdc, uint32_t ebc, uint32_t (&An)[4][4], uint32_t& bdn, uint32_t& ebn) {
            wg_fence();
            wgmma_n64_p(ys, yv, Ac[0], bdc, gi);
            wgmma_n16_p(dQ[0], Ac[1], bdc, gi);
            wgmma_n16_p(dQ[1], Ac[2], bdc, gi);
            wgmma_n16_p(dQ[2], Ac[3], bdc, gi);
            wg_commit();
            if (--left > 0) fetch(An, bdn, ebn);
            const bool last = ++gi == G;
            uint32_t info_next = 0;
            if (last) { ninfo_a += 4; info_next = lds32(ninfo_a); }
            wg_wait0();
            mbar_arrive_elected(ebc);
            if (last) {
                const uint32_t hb = hk & 1;
                mbar_wait(bar_hempty + (2 * wg + hb) * 8, ((hk >> 1) & 1) ^ 1);
                hk++;
                const uint32_t stsm_a = stsm_0 + hb * 8192, pv_a = pv_0 + hb * 1536;
                stsm4(stsm_a, pack_bf(ys[0], ys[1]), pack_bf(ys[2], ys[3]), pack_bf(ys[4], ys[5]), pack_bf(ys[6], ys[7]));
#pragma unroll
                for (int i = 0; i < 6; i += 2) {
                    stsm4(stsm_a ^ ((i + 2) << 4),
                          pack_bf(yv[4 * i], yv[4 * i + 1]), pack_bf(yv[4 * i + 2], yv[4 * i + 3]),
                          pack_bf(yv[4 * i + 4], yv[4 * i + 5]), pack_bf(yv[4 * i + 6], yv[4 * i + 7]));
                }
#pragma unroll
                for (int i = 0; i < 4; i++) asm volatile("" : "+r"(wp[1][i]));
#pragma unroll
                for (int a = 0; a < 3; a++) {
                    const float* q = dQ[a];
                    const float p0 = bf_lo(wp[1][0]) * q[0] + bf_hi(wp[1][0]) * q[1] + bf_lo(wp[1][2]) * q[4] + bf_hi(wp[1][2]) * q[5];
                    const float p1 = bf_lo(wp[1][1]) * q[2] + bf_hi(wp[1][1]) * q[3] + bf_lo(wp[1][3]) * q[6] + bf_hi(wp[1][3]) * q[7];
                    sts32(pv_a + a * 512, pack_bf(p0, p1));
                }
                fence_async_smem();
                __syncwarp();
                mbar_arrive_elected(bar_hfull + (2 * wg + hb) * 8);
                G = __reduce_max_sync(0xffffffffu, (int)(info_next >> 20));
                gi = 0;
            }
        };
        if (left > 0) {
            uint32_t bd0, eb0, bd1 = 0, eb1 = 0;
            fetch(A0, bd0, eb0);
            while (true) {
                step(A0, bd0, eb0, A1, bd1, eb1);
                if (left <= 0) break;
                step(A1, bd1, eb1, A0, bd0, eb0);
                if (left <= 0) break;
            }
        }
    }
    STAMP(8);
}

typedef CUresult (*EncodeFn)(CUtensorMap*, CUtensorMapDataType, cuuint32_t, void*, const cuuint64_t*, const cuuint64_t*,
                             const cuuint32_t*, const cuuint32_t*, CUtensorMapInterleave, CUtensorMapSwizzle,
                             CUtensorMapL2promotion, CUtensorMapFloatOOBfill);

void make_map(EncodeFn enc, CUtensorMap* tm, const void* base, uint64_t lines, uint32_t box) {
    cuuint64_t gd[2] = {64, lines};
    cuuint64_t gs[1] = {128};
    cuuint32_t bd[2] = {64, box};
    cuuint32_t es[2] = {1, 1};
    enc(tm, CU_TENSOR_MAP_DATA_TYPE_BFLOAT16, 2, const_cast<void*>(base), gd, gs, bd, es, CU_TENSOR_MAP_INTERLEAVE_NONE,
        CU_TENSOR_MAP_SWIZZLE_128B, CU_TENSOR_MAP_L2_PROMOTION_L2_128B, CU_TENSOR_MAP_FLOAT_OOB_FILL_NONE);
}

void make_map3(EncodeFn enc, CUtensorMap* tm, const void* base, uint64_t nodes, uint32_t box) {
    cuuint64_t gd[3] = {64, 4, nodes};
    cuuint64_t gs[2] = {128, 512};
    cuuint32_t bd[3] = {64, 1, box};
    cuuint32_t es[3] = {1, 1, 1};
    enc(tm, CU_TENSOR_MAP_DATA_TYPE_BFLOAT16, 3, const_cast<void*>(base), gd, gs, bd, es, CU_TENSOR_MAP_INTERLEAVE_NONE,
        CU_TENSOR_MAP_SWIZZLE_128B, CU_TENSOR_MAP_L2_PROMOTION_L2_128B, CU_TENSOR_MAP_FLOAT_OOB_FILL_NONE);
}

}

extern "C" void kernel_launch(void* const* d_in, const int* in_sizes, int n_in, void* d_out, int out_size) {
    (void)n_in; (void)out_size;
    static int n_sm = 0;
    static EncodeFn enc = nullptr;
    static void* f_ptr = nullptr;
    if (n_sm == 0) {
        int dev = 0;
        cudaGetDevice(&dev);
        cudaDeviceGetAttribute(&n_sm, cudaDevAttrMultiProcessorCount, dev);
        cudaFuncSetAttribute(painn_kernel, cudaFuncAttributeMaxDynamicSharedMemorySize, SM_TOTAL);
        void* fn = nullptr;
        cudaDriverEntryPointQueryResult qr;
        cudaGetDriverEntryPoint("cuTensorMapEncodeTiled", &fn, cudaEnableDefault, &qr);
        enc = (EncodeFn)fn;
        cudaGetSymbolAddress(&f_ptr, g_F);
    }
    Params p;
    p.sv    = (const __nv_bfloat16*)d_in[0];
    p.pos   = (const __nv_bfloat16*)d_in[1];
    p.src   = (const int*)d_in[2];
    p.dst   = (const int*)d_in[3];
    p.freqs = (const __nv_bfloat16*)d_in[4];
    p.w1    = (const __nv_bfloat16*)d_in[5];
    p.w2    = (const __nv_bfloat16*)d_in[6];
    p.wr    = (const __nv_bfloat16*)d_in[7];
    p.out   = (__nv_bfloat16*)d_out;
    p.N = in_sizes[1] / 3;
    p.E = in_sizes[2];
    p.ncta = n_sm < MAX_CTA ? n_sm : MAX_CTA;
    p.npc = ((p.N + p.ncta - 1) / p.ncta + 3) & ~3;
    p.npc_magic = (uint32_t)(0x100000000ull / (uint32_t)p.npc) + 1u;
    p.quads_per_cta = ((p.E >> 2) + p.ncta - 1) / p.ncta;
    if (!enc || p.N > MAX_N || p.npc > MAX_NPC || (p.E & 3) || p.quads_per_cta > MAX_ROUNDS * 32) return;

    CUtensorMap tmF, tmFs;
    make_map(enc, &tmF, f_ptr, (uint64_t)p.N * 4, 4);
    make_map3(enc, &tmFs, f_ptr, (uint64_t)p.N, 4);

    cudaLaunchConfig_t cfg = {};
    cfg.gridDim = dim3(p.ncta);
    cfg.blockDim = dim3(NT);
    cfg.dynamicSmemBytes = SM_TOTAL;
    cfg.stream = cudaStreamPerThread;
    cudaLaunchAttribute attr[1];
    attr[0].id = cudaLaunchAttributeCooperative;
        attr[0].val.cooperative = 1;
    cfg.attrs = attr;
    cfg.numAttrs = 1;
    cudaLaunchKernelEx(&cfg, painn_kernel, p, tmF, tmFs);
}
```
